```python
import torch

def _softmax(x, axis=-1):
    return torch.softmax(x, dim=axis)
def _gelu(x):
    return torch.nn.functional.gelu(x, approximate="tanh")
def _silu(x):
    return torch.nn.functional.silu(x)
def _sigmoid(x):
    return torch.sigmoid(x)
def _layernorm(x, axis=-1, eps=1e-5):
    m = x.mean(dim=axis, keepdim=True)
    v = x.var(dim=axis, keepdim=True, unbiased=False)
    return (x - m) / torch.sqrt(v + eps)
def _scatter_add(tgt, idx, src, axis=0):
    return tgt.clone().index_add_(axis, idx, src)
def _segment_sum(src, seg, n):
    out = torch.zeros((n,) + src.shape[1:], dtype=src.dtype)
    return out.index_add_(0, seg, src)
def _pad(x, pw):
    flat = tuple(v for pair in reversed(pw) for v in pair)
    return torch.nn.functional.pad(x, flat)

kernel_name = 'recurrent_scan__sliding_local_dilated__mixer_token_mlp__prompt'

def setup_inputs():

    _w = (lambda a: (lambda t: t.to(torch.bfloat16) if t.is_floating_point() else t)(torch.as_tensor(a)))
    def _A_setup():
        B, S, D = 1, 2048, 448
        return {
            "x": _w((lambda *s: torch.randn(*s, dtype=torch.bfloat16) * 0.05)(B, S, D)),
            "wqkv": _w((lambda *s: torch.randn(*s, dtype=torch.bfloat16) * 0.2)(D, 3 * D)),
            "wo": _w((lambda *s: torch.randn(*s, dtype=torch.bfloat16) * 0.2)(D, D)),
        }
    _A_in = _A_setup()

    def _B_setup():
        B, S, D, F = 1, 2048, 448, 1792
        return {
            "x": _w((lambda *s: torch.randn(*s, dtype=torch.bfloat16) * 0.05)(B, S, D)),
            "w1": _w((lambda *s: torch.randn(*s, dtype=torch.bfloat16) * 0.8)(S, F) * (S ** -0.5)),
            "b1": _w((lambda *s: torch.randn(*s, dtype=torch.bfloat16) * 0.8)(F) * 0.02),
            "w2": _w((lambda *s: torch.randn(*s, dtype=torch.bfloat16) * 0.1)(F, S) * (F ** -0.5)),
            "b2": _w((lambda *s: torch.randn(*s, dtype=torch.bfloat16) * 0.1)(S) * 0.02),
        }
    _B_in = _B_setup()

    return {
        "A_x": _A_in["x"],
        "A_wqkv": _A_in["wqkv"],
        "A_wo": _A_in["wo"],
        "B_x": _B_in["x"],
        "B_w1": _B_in["w1"],
        "B_b1": _B_in["b1"],
        "B_w2": _B_in["w2"],
        "B_b2": _B_in["b2"],
    }

def reference(A_x, A_wqkv, A_wo, B_x, B_w1, B_b1, B_w2, B_b2):
    def _A_ref(x, wqkv, wo):
        B, S, D = x.shape
        H = 16; Dh = D // H
        W, dil = 8, 2
        qkv = (lambda x, *d: x.permute(*d))((x @ wqkv).reshape(B, S, 3, H, Dh), 2, 0, 3, 1, 4)
        q, k, v = qkv[0], qkv[1], qkv[2]
        scale = Dh ** -0.5
        pos = torch.arange(S)
        off = torch.arange(W) * dil
        idx = pos[:, None] - off[None, :]
        mask = idx >= 0
        idx_c = torch.where(mask, idx, 0).reshape(-1)
        kg = k[:, :, idx_c, :].reshape(B, H, S, W, Dh)
        vg = v[:, :, idx_c, :].reshape(B, H, S, W, Dh)
        logits = torch.einsum("bhsd,bhswd->bhsw", q, kg) * scale
        logits = torch.where(mask[None, None, :, :], logits, -1e9)
        attn = _softmax(logits, axis=-1)
        o = torch.einsum("bhsw,bhswd->bhsd", attn, vg)
        return (lambda x, *d: x.permute(*d))(o, 0, 2, 1, 3).reshape(B, S, D) @ wo

    def _B_ref(x, w1, b1, w2, b2):
        B, S, D = x.shape
        h = _layernorm(x, axis=-1)
        u = torch.einsum("bsd,sf->bdf", h, w1) + b1
        u = _gelu(u)
        y = torch.einsum("bdf,fs->bds", u, w2) + b2
        return (lambda x, *d: x.permute(*d))(y, 0, 2, 1)

    x = A_x
    xn = _layernorm(x, axis=-1)
    s = _A_ref(xn, A_wqkv, A_wo)
    g = _silu(_B_ref(xn, B_w1, B_b1, B_w2, B_b2))
    return x + s * g
```

```cpp
#include <cuda_runtime.h>
#include <cuda.h>
#include <cuda_bf16.h>
#include <stdint.h>

template<int TA, int TB> __device__ __forceinline__ void wgmma_n112(float (&d)[56], uint64_t da, uint64_t db, int sc) {
  asm volatile("{\n.reg .pred p;\nsetp.ne.b32 p, %58, 0;\n"
    "wgmma.mma_async.sync.aligned.m64n112k16.f32.bf16.bf16 {%0, %1, %2, %3, %4, %5, %6, %7, %8, %9, %10, %11, %12, %13, %14, %15, %16, %17, %18, %19, %20, %21, %22, %23, %24, %25, %26, %27, %28, %29, %30, %31, %32, %33, %34, %35, %36, %37, %38, %39, %40, %41, %42, %43, %44, %45, %46, %47, %48, %49, %50, %51, %52, %53, %54, %55}, %56, %57, p, 1, 1, %59, %60;\n}\n"
    : "+f"(d[0]), "+f"(d[1]), "+f"(d[2]), "+f"(d[3]), "+f"(d[4]), "+f"(d[5]), "+f"(d[6]), "+f"(d[7]), "+f"(d[8]), "+f"(d[9]), "+f"(d[10]), "+f"(d[11]), "+f"(d[12]), "+f"(d[13]), "+f"(d[14]), "+f"(d[15]), "+f"(d[16]), "+f"(d[17]), "+f"(d[18]), "+f"(d[19]), "+f"(d[20]), "+f"(d[21]), "+f"(d[22]), "+f"(d[23]), "+f"(d[24]), "+f"(d[25]), "+f"(d[26]), "+f"(d[27]), "+f"(d[28]), "+f"(d[29]), "+f"(d[30]), "+f"(d[31]), "+f"(d[32]), "+f"(d[33]), "+f"(d[34]), "+f"(d[35]), "+f"(d[36]), "+f"(d[37]), "+f"(d[38]), "+f"(d[39]), "+f"(d[40]), "+f"(d[41]), "+f"(d[42]), "+f"(d[43]), "+f"(d[44]), "+f"(d[45]), "+f"(d[46]), "+f"(d[47]), "+f"(d[48]), "+f"(d[49]), "+f"(d[50]), "+f"(d[51]), "+f"(d[52]), "+f"(d[53]), "+f"(d[54]), "+f"(d[55])
    : "l"(da), "l"(db), "r"(sc), "n"(TA), "n"(TB));
}

template<int TB> __device__ __forceinline__ void wgmma_rs_n80(float (&d)[40], const uint32_t (&a)[4], uint64_t db, int sc) {
  asm volatile("{\n.reg .pred p;\nsetp.ne.b32 p, %45, 0;\n"
    "wgmma.mma_async.sync.aligned.m64n80k16.f32.bf16.bf16 {%0, %1, %2, %3, %4, %5, %6, %7, %8, %9, %10, %11, %12, %13, %14, %15, %16, %17, %18, %19, %20, %21, %22, %23, %24, %25, %26, %27, %28, %29, %30, %31, %32, %33, %34, %35, %36, %37, %38, %39}, {%40, %41, %42, %43}, %44, p, 1, 1, %46;\n}\n"
    : "+f"(d[0]), "+f"(d[1]), "+f"(d[2]), "+f"(d[3]), "+f"(d[4]), "+f"(d[5]), "+f"(d[6]), "+f"(d[7]), "+f"(d[8]), "+f"(d[9]), "+f"(d[10]), "+f"(d[11]), "+f"(d[12]), "+f"(d[13]), "+f"(d[14]), "+f"(d[15]), "+f"(d[16]), "+f"(d[17]), "+f"(d[18]), "+f"(d[19]), "+f"(d[20]), "+f"(d[21]), "+f"(d[22]), "+f"(d[23]), "+f"(d[24]), "+f"(d[25]), "+f"(d[26]), "+f"(d[27]), "+f"(d[28]), "+f"(d[29]), "+f"(d[30]), "+f"(d[31]), "+f"(d[32]), "+f"(d[33]), "+f"(d[34]), "+f"(d[35]), "+f"(d[36]), "+f"(d[37]), "+f"(d[38]), "+f"(d[39])
    : "r"(a[0]), "r"(a[1]), "r"(a[2]), "r"(a[3]), "l"(db), "r"(sc), "n"(TB));
}

template<int TB> __device__ __forceinline__ void wgmma_rs_n32(float (&d)[16], const uint32_t (&a)[4], uint64_t db, int sc) {
  asm volatile("{\n.reg .pred p;\nsetp.ne.b32 p, %21, 0;\n"
    "wgmma.mma_async.sync.aligned.m64n32k16.f32.bf16.bf16 {%0, %1, %2, %3, %4, %5, %6, %7, %8, %9, %10, %11, %12, %13, %14, %15}, {%16, %17, %18, %19}, %20, p, 1, 1, %22;\n}\n"
    : "+f"(d[0]), "+f"(d[1]), "+f"(d[2]), "+f"(d[3]), "+f"(d[4]), "+f"(d[5]), "+f"(d[6]), "+f"(d[7]), "+f"(d[8]), "+f"(d[9]), "+f"(d[10]), "+f"(d[11]), "+f"(d[12]), "+f"(d[13]), "+f"(d[14]), "+f"(d[15])
    : "r"(a[0]), "r"(a[1]), "r"(a[2]), "r"(a[3]), "l"(db), "r"(sc), "n"(TB));
}

namespace {
constexpr int S_ = 2048, D_ = 448, F_ = 1792;
constexpr int SLOT = 22528, BT = 14336;
constexpr int OFF_KV = 8 * SLOT;
constexpr int KV = 10 * 1792;
constexpr int OFF_PART = OFF_KV + 2 * BT;
constexpr int OFF_U = OFF_KV + 10 * 3584;
constexpr int OFF_BAR = OFF_U + BT + 64;
constexpr int OFF_OBS = OFF_BAR + 256;
constexpr int SMEM_BYTES = OFF_OBS + 768;
#define DLY_B 900
#define DLY_W 4300
#define DLY_R 1600
#define POLLB 8
#define POLL0 24
#define DLY_N 7000
#define STG_S 6
#define PS_H 150
#define PS_N 300
#define PS_U 100
#define PS_O 130
#define UG 1
#define PP 1
#define PFS 0
#define PF0 2800
#define PACE1 420
#define PACE2 500
#define TRIG0 2
#define TRIG1 9
#define SA 1
#define SB 8
#define TPW 210
#define DLY_S 5400
#define DLY_I 6700
#define HK 1
#define OBS(c, i) do {} while (0)
constexpr int NTHREADS = 384;
constexpr float SCALE = 0.18898223650461361f, LOG2E = 1.4426950408889634f;

constexpr int GRP = 7168;
constexpr int G_H = 0, G_XN = 256, G_O = 512, G_W = 768, G_U = G_W + 168, G_WO = G_U + 224, G_HALO = G_WO + 56, G_END = G_HALO + 128;
constexpr int SCR_BYTES = G_END * GRP;
__device__ __align__(1024) unsigned char g_scr[SCR_BYTES];
constexpr int C_TICKET = 0, C_W = 1, C_H = 2, C_U = 4, C_W2 = 5, C_O = 8, C_HALO = 40, C_END = 168;
__device__ __align__(128) unsigned g_cnt[C_END * 32];

__device__ __forceinline__ uint32_t smem_u32(const void* p) { return (uint32_t)__cvta_generic_to_shared(p); }
__device__ __forceinline__ void mbar_init(uint32_t bar, uint32_t cnt) { asm volatile("mbarrier.init.shared::cta.b64 [%0], %1;" :: "r"(bar), "r"(cnt)); }
__device__ __forceinline__ void mbar_expect_tx(uint32_t bar, uint32_t bytes) { asm volatile("mbarrier.arrive.expect_tx.shared::cta.b64 _, [%0], %1;" :: "r"(bar), "r"(bytes) : "memory"); }
__device__ __forceinline__ void mbar_arrive(uint32_t bar) { asm volatile("mbarrier.arrive.shared::cta.b64 _, [%0];" :: "r"(bar) : "memory"); }
__device__ __forceinline__ void mbar_wait(uint32_t bar, uint32_t parity) {
  asm volatile("{\n.reg .pred p;\n.reg .u32 n;\nmov.u32 n, 0;\nLAB_WAIT:\n"
               "mbarrier.try_wait.parity.shared::cta.b64 p, [%0], %1;\n@p bra DONE;\n"
               "add.u32 n, n, 1;\nsetp.lt.u32 p, n, 4000000;\n@p bra LAB_WAIT;\ntrap;\nDONE:\n}" :: "r"(bar), "r"(parity) : "memory");
}
__device__ __forceinline__ uint32_t mbar_try(uint32_t bar, uint32_t parity) {
  uint32_t ok;
  asm volatile("{\n.reg .pred p;\nmbarrier.test_wait.parity.shared::cta.b64 p, [%1], %2;\nselp.u32 %0, 1, 0, p;\n}" : "=r"(ok) : "r"(bar), "r"(parity) : "memory");
  return ok;
}
__device__ __forceinline__ void tma4d(uint32_t dst, const CUtensorMap* m, int c0, int c1, int c3, uint32_t bar) {
  asm volatile("cp.async.bulk.tensor.4d.shared::cluster.global.mbarrier::complete_tx::bytes [%0], [%1, {%3, %4, %6, %5}], [%2];"
               :: "r"(dst), "l"(m), "r"(bar), "r"(c0), "r"(c1), "r"(c3), "r"(0) : "memory");
}
__device__ __forceinline__ void bulk_g2s(uint32_t dst, const void* src, uint32_t bytes, uint32_t bar) {
  asm volatile("cp.async.bulk.shared::cluster.global.mbarrier::complete_tx::bytes [%0], [%1], %2, [%3];" :: "r"(dst), "l"(src), "r"(bytes), "r"(bar) : "memory");
}
__device__ __forceinline__ void bulk_s2g(void* dst, uint32_t src, uint32_t bytes) {
  asm volatile("cp.async.bulk.global.shared::cta.bulk_group [%0], [%1], %2;" :: "l"(dst), "r"(src), "r"(bytes) : "memory");
}
__device__ __forceinline__ void wg_fence() { asm volatile("wgmma.fence.sync.aligned;" ::: "memory"); }
__device__ __forceinline__ void wg_commit() { asm volatile("wgmma.commit_group.sync.aligned;" ::: "memory"); }
template <int N> __device__ __forceinline__ void wg_wait() { asm volatile("wgmma.wait_group.sync.aligned %0;" :: "n"(N) : "memory"); }
__device__ __forceinline__ void proxy_fence() { asm volatile("fence.proxy.async.global;" ::: "memory"); }
#define LIGHT 1
__device__ __forceinline__ void smem_fence(uint32_t base) {
  if (LIGHT == 2) return;
  if (LIGHT) asm volatile("mbarrier.init.shared::cta.b64 [%0], 1;" :: "r"(base + OFF_BAR + 248) : "memory");
  else asm volatile("fence.proxy.async.shared::cta;" ::: "memory");
}
__device__ __forceinline__ void publish(int i) {
  asm volatile("cp.async.bulk.commit_group;" ::: "memory");
  asm volatile("cp.async.bulk.wait_group 0;" ::: "memory");
  asm volatile("red.relaxed.gpu.global.inc.u32 [%0], 0xffffffff;" :: "l"(&g_cnt[i * 32]) : "memory");
}
__device__ __forceinline__ void spin_ge(int i, unsigned target) {
  asm volatile("{\n.reg .pred p;\n.reg .u32 n, v;\nmov.u32 n, 0;\nLAB_SPIN:\n"
               "ld.relaxed.gpu.global.u32 v, [%0];\nsetp.ge.u32 p, v, %1;\n@p bra DONE;\n"
               "add.u32 n, n, 1;\nsetp.lt.u32 p, n, 4000000;\n@p bra LAB_SPIN;\ntrap;\nDONE:\n}" :: "l"(&g_cnt[i * 32]), "r"(target) : "memory");
}
__device__ __forceinline__ unsigned ld_relaxed(int i) { unsigned v; asm volatile("ld.relaxed.gpu.global.u32 %0, [%1];" : "=r"(v) : "l"(&g_cnt[i * 32]) : "memory"); return v; }
__device__ __forceinline__ bool elect() {
  uint32_t r; asm volatile("{\n.reg .pred p;\nelect.sync _|p, 0xffffffff;\nselp.u32 %0, 1, 0, p;\n}" : "=r"(r)); return r != 0;
}
__device__ __forceinline__ void wait_until(uint32_t tn) { while ((int)(clock() - tn) < 0) __nanosleep(20); }
__device__ __forceinline__ void store_paced(unsigned char* dst, int dstep, uint32_t src, int sstep, int n, int gap) {
  uint32_t tn = clock();
#pragma unroll 1
  for (int i = 0; i < n; i++) { wait_until(tn); bulk_s2g(dst, src, 1792); dst += dstep; src += sstep; tn += gap; }
}
__device__ __forceinline__ uint4 lds128(uint32_t a) { uint4 v; asm volatile("ld.shared.v4.u32 {%0,%1,%2,%3}, [%4];" : "=r"(v.x), "=r"(v.y), "=r"(v.z), "=r"(v.w) : "r"(a) : "memory"); return v; }
__device__ __forceinline__ uint32_t lds32(uint32_t a) { uint32_t v; asm volatile("ld.shared.u32 %0, [%1];" : "=r"(v) : "r"(a) : "memory"); return v; }
__device__ __forceinline__ void sts128(uint32_t p, uint32_t a, uint32_t b, uint32_t c, uint32_t d) { asm volatile("st.shared.v4.u32 [%0], {%1,%2,%3,%4};" :: "r"(p), "r"(a), "r"(b), "r"(c), "r"(d) : "memory"); }
__device__ __forceinline__ void sts64(uint32_t p, float a, float b) { asm volatile("st.shared.v2.f32 [%0], {%1,%2};" :: "r"(p), "f"(a), "f"(b) : "memory"); }
__device__ __forceinline__ void named_sync(int id, int n) { asm volatile("bar.sync %0, %1;" :: "r"(id), "r"(n) : "memory"); }
__device__ __forceinline__ void named_arrive(int id, int n) { asm volatile("bar.arrive %0, %1;" :: "r"(id), "r"(n) : "memory"); }
__device__ __forceinline__ uint64_t mkdesc(uint32_t hi, uint32_t lo) { return ((uint64_t)hi << 32) | lo; }
constexpr uint32_t HI_SW128 = 0x40000040u;
__device__ __forceinline__ uint32_t pack2(float lo, float hi) { uint32_t r; asm("cvt.rn.bf16x2.f32 %0, %1, %2;" : "=r"(r) : "f"(hi), "f"(lo)); return r; }
__device__ __forceinline__ float bf_lo(uint32_t v) { return __uint_as_float(v << 16); }
__device__ __forceinline__ float bf_hi(uint32_t v) { return __uint_as_float(v & 0xffff0000u); }
__device__ __forceinline__ float rbf(float x) { return bf_lo(pack2(x, 0.f)); }
__device__ __forceinline__ uint32_t hsub2(uint32_t a, uint32_t b) { uint32_t r; asm("sub.rn.bf16x2 %0, %1, %2;" : "=r"(r) : "r"(a), "r"(b)); return r; }
__device__ __forceinline__ uint32_t hadd2(uint32_t a, uint32_t b) { uint32_t r; asm("add.rn.bf16x2 %0, %1, %2;" : "=r"(r) : "r"(a), "r"(b)); return r; }
__device__ __forceinline__ uint32_t hmul2(uint32_t a, uint32_t b) { uint32_t r; asm("mul.rn.bf16x2 %0, %1, %2;" : "=r"(r) : "r"(a), "r"(b)); return r; }
__device__ __forceinline__ uint32_t hfma2(uint32_t a, uint32_t b, uint32_t c) { uint32_t r; asm("fma.rn.bf16x2 %0, %1, %2, %3;" : "=r"(r) : "r"(a), "r"(b), "r"(c)); return r; }
__device__ __forceinline__ float tanh_fast(float x) { float r; asm("tanh.approx.f32 %0, %1;" : "=f"(r) : "f"(x)); return r; }
__device__ __forceinline__ float rcp_fast(float x) { float r; asm("rcp.approx.ftz.f32 %0, %1;" : "=f"(r) : "f"(x)); return r; }
__device__ __forceinline__ float ex2_fast(float x) { float r; asm("ex2.approx.ftz.f32 %0, %1;" : "=f"(r) : "f"(x)); return r; }
__device__ __forceinline__ void stsm4(uint32_t addr, uint32_t a, uint32_t b, uint32_t c, uint32_t d) {
  asm volatile("stmatrix.sync.aligned.m8n8.x4.shared.b16 [%0], {%1,%2,%3,%4};" :: "r"(addr), "r"(a), "r"(b), "r"(c), "r"(d) : "memory");
}
__device__ __forceinline__ void stsm2(uint32_t addr, uint32_t a, uint32_t b) {
  asm volatile("stmatrix.sync.aligned.m8n8.x2.shared.b16 [%0], {%1,%2};" :: "r"(addr), "r"(a), "r"(b) : "memory");
}
__device__ __forceinline__ void load_row(uint32_t (&r)[14], const unsigned char* p, int t) {
#pragma unroll
  for (int i = 0; i < 3; i++)
    asm volatile("ld.global.nc.L1::no_allocate.v4.u32 {%0,%1,%2,%3}, [%4];" : "=r"(r[4 * i]), "=r"(r[4 * i + 1]), "=r"(r[4 * i + 2]), "=r"(r[4 * i + 3]) : "l"(p + i * 64 + t * 16));
  asm volatile("ld.global.nc.L1::no_allocate.v2.u32 {%0,%1}, [%2];" : "=r"(r[12]), "=r"(r[13]) : "l"(p + 192 + t * 8));
}

template <int N> __device__ __forceinline__ void fresh(float (&a)[N]) {
#pragma unroll
  for (int i = 0; i < N; i++) asm volatile("" : "=f"(a[i]));
}
__device__ __forceinline__ void pin(uint32_t (&a)[4]) { asm volatile("" : "+r"(a[0]), "+r"(a[1]), "+r"(a[2]), "+r"(a[3])); }
constexpr int B_EMPTY = 64, B_F0 = 128, B_F1 = 136, B_F2 = 144, B_F3 = 152, B_HALO = 160, B_RT = 176, B_RES = 184, B_TS = 192, B_F1B = 200;
constexpr int N_GO = 6, N_DONE = 7;
template <int ROT, bool YIELD, int CONT, class F>
__device__ __forceinline__ void ring_loop(uint32_t base, int c0, int n, int next, bool rel, uint32_t t0, int oi, F mma) {
  const uint32_t bars = base + OFF_BAR;
  uint32_t ok = 0;
#pragma unroll 1
  for (int c = c0; c < c0 + n; c++) {
    if (!ok) mbar_wait(bars + (c & 7) * 8, (c >> 3) & 1);
    const uint32_t lo = (base >> 4) + (c & 7) * (SLOT >> 4), la = (base >> 4) + ((c + ROT) & 7) * (SLOT >> 4);
    constexpr int KS = 4;
    const bool yield = YIELD && (c == c0 + SA || c == c0 + SB);
    wg_fence();
#pragma unroll
    for (int k = 0; k < KS; k++) {
      mma(la, lo, k, CONT || c != c0 || k != 0);
      if (k == KS / 2 - 1) ok = mbar_try(bars + ((c + 1) & 7) * 8, ((c + 1) >> 3) & 1);
      if (k == KS - 1 - HK && next)
        asm volatile("{\n.reg .pred p;\nsetp.ne.u32 p, %1, 0;\n@p bar.arrive %0, 256;\n}" :: "r"(yield ? N_GO : next), "r"((uint32_t)(yield || c == c0 + n - 1)) : "memory");
    }
    wg_commit();
    wg_wait<1>();
    if ((CONT == 1 || c != c0) && rel) mbar_arrive(bars + B_EMPTY + ((c - 1) & 7) * 8);
    if (yield) named_sync(N_DONE, 256);
  }
}

template <uint32_t BYTES>
__device__ __forceinline__ void produce(uint32_t base, int c, int cend, int rot, const CUtensorMap* mp, int c0, int c1, int s1, int c3, int s3, int tr = 0) {
#pragma unroll 1
  for (; c < cend; c++) {
    const uint32_t fb = base + OFF_BAR + (c & 7) * 8, dst = base + (BYTES ? 8192 : 0) + ((c + rot) & 7) * SLOT;
    mbar_wait(fb + B_EMPTY, ((c >> 3) & 1) ^ 1);
    if (BYTES) mbar_expect_tx(fb, BYTES);
    tma4d(dst, mp, c0, c1, c3, fb);
    c1 += s1; c3 += s3;
  }
}

struct Params {
  const unsigned char *x, *wqkv, *wo, *w1, *w2;
  const unsigned short *b1, *b2;
  unsigned char* out;
};

__global__ void __launch_bounds__(NTHREADS, 1)
fused_kernel(const __grid_constant__ CUtensorMap m_w1, const __grid_constant__ CUtensorMap m_w2, const __grid_constant__ CUtensorMap m_b14,
             const __grid_constant__ CUtensorMap m_a8, const __grid_constant__ CUtensorMap m_x, const Params p) {
  extern __shared__ __align__(1024) unsigned char smem_raw[];
  const uint32_t t0 = clock();
  const int tid = threadIdx.x, lane = tid & 31, b = blockIdx.x;
  const int g = lane >> 2, t = lane & 3, r8 = lane & 7, mi = lane >> 3;
  const int tg = (tid & 128) + b;
  const unsigned char* xrow = p.x + ((tg >> 1) * 16 + (tg & 1) + 2 * g) * (D_ * 2) + ((tid >> 5) & 3) * 224;
  uint32_t H[14];
  if (tid < 128) load_row(H, xrow, t);
  const uint32_t base = smem_u32(smem_raw), bars = base + OFF_BAR;
  const int warp = __shfl_sync(0xffffffffu, tid >> 5, 0);
  const int dt = b & 3, mt = b >> 2;
  const bool g1 = b < 112;
  const int ft = mt, d1 = dt;
  if (warp >= 8) {
    if (warp == 8) {
      if (elect()) {
#pragma unroll
        for (int i = 0; i < 26; i++) mbar_init(bars + i * 8, i * 8 == B_F1 && !g1 ? 3 : 1);
        asm volatile("fence.mbarrier_init.release.cluster;" ::: "memory");
      }
      __syncwarp();
      named_arrive(12, 160); named_arrive(13, 160);
    }
    named_sync(15, 128);
    asm volatile("setmaxnreg.dec.sync.aligned.u32 40;");
    if (warp == 8) {
      unsigned tk = 0;
      if (elect()) {
        asm volatile("prefetch.tensormap [%0];" :: "l"(&m_w1) : "memory");
        asm volatile("prefetch.tensormap [%0];" :: "l"(&m_a8) : "memory");
        if (g1) {
#pragma unroll 1
          for (int c = 0; c < 8; c++) { wait_until(t0 + DLY_W + c * TPW); tma4d(base + c * SLOT, &m_w1, ft * 64, 0, c * 4, bars + c * 8); }
          produce<0>(base, 8, 32, 0, &m_w1, ft * 64, 0, 0, 32, 4);
        } else {
          const int bytes = (dt < 3 ? 32 : 16) * 2688;
          wait_until(t0 + DLY_R);
          mbar_expect_tx(bars + B_RT, bytes);
          bulk_g2s(base, p.wqkv + ((mt & 3) * 112 + dt * 32) * 2688, bytes, bars + B_RT);
        }
        mbar_wait(bars + B_F1, 0);
        produce<0>(base, 0, 7, 0, &m_a8, 0, 0, 8, G_XN + mt * 8, 0);
        mbar_wait(bars + B_EMPTY + 5 * 8, 0);
        produce<0>(base, 21, 49, 2, &m_w2, mt * 64, 0, 0, 0, 64);
        mbar_wait(bars + B_F3, 0);
        OBS(1, 22);
        produce<0>(base, 49, 56, 2, &m_a8, 0, 0, 8, G_O + mt * 8, 0);
        tk = atomicInc(&g_cnt[C_TICKET * 32], 0xffffffffu);
      }
      if (__any_sync(0xffffffffu, tk == 127)) {
#pragma unroll 1
        for (int i = lane; i < C_END; i += 32) g_cnt[i * 32] = 0;
      }
    } else if (warp == 9) {
      if (elect()) {
        asm volatile("prefetch.tensormap [%0];" :: "l"(&m_b14) : "memory");
        asm volatile("prefetch.tensormap [%0];" :: "l"(&m_w2) : "memory");
        asm volatile("prefetch.tensormap [%0];" :: "l"(&m_x) : "memory");
        if (g1) {
          spin_ge(C_H, 128);
          OBS(1, 16);
          produce<SLOT>(base, 0, STG_S, 0, &m_b14, 0, d1 * 14, 0, G_H, 8);
          mbar_arrive(bars + B_TS);
          produce<SLOT>(base, STG_S, 16, 0, &m_b14, 0, d1 * 14, 0, G_H + STG_S * 8, 8);
          mbar_wait(bars + B_F0, 0);
          OBS(1, 17);
          produce<SLOT>(base, 16, 32, 0, &m_b14, 0, d1 * 14, 0, G_H + 128, 8);
        }
        mbar_wait(bars + B_F1, 0);
        OBS(1, 18);
        produce<SLOT>(base, 0, 7, 0, &m_b14, 0, dt * 14, 0, G_W, 8, 32);
        mbar_wait(bars + B_F1B, 0);
        produce<BT>(base, 7, 21, 0, &m_b14, 0, dt * 14, 0, G_W + 56, 8, 32);
        mbar_wait(bars + B_F2, 0);
        OBS(1, 20);
        produce<SLOT>(base, 21, 56, 0, &m_b14, 0, dt * 14, 0, G_U, 8, 32);
      }
    } else if (warp == 10) {
      uint32_t tn = t0 + PF0;
      const unsigned char* src = p.w1 + PFS * 458752 + b * 3584 + lane * 128;
      float z[4] = {};
      bool useen = false;
#pragma unroll 1
      for (int i = PFS; i < 32; i++) {
        if (!useen && i >= POLL0) {
          while ((int)(clock() - tn) < 0 && !useen) useen = ld_relaxed(C_U) >= 128;
          if (useen && lane == 0) mbar_arrive(bars + B_F2);
        }
        wait_until(tn);
        if (i == 16) src = p.w2 + b * 3584 + lane * 128;
        if (lane < 28) asm volatile("prefetch.global.L2 [%0];" :: "l"(src) : "memory");
        __syncwarp();
        if (i >= TRIG0 && i < TRIG1 && g1)
          asm volatile("mma.sync.aligned.m16n8k16.row.col.f32.bf16.bf16.f32 {%0,%1,%2,%3}, {%4,%4,%4,%4}, {%4,%4}, {%0,%1,%2,%3};" : "+f"(z[0]), "+f"(z[1]), "+f"(z[2]), "+f"(z[3]) : "r"(0));
        src += 458752;
        tn += i < 16 ? PACE1 : PACE2;
      }
      if (!useen) { spin_ge(C_U, 128); if (lane == 0) mbar_arrive(bars + B_F2); }
      spin_ge(C_O + mt, 16);
      if (lane == 0) mbar_arrive(bars + B_F3);
    } else {
#pragma unroll 1
      for (int i = 0; i < 4; i++) {
        const int v = i ^ (i >> 1);
        unsigned char* dst = g_scr + (((v & 1) ? G_H : G_XN) + (i >> 1) * 128 + b) * GRP;
        asm volatile("" : "+l"(dst));
        if (i < 3) named_sync(i == 2 ? 9 : (i ? 10 : 14), 160);
        const bool slow = i > 1 && g1;
        if (slow) mbar_wait(bars + B_TS, 0);
        smem_fence(base);
        if (elect()) {
          if (slow) store_paced(dst, 1792, base + OFF_KV + v * GRP, 1792, 4, i == 2 ? PS_H : PS_N);
          else bulk_s2g(dst, base + OFF_KV + v * GRP, GRP);
          if (i) publish(i == 3 ? C_W : C_H + (i >> 1));
        }
        __syncwarp();
        OBS(lane == 0 && (v & 1), 3 + (i >> 1));
      }
      spin_ge(C_W, 144);
      if (lane == 0) mbar_arrive(bars + B_F1);
      spin_ge(C_W2, 16);
      if (lane == 0) mbar_arrive(bars + B_F1B);
      if (mt == 0) {
#pragma unroll
        for (int i = 0; i < 14; i++) sts128(base + OFF_KV + (i / 7) * KV + (i % 7) * 512 + lane * 16, 0, 0, 0, 0);
        smem_fence(base);
        __syncwarp();
        if (lane < 2) mbar_arrive(bars + B_HALO + lane * 8);
      }
      if (g1) {
#pragma unroll 1
        for (int i = 0; i < 2; i++) {
          unsigned char* ug = g_scr + (G_U + ft * 8 + i) * GRP + d1 * 1792;
          asm volatile("" : "+l"(ug));
          named_sync(i ? 10 : 14, 160);
          smem_fence(base);
          if (elect()) { store_paced(ug, 2 * GRP, base + OFF_U + i * 1792, 3600, 4, PS_U); if (i) publish(C_U); }
          __syncwarp();
        }
        OBS(lane == 0, 7);
      }
#pragma unroll 1
      for (int i = 0; i < 2; i++) {
        unsigned char* hg = g_scr + (G_HALO + b) * GRP + i * 3584;
        named_sync(i ? 0 : 11, 64);
        smem_fence(base);
        if (mt < 31 && elect()) { bulk_s2g(hg, base + OFF_KV + i * KV + 8 * 1792, 3584); publish(C_HALO + b); }
        OBS(lane == 0, i ? 15 : 23);
        if (mt > 0) {
          spin_ge(C_HALO + b - 4, i + 1);
          if (elect()) { mbar_expect_tx(bars + B_HALO + i * 8, 3584); bulk_g2s(base + OFF_KV + i * KV, hg - 4 * GRP, 3584, bars + B_HALO + i * 8); }
        }
        __syncwarp();
      }
    }
  } else {
    const int wg = warp >> 2, w4 = warp & 3;
    const bool rel = (tid & 127) == 0;
    if (wg) { wait_until(t0 + DLY_B); load_row(H, xrow, t); }
    {
      const uint32_t part = base + OFF_PART + wg * 512 + g * 32, st = base + OFF_KV + wg * BT + (w4 * 14 + mi) * 128 + r8 * 16;
#pragma unroll
      for (int ln = 0; ln < 2; ln++) {
        float s0 = 0.f, s1 = 0.f, q0 = 0.f, q1 = 0.f;
#pragma unroll
        for (int j = 0; j < 14; j++) { const float a = bf_lo(H[j]), c = bf_hi(H[j]); s0 += a; s1 += c; q0 = fmaf(a, a, q0); q1 = fmaf(c, c, q1); }
        s0 += s1; q0 += q1;
#pragma unroll
        for (int o = 1; o < 4; o <<= 1) { s0 += __shfl_xor_sync(0xffffffffu, s0, o); q0 += __shfl_xor_sync(0xffffffffu, q0, o); }
        if (t == 0) sts64(part + ln * 256 + w4 * 8, s0, q0);
        OBS(tid == 0 && ln == 0, 0);
        named_sync(1 + wg, 128);
        const uint4 u = lds128(part + ln * 256), v = lds128(part + ln * 256 + 16);
        const float mean = ((__uint_as_float(u.x) + __uint_as_float(u.z)) + (__uint_as_float(v.x) + __uint_as_float(v.z))) * (1.0f / D_);
        const float sq = (__uint_as_float(u.y) + __uint_as_float(u.w)) + (__uint_as_float(v.y) + __uint_as_float(v.w));
        float sd;
        asm("sqrt.approx.ftz.f32 %0, %1;" : "=f"(sd) : "f"(rbf(rbf(fmaxf(fmaf(-mean, mean, sq * (1.0f / D_)), 0.f)) + 1e-5f)));
        const float r = rcp_fast(rbf(sd)), rh = rbf(r);
        const uint32_t m2 = pack2(mean, mean), rh2 = pack2(rh, rh), rl2 = pack2(r - rh, r - rh);
#pragma unroll
        for (int j = 0; j < 14; j++) { const uint32_t d = hsub2(H[j], m2); H[j] = hfma2(d, rh2, hmul2(d, rl2)); }
#pragma unroll
        for (int i = 0; i < 3; i++) stsm4(st + ln * GRP + i * 512, H[4 * i], H[4 * i + 1], H[4 * i + 2], H[4 * i + 3]);
        stsm2(st + ln * GRP + 1536, H[12], H[13]);
        if (ln || !wg) named_arrive(ln ? 10 - wg : 14, 160);
      }
      OBS(rel, 1 + wg);
    }
    named_sync(12 + wg, 160);
    asm volatile("setmaxnreg.inc.sync.aligned.u32 232;");
    uint32_t hb[2];
#pragma unroll
    for (int i = 0; i < 2; i++) {
      asm volatile("ld.relaxed.cta.global.u16 %0, [%1];" : "=r"(hb[i]) : "l"((wg ? p.b2 + mt * 64 : p.b1 + (g1 ? ft * 64 : 0)) + w4 * 16 + g + i * 8) : "memory");
    }
    if (!g1) {
      const int kg0 = (mt & 3) * 14 + dt * 4, nk = dt < 3 ? 4 : 2;
      mbar_wait(bars + B_RT, 0);
      OBS(tid == 0, 7);
      if (w4 < nk) {
        const int c = (r8 + mi + wg * 4) & 7;
        const uint32_t src = base + ((r8 >> 1) * 2 * nk + 2 * w4 + (r8 & 1)) * 2688 + c * 16, dst = base + (12 + w4) * GRP + c * 128 + r8 * 16;
#pragma unroll 1
        for (int m = 0; m < 3; m++) {
          uint4 v[7];
#pragma unroll
          for (int l = 0; l < 7; l++) v[l] = lds128(src + m * 896 + l * 128);
#pragma unroll
          for (int l = 0; l < 7; l++) sts128(dst + m * 4 * GRP + l * 1024, v[l].x, v[l].y, v[l].z, v[l].w);
        }
      }
      smem_fence(base);
      named_sync(0, 256);
      OBS(tid == 0, 5);
      if (warp == 0 && elect()) {
        mbar_expect_tx(bars + B_RT, nk * GRP);
        bulk_g2s(base, p.wo + kg0 * GRP, nk * GRP, bars + B_RT);
#pragma unroll
        for (int m = 0; m < 3; m++) {
          bulk_s2g(g_scr + (G_W + m * 56 + kg0) * GRP, base + (12 + (m + 1) % 3 * 4) * GRP, nk * GRP);
          if (m != 1) publish(m ? C_W2 : C_W);
        }
        mbar_arrive(bars + B_F1);
        OBS(1, 6);
      }
      if (wg) {
        mbar_wait(bars + B_RT, 1);
#pragma unroll 1
        for (int i = 0; i < nk; i++) {
          const uint32_t src = base + i * GRP + g * 896 + w4 * 224, st = base + (4 + i) * GRP + (w4 * 14 + mi) * 128 + r8 * 16;
#pragma unroll
          for (int j = 0; j < 3; j++) { const uint4 v = lds128(src + j * 64 + t * 16); stsm4(st + j * 512, v.x, v.y, v.z, v.w); }
          stsm2(st + 1536, lds32(src + 192 + t * 8), lds32(src + 196 + t * 8));
        }
        smem_fence(base);
        named_sync(2, 128);
        if (w4 == 0 && elect()) {
          bulk_s2g(g_scr + (G_WO + kg0) * GRP, base + 4 * GRP, nk * GRP);
          publish(C_U);
          mbar_arrive(bars + B_F1);
          OBS(1, 16);
        }
      }
      __syncwarp();
    }
    constexpr uint32_t LB = (112u << 16) + 512;
    const uint32_t gx = base + 8192 + (tid & 127) * 16;
    if (wg == 0) {
      float acc[56];
      const uint32_t ust = base + OFF_U + w4 * 3600 + (mi >> 1) * 128;
      if (g1) {
#pragma unroll
        for (int i = 0; i < 56; i++) { acc[i] = bf_lo(hb[(i >> 1) & 1]); asm volatile("" : "+f"(acc[i])); }
        ring_loop<0, false, 2>(base, 0, 32, 3, rel, t0, 5, [&](uint32_t la, uint32_t lo, int k, int sc) {
          wgmma_n112<1, 1>(acc, mkdesc(HI_SW128, la + (512u << 16) + k * 128), mkdesc(8, lo + LB + k * 224), sc); });
        wg_wait<0>();
        if (rel) mbar_arrive(bars + B_EMPTY + 7 * 8);
        OBS(rel, 6);
        const uint32_t us = base + OFF_U + w4 * 3600 + mi * 128 + r8 * 16;
#pragma unroll
        for (int h = 0; h < 2; h++) {
          uint32_t R[14];
#pragma unroll
          for (int n = 0; n < 14; n++) {
            const float a = acc[4 * n + 2 * h], c = acc[4 * n + 2 * h + 1];
            R[n] = pack2(fmaf(a, tanh_fast(a * fmaf(a * a, 0.0356774081f, 0.7978845608f)), a), fmaf(c, tanh_fast(c * fmaf(c * c, 0.0356774081f, 0.7978845608f)), c));
            if ((n & 3) == 3) stsm4(us + h * 1792 + (n - 3) * 128, R[n - 3], R[n - 2], R[n - 1], R[n]);
          }
          stsm2(us + h * 1792 + 1536, R[12], R[13]);
          named_arrive(h ? 10 : 14, 160);
        }
        OBS(rel, 30);
      } else named_arrive(3, 256);
      named_sync(4, 256);
      fresh(acc);
      ring_loop<2, false, false>(base, 14, 7, 5, rel, t0, 9, [&](uint32_t la, uint32_t lo, int k, int sc) {
        wgmma_n112<0, 1>(acc, mkdesc(64, la + (8u << 16) + k * 16), mkdesc(8, lo + LB + k * 224), sc); });
      wg_wait<0>();
      if (rel) mbar_arrive(bars + B_EMPTY + 4 * 8);
      {
        uint32_t Q[8][4];
#pragma unroll
        for (int i = 0; i < 16; i++) {
          const int n = i - (i + 4) / 8;
#pragma unroll
          for (int h = 0; h < 2; h++) {
            const uint32_t v = pack2(acc[4 * n + 2 * h], acc[4 * n + 2 * h + 1]);
            Q[i >> 1][(i & 1) * 2 + h] = (i & 7) == 3 ? (t < 2 ? v : 0u) : ((i & 7) == 4 ? (t < 2 ? 0u : v) : v);
          }
        }
#pragma unroll
        for (int i = 0; i < 8; i++) pin(Q[i]);
        const uint32_t dk = (base + OFF_KV) >> 4;
        float Sc[4][40], O[4][16];
        mbar_wait(bars + B_HALO, 0);
        OBS(rel, 11);
#pragma unroll
        for (int hh = 0; hh < 4; hh++) fresh(Sc[hh]);
        wg_fence();
        named_sync(N_GO, 256);
#pragma unroll
        for (int k = 0; k < 2; k++)
#pragma unroll
          for (int hh = 0; hh < 4; hh++) {
            if (k == 1 && hh == 3) named_arrive(N_DONE, 256);
            wgmma_rs_n80<0>(Sc[hh], Q[hh * 2 + k], mkdesc(112, dk + (8u << 16) + (hh * 7 / 2 + 2 * k) * 8), k);
          }
        wg_commit();
        const bool e0 = 2 * t > g, e1 = 2 * t + 1 > g;
        const uint32_t em = (e0 ? 0xffffu : 0u) | (e1 ? 0xffff0000u : 0u);
        uint32_t L[4][2];
        wg_wait<0>();
        OBS(rel, 12);
        auto pick = [&](int w) {
#pragma unroll
          for (int hh = 0; hh < 4; hh++)
#pragma unroll
            for (int h = 0; h < 2; h++) {
              const int i = (2 * w + h) * 4 + 2 * h;
              L[hh][h] = pack2(e0 ? Sc[hh][i] : Sc[hh][i + 8], e1 ? Sc[hh][i + 1] : Sc[hh][i + 9]);
              asm volatile("" : "+r"(L[hh][h]));
            }
        };
        if (w4 == 0) pick(0); else if (w4 == 1) pick(1); else if (w4 == 2) pick(2); else pick(3);
        const bool edge = mt == 0 && w4 == 0;
        uint32_t A[4][5][4], sign = 0;
#pragma unroll
        for (int hh = 0; hh < 4; hh++) {
#pragma unroll
          for (int h = 0; h < 2; h++) {
            const uint32_t pk = pack2(bf_lo(L[hh][h]) * SCALE, bf_hi(L[hh][h]) * SCALE);
            const float l0 = edge && e0 ? -1e9f : bf_lo(pk), l1 = edge && e1 ? -1e9f : bf_hi(pk);
            float mx = fmaxf(l0, l1);
            mx = fmaxf(mx, __shfl_xor_sync(0xffffffffu, mx, 1));
            mx = fmaxf(mx, __shfl_xor_sync(0xffffffffu, mx, 2));
            const float p0 = ex2_fast((l0 - mx) * LOG2E), p1 = ex2_fast((l1 - mx) * LOG2E);
            float sm = p0 + p1;
            sm += __shfl_xor_sync(0xffffffffu, sm, 1);
            sm += __shfl_xor_sync(0xffffffffu, sm, 2);
            const float inv = rcp_fast(sm);
            const uint32_t pp = pack2(p0 * inv, p1 * inv);
#pragma unroll
            for (int j = 0; j < 5; j++) { A[hh][j][3 * h] = pp & (j == w4 ? em : (j == w4 + 1 ? ~em : 0u)); A[hh][j][1 + h] = 0u; }
            sign |= pp;
          }
        }
#pragma unroll
        for (int hh = 0; hh < 4; hh++) fresh(O[hh]);
#pragma unroll
        for (int i = 0; i < 20; i++) pin(A[i / 5][i % 5]);
        OBS(rel, 13);
        mbar_wait(bars + B_HALO + 8 + (sign >> 31), 0);
        if (w4 == 0) {
          if (elect()) { mbar_expect_tx(bars + B_RES, BT); tma4d(base + OFF_KV, &m_x, dt * 112, 0, mt * 64, bars + B_RES); }
          __syncwarp();
        }
        OBS(rel, 31);
        named_sync(N_GO, 256);
        wg_fence();
#pragma unroll
        for (int j = 0; j < 5; j++)
#pragma unroll
          for (int hh = 0; hh < 4; hh++) {
            if (j == 4 && hh == 2) named_arrive(N_DONE, 256);
            wgmma_rs_n32<1>(O[hh], A[hh][j], mkdesc(8, dk + (112u << 16) + (KV >> 4) + hh * 7 / 2 * 8 + j * 224), j);
          }
        wg_commit();
        OBS(rel, 19);
        wg_wait<0>();
        OBS(rel, 21);
        const uint32_t ost = ust + (r8 >> 2) * 1808 + ((2 * r8 + (mi & 1)) & 7) * 16;
#pragma unroll
        for (int n = 0; n < 14; n += 2) {
          uint32_t R[4];
#pragma unroll
          for (int j = 0; j < 4; j++) {
            const int m = n + (j >> 1), hb2 = m / 7 * 2, r = m % 7, h2 = (j & 1) * 2;
            if (r < 3) R[j] = pack2(O[hb2][4 * r + h2], O[hb2][4 * r + h2 + 1]);
            else if (r == 3) R[j] = pack2(t < 2 ? O[hb2][12 + h2] : O[hb2 + 1][h2], t < 2 ? O[hb2][13 + h2] : O[hb2 + 1][h2 + 1]);
            else R[j] = pack2(O[hb2 + 1][4 * (r - 3) + h2], O[hb2 + 1][4 * (r - 3) + h2 + 1]);
          }
          stsm4(ost + n * 128, R[0], R[1], R[2], R[3]);
        }
        OBS(rel, 29);
        smem_fence(base);
        __syncwarp();
        OBS(rel, 14);
        if (elect()) {
          unsigned char* og = g_scr + (G_O + mt * 8 + w4 * 2) * GRP + dt * 1792;
          wait_until(clock() + w4 * PS_O);
          store_paced(og, GRP, base + OFF_U + w4 * 3600, 1808, 2, 4 * PS_O);
          publish(C_O + mt);
        }
        __syncwarp();
      }
      const int ro = (mt * 64 + w4 * 16 + g) * (D_ * 2) + dt * 224;
      uint32_t X[28], G[28];
      mbar_wait(bars + B_RES, 0);
#pragma unroll
      for (int h = 0; h < 2; h++) {
        const uint32_t a = base + OFF_KV + (w4 * 16 + h * 8 + g) * 224;
#pragma unroll
        for (int i = 0; i < 3; i++) { const uint4 v = lds128(a + i * 64 + t * 16); X[h * 14 + 4 * i] = v.x; X[h * 14 + 4 * i + 1] = v.y; X[h * 14 + 4 * i + 2] = v.z; X[h * 14 + 4 * i + 3] = v.w; }
        X[h * 14 + 12] = lds32(a + 192 + t * 8); X[h * 14 + 13] = lds32(a + 196 + t * 8);
      }
      unsigned char *outp = p.out + ro + t * 16, *outq = p.out + ro + 192 + t * 8;
      asm volatile("" : "+l"(outp), "+l"(outq));
      named_sync(8, 256);
      fresh(acc);
      ring_loop<2, false, false>(base, 49, 7, 0, rel, t0, 25, [&](uint32_t la, uint32_t lo, int k, int sc) {
        wgmma_n112<0, 1>(acc, mkdesc(64, la + (8u << 16) + k * 16), mkdesc(8, lo + LB + k * 224), sc); });
      named_sync(9, 256);
#pragma unroll
      for (int j = 0; j < 28; j += 4) { const uint4 v = lds128(gx + j * 512); G[j] = v.x; G[j + 1] = v.y; G[j + 2] = v.z; G[j + 3] = v.w; }
      wg_wait<0>();
      OBS(rel, 27);
#pragma unroll
      for (int i = 0; i < 4; i++)
#pragma unroll
        for (int h = 0; h < 2; h++) {
          uint32_t R[4];
#pragma unroll
          for (int j = 0; j < (i < 3 ? 4 : 2); j++) {
            const int n = 4 * i + j;
            R[j] = hadd2(X[h * 14 + n], hmul2(pack2(acc[4 * n + 2 * h], acc[4 * n + 2 * h + 1]), G[2 * n + h]));
          }
          if (i < 3) asm volatile("st.global.v4.u32 [%0], {%1,%2,%3,%4};" :: "l"(outp + h * 8 * D_ * 2 + i * 64), "r"(R[0]), "r"(R[1]), "r"(R[2]), "r"(R[3]) : "memory");
          else asm volatile("st.global.v2.u32 [%0], {%1,%2};" :: "l"(outq + h * 8 * D_ * 2), "r"(R[0]), "r"(R[1]) : "memory");
        }
      OBS(rel, 28);
    } else {
      if (g1 && w4 == 1) { mbar_wait(bars + B_TS, 0); spin_ge(C_H + 1, 128); if (lane == 0) mbar_arrive(bars + B_F0); __syncwarp(); }
      {
        float ka[56], va[56];
        const uint32_t kst = base + OFF_KV + (2 + 2 * w4 + (mi & 1)) * 1792 + (mi >> 1) * 128 + r8 * 16;
        auto stage = [&](const float (&a)[56], uint32_t dst, int n) {
          stsm4(dst + n * 128, pack2(a[4 * n], a[4 * n + 1]), pack2(a[4 * n + 2], a[4 * n + 3]), pack2(a[4 * n + 4], a[4 * n + 5]), pack2(a[4 * n + 6], a[4 * n + 7])); };
        auto vmma = [&](uint32_t la, uint32_t lo, int k, int sc) { wgmma_n112<0, 1>(va, mkdesc(64, la + (8u << 16) + k * 16), mkdesc(8, lo + LB + k * 224), sc); };
        named_sync(3, 256);
        fresh(ka);
        ring_loop<0, false, false>(base, 0, 7, 0, rel, t0, 8, [&](uint32_t la, uint32_t lo, int k, int sc) {
          wgmma_n112<0, 1>(ka, mkdesc(64, la + (8u << 16) + k * 16), mkdesc(8, lo + LB + k * 224), sc); });
        fresh(va);
#pragma unroll
        for (int c = 7; c < 10; c++) {
          mbar_wait(bars + (c & 7) * 8, c >> 3);
          wg_fence();
#pragma unroll
          for (int k = 0; k < 4; k++) {
            vmma((base >> 4) + (c - 7) * (SLOT >> 4), (base >> 4) + (c & 7) * (SLOT >> 4), k, c > 7 || k);
            if (c > 7 && (c - 8) * 4 + k < 7) stage(ka, kst, (c - 8) * 8 + k * 2);
          }
          wg_commit();
          wg_wait<1>();
          if (rel) mbar_arrive(bars + B_EMPTY + ((c - 1) & 7) * 8);
        }
        if (w4 == 3) named_arrive(11, 64);
        ring_loop<1, false, true>(base, 10, 4, 4, rel, t0, 125, vmma);
        wg_wait<0>();
        if (rel) mbar_arrive(bars + B_EMPTY + 5 * 8);
#pragma unroll
        for (int n = 0; n < 14; n += 2) stage(va, kst + KV, n);
        if (w4 == 3) named_arrive(0, 64);
        smem_fence(base);
      }
      float acc[56];
#pragma unroll
      for (int i = 0; i < 2; i++) { hb[i] = hmul2(hb[i] * 0x10001u, 0x3f003f00u); asm volatile("" : "+r"(hb[i])); }
      named_sync(5, 256);
      fresh(acc);
      ring_loop<2, true, false>(base, 21, 28, 8, rel, t0, 10, [&](uint32_t la, uint32_t lo, int k, int sc) {
        wgmma_n112<1, 1>(acc, mkdesc(HI_SW128, la + (512u << 16) + k * 128), mkdesc(8, lo + LB + k * 224), sc); });
      wg_wait<0>();
      OBS(rel, 24);
#pragma unroll
      for (int j = 0; j < 28; j += 4) {
        uint32_t R[4];
#pragma unroll
        for (int i = 0; i < 4; i++) {
          const uint32_t hh = hfma2(pack2(acc[2 * (j + i)], acc[2 * (j + i) + 1]), 0x3e803e80u, hb[i & 1]);
          const float a = bf_lo(hh), c = bf_hi(hh);
          R[i] = pack2(fmaf(a, tanh_fast(a), a), fmaf(c, tanh_fast(c), c));
        }
        sts128(gx + j * 512, R[0], R[1], R[2], R[3]);
      }
      OBS(rel, 26);
      named_arrive(9, 256);
    }
  }
}

typedef CUresult (*EncFn)(CUtensorMap*, CUtensorMapDataType, cuuint32_t, void*, const cuuint64_t*, const cuuint64_t*, const cuuint32_t*,
                          const cuuint32_t*, CUtensorMapInterleave, CUtensorMapSwizzle, CUtensorMapL2promotion, CUtensorMapFloatOOBfill);
void enc(EncFn f, CUtensorMap* m, const void* ptr, const cuuint64_t (&gd)[4], const cuuint64_t (&gs)[3], const cuuint32_t (&bx)[4], CUtensorMapSwizzle sw) {
  cuuint32_t es[4] = {1, 1, 1, 1};
  f(m, CU_TENSOR_MAP_DATA_TYPE_BFLOAT16, 4, (void*)ptr, gd, gs, bx, es, CU_TENSOR_MAP_INTERLEAVE_NONE, sw,
    CU_TENSOR_MAP_L2_PROMOTION_L2_128B, CU_TENSOR_MAP_FLOAT_OOB_FILL_NONE);
}
}

extern "C" void kernel_launch(void* const* d_in, const int* in_sizes, int n_in, void* d_out, int out_size) {
  (void)in_sizes; (void)n_in; (void)out_size;
  void* fp = nullptr;
  cudaDriverEntryPointQueryResult qr;
  cudaGetDriverEntryPoint("cuTensorMapEncodeTiled", &fp, cudaEnableDefault, &qr);
  EncFn f = (EncFn)fp;
  CUtensorMap m_w1, m_w2, m_b14, m_a8, m_x;
  void* scr = nullptr;
  cudaGetSymbolAddress(&scr, g_scr);
  enc(f, &m_w1, d_in[4], {F_, 8, 2, S_ / 16}, {F_ * 4, F_ * 2, F_ * 32}, {64, 8, 2, 4}, CU_TENSOR_MAP_SWIZZLE_128B);
  enc(f, &m_w2, d_in[6], {S_, 1, 1, F_}, {S_ * 2, S_ * 2, S_ * 2}, {64, 1, 1, 64}, CU_TENSOR_MAP_SWIZZLE_128B);
  enc(f, &m_b14, scr, {64, 56, 1, G_END}, {128, GRP, GRP}, {64, 14, 1, 8}, CU_TENSOR_MAP_SWIZZLE_NONE);
  enc(f, &m_a8, scr, {64, 56, 1, G_END}, {128, GRP, GRP}, {64, 8, 1, 8}, CU_TENSOR_MAP_SWIZZLE_NONE);
  enc(f, &m_x, d_in[0], {D_, 1, 1, S_}, {D_ * 2, D_ * 2, D_ * 2}, {112, 1, 1, 64}, CU_TENSOR_MAP_SWIZZLE_NONE);
  Params p;
  p.x = (const unsigned char*)d_in[0]; p.wqkv = (const unsigned char*)d_in[1]; p.wo = (const unsigned char*)d_in[2];
  p.w1 = (const unsigned char*)d_in[4]; p.b1 = (const unsigned short*)d_in[5];
  p.w2 = (const unsigned char*)d_in[6]; p.b2 = (const unsigned short*)d_in[7];
  p.out = (unsigned char*)d_out;
  cudaFuncSetAttribute(fused_kernel, cudaFuncAttributeMaxDynamicSharedMemorySize, SMEM_BYTES);
  fused_kernel<<<128, NTHREADS, SMEM_BYTES, cudaStreamPerThread>>>(m_w1, m_w2, m_b14, m_a8, m_x, p);
}
```

```cpp
#include <cuda_runtime.h>
#include <cuda.h>
#include <cuda_bf16.h>
#include <stdint.h>

template<int TA, int TB> __device__ __forceinline__ void wgmma_n112(float (&d)[56], uint32_t al, uint32_t ah, uint32_t bl, uint32_t bh, int sc) {
  asm volatile("{\n.reg .pred p;\n.reg .b64 a, b;\nsetp.ne.b32 p, %60, 0;\nmov.b64 a, {%56, %57};\nmov.b64 b, {%58, %59};\n"
    "wgmma.mma_async.sync.aligned.m64n112k16.f32.bf16.bf16 {%0, %1, %2, %3, %4, %5, %6, %7, %8, %9, %10, %11, %12, %13, %14, %15, %16, %17, %18, %19, %20, %21, %22, %23, %24, %25, %26, %27, %28, %29, %30, %31, %32, %33, %34, %35, %36, %37, %38, %39, %40, %41, %42, %43, %44, %45, %46, %47, %48, %49, %50, %51, %52, %53, %54, %55}, a, b, p, 1, 1, %61, %62;\n}\n"
    : "+f"(d[0]), "+f"(d[1]), "+f"(d[2]), "+f"(d[3]), "+f"(d[4]), "+f"(d[5]), "+f"(d[6]), "+f"(d[7]), "+f"(d[8]), "+f"(d[9]), "+f"(d[10]), "+f"(d[11]), "+f"(d[12]), "+f"(d[13]), "+f"(d[14]), "+f"(d[15]), "+f"(d[16]), "+f"(d[17]), "+f"(d[18]), "+f"(d[19]), "+f"(d[20]), "+f"(d[21]), "+f"(d[22]), "+f"(d[23]), "+f"(d[24]), "+f"(d[25]), "+f"(d[26]), "+f"(d[27]), "+f"(d[28]), "+f"(d[29]), "+f"(d[30]), "+f"(d[31]), "+f"(d[32]), "+f"(d[33]), "+f"(d[34]), "+f"(d[35]), "+f"(d[36]), "+f"(d[37]), "+f"(d[38]), "+f"(d[39]), "+f"(d[40]), "+f"(d[41]), "+f"(d[42]), "+f"(d[43]), "+f"(d[44]), "+f"(d[45]), "+f"(d[46]), "+f"(d[47]), "+f"(d[48]), "+f"(d[49]), "+f"(d[50]), "+f"(d[51]), "+f"(d[52]), "+f"(d[53]), "+f"(d[54]), "+f"(d[55])
    : "r"(al), "r"(ah), "r"(bl), "r"(bh), "r"(sc), "n"(TA), "n"(TB));
}

template<int TB> __device__ __forceinline__ void wgmma_rs_n80(float (&d)[40], const uint32_t (&a)[4], uint32_t bl, uint32_t bh, int sc) {
  asm volatile("{\n.reg .pred p;\n.reg .b64 b;\nsetp.ne.b32 p, %46, 0;\nmov.b64 b, {%44, %45};\n"
    "wgmma.mma_async.sync.aligned.m64n80k16.f32.bf16.bf16 {%0, %1, %2, %3, %4, %5, %6, %7, %8, %9, %10, %11, %12, %13, %14, %15, %16, %17, %18, %19, %20, %21, %22, %23, %24, %25, %26, %27, %28, %29, %30, %31, %32, %33, %34, %35, %36, %37, %38, %39}, {%40, %41, %42, %43}, b, p, 1, 1, %47;\n}\n"
    : "+f"(d[0]), "+f"(d[1]), "+f"(d[2]), "+f"(d[3]), "+f"(d[4]), "+f"(d[5]), "+f"(d[6]), "+f"(d[7]), "+f"(d[8]), "+f"(d[9]), "+f"(d[10]), "+f"(d[11]), "+f"(d[12]), "+f"(d[13]), "+f"(d[14]), "+f"(d[15]), "+f"(d[16]), "+f"(d[17]), "+f"(d[18]), "+f"(d[19]), "+f"(d[20]), "+f"(d[21]), "+f"(d[22]), "+f"(d[23]), "+f"(d[24]), "+f"(d[25]), "+f"(d[26]), "+f"(d[27]), "+f"(d[28]), "+f"(d[29]), "+f"(d[30]), "+f"(d[31]), "+f"(d[32]), "+f"(d[33]), "+f"(d[34]), "+f"(d[35]), "+f"(d[36]), "+f"(d[37]), "+f"(d[38]), "+f"(d[39])
    : "r"(a[0]), "r"(a[1]), "r"(a[2]), "r"(a[3]), "r"(bl), "r"(bh), "r"(sc), "n"(TB));
}

template<int TB> __device__ __forceinline__ void wgmma_rs_n32(float (&d)[16], const uint32_t (&a)[4], uint32_t bl, uint32_t bh, int sc) {
  asm volatile("{\n.reg .pred p;\n.reg .b64 b;\nsetp.ne.b32 p, %22, 0;\nmov.b64 b, {%20, %21};\n"
    "wgmma.mma_async.sync.aligned.m64n32k16.f32.bf16.bf16 {%0, %1, %2, %3, %4, %5, %6, %7, %8, %9, %10, %11, %12, %13, %14, %15}, {%16, %17, %18, %19}, b, p, 1, 1, %23;\n}\n"
    : "+f"(d[0]), "+f"(d[1]), "+f"(d[2]), "+f"(d[3]), "+f"(d[4]), "+f"(d[5]), "+f"(d[6]), "+f"(d[7]), "+f"(d[8]), "+f"(d[9]), "+f"(d[10]), "+f"(d[11]), "+f"(d[12]), "+f"(d[13]), "+f"(d[14]), "+f"(d[15])
    : "r"(a[0]), "r"(a[1]), "r"(a[2]), "r"(a[3]), "r"(bl), "r"(bh), "r"(sc), "n"(TB));
}

namespace {
constexpr int S_ = 2048, D_ = 448, F_ = 1792;
constexpr int SLOT = 22528, BT = 14336;
constexpr int OFF_KV = 8 * SLOT;
constexpr int KV = 10 * 1792;
constexpr int OFF_PART = OFF_KV + 2 * BT;
constexpr int OFF_U = OFF_KV + 10 * 3584;
constexpr int OFF_BAR = OFF_U + BT;
constexpr uint32_t base = 1024, bars = base + OFF_BAR;
constexpr int OFF_OBS = OFF_BAR + 256;
constexpr int SMEM_BYTES = OFF_OBS + 768;
#ifdef TUNE
#define TV(i) p.tune[i]
const char* tune_names[] = {"DLY_B", "DLY_W", "TPW", "DLY_R", "PF0", "PACE1", "PACE2", "TRIG0", "TRIG1", "POLL0", "MODE_B", "X1", "STG_S", "PS_H", "PS_N"};
int tune_vals[15] = {900, 4300, 210, 1600, 2800, 420, 420, 3600, 900, 24, 0, 0, 2, 0, 300};
constexpr int NTUNE = 15;
#define DLY_B TV(0)
#define DLY_W TV(1)
#define TPW TV(2)
#define DLY_R TV(3)
#define PF0 TV(4)
#define PACE1 TV(5)
#define PACE2 TV(6)
#define TRIG0 TV(7)
#define TRIG1 TV(8)
#define POLL0 TV(9)
#define MODE_B TV(10)
#define X1 TV(11)
#define STG_S TV(12)
#define PS_H TV(13)
#define PS_N TV(14)
#else
#ifndef DLY_B
#define DLY_B 900
#endif
#ifndef DLY_W
#define DLY_W 4300
#endif
#ifndef TPW
#define TPW 210
#endif
#ifndef DLY_R
#define DLY_R 1600
#endif
#ifndef PF0
#define PF0 2800
#endif
#ifndef PACE1
#define PACE1 420
#endif
#ifndef PACE2
#define PACE2 420
#endif
#ifndef TRIG0
#define TRIG0 3600
#endif
#ifndef TRIG1
#define TRIG1 900
#endif
#ifndef POLL0
#define POLL0 24
#endif
#ifndef MODE_B
#define MODE_B 0
#endif
#ifndef STG_S
#define STG_S 2
#endif
#ifndef PS_H
#define PS_H 0
#endif
#ifndef PS_N
#define PS_N 300
#endif
#endif
#ifndef SA
#define SA 1
#endif
#ifndef SB
#define SB 8
#endif
#ifndef PFS
#define PFS 0
#endif
#ifndef PS_O
#define PS_O 0
#endif
#ifndef HK
#define HK 1
#endif
#ifndef HE
#define HE 1
#endif
#ifdef DBG_OBS
__device__ int g_obs[128 * 128];
#define OBS(c, i) asm volatile("{\n.reg .pred p;\n.reg .u32 k;\nsetp.ne.u32 p, %1, 0;\nmov.u32 k, %%clock;\nsub.u32 k, k, %2;\n@p st.shared.u32 [%0], k;\n}" :: "r"(base + OFF_OBS + (i) * 4), "r"((uint32_t)(c)), "r"(t0) : "memory")
#else
#define OBS(c, i) do {} while (0)
#endif
constexpr int NTHREADS = 384;
constexpr float SCALE = 0.18898223650461361f, LOG2E = 1.4426950408889634f;

constexpr int GRP = 7168;
constexpr int G_H = 0, G_XN = 256, G_O = 512, G_W = 768, G_U = G_W + 168, G_WO = G_U + 224, G_HALO = G_WO + 56, G_END = G_HALO + 128;
constexpr int SCR_BYTES = G_END * GRP;
__device__ __align__(1024) unsigned char g_scr[SCR_BYTES];
constexpr int C_TICKET = 0, C_W = 1, C_H = 2, C_U = 4, C_W2 = 5, C_O = 8, C_HALO = 40, C_END = 168;
__device__ __align__(128) unsigned g_cnt[C_END * 32];

__device__ __forceinline__ uint32_t smem_u32(const void* p) { return (uint32_t)__cvta_generic_to_shared(p); }
__device__ __forceinline__ void mbar_init(uint32_t bar, uint32_t cnt) { asm volatile("mbarrier.init.shared::cta.b64 [%0], %1;" :: "r"(bar), "r"(cnt)); }
__device__ __forceinline__ void mbar_expect_tx(uint32_t bar, uint32_t bytes) { asm volatile("mbarrier.arrive.expect_tx.shared::cta.b64 _, [%0], %1;" :: "r"(bar), "r"(bytes) : "memory"); }
__device__ __forceinline__ void mbar_arrive(uint32_t bar) { asm volatile("mbarrier.arrive.shared::cta.b64 _, [%0];" :: "r"(bar) : "memory"); }
__device__ __forceinline__ void mbar_wait(uint32_t bar, uint32_t parity) {
  asm volatile("{\n.reg .pred p;\n.reg .u32 n;\nmov.u32 n, 0;\nLAB_WAIT:\n"
               "mbarrier.try_wait.parity.shared::cta.b64 p, [%0], %1;\n@p bra DONE;\n"
               "add.u32 n, n, 1;\nsetp.lt.u32 p, n, 4000000;\n@p bra LAB_WAIT;\ntrap;\nDONE:\n}" :: "r"(bar), "r"(parity) : "memory");
}
__device__ __forceinline__ uint32_t mbar_try(uint32_t bar, uint32_t parity) {
  uint32_t ok;
  asm volatile("{\n.reg .pred p;\nmbarrier.test_wait.parity.shared::cta.b64 p, [%1], %2;\nselp.u32 %0, 1, 0, p;\n}" : "=r"(ok) : "r"(bar), "r"(parity) : "memory");
  return ok;
}
__device__ __forceinline__ void tma4d(uint32_t dst, const CUtensorMap* m, int c0, int c1, int c3, uint32_t bar) {
  asm volatile("cp.async.bulk.tensor.4d.shared::cluster.global.mbarrier::complete_tx::bytes [%0], [%1, {%3, %4, %6, %5}], [%2];"
               :: "r"(dst), "l"(m), "r"(bar), "r"(c0), "r"(c1), "r"(c3), "r"(0) : "memory");
}
__device__ __forceinline__ void tma_store(const CUtensorMap* m, int c1, int c3, uint32_t src) {
  asm volatile("cp.async.bulk.tensor.4d.global.shared::cta.bulk_group [%0, {%4, %2, %4, %3}], [%1];" :: "l"(m), "r"(src), "r"(c1), "r"(c3), "r"(0) : "memory");
}
__device__ __forceinline__ void bulk_g2s(uint32_t dst, const void* src, uint32_t bytes, uint32_t bar) {
  asm volatile("cp.async.bulk.shared::cluster.global.mbarrier::complete_tx::bytes [%0], [%1], %2, [%3];" :: "r"(dst), "l"(src), "r"(bytes), "r"(bar) : "memory");
}
__device__ __forceinline__ void bulk_s2g(void* dst, uint32_t src, uint32_t bytes) {
  asm volatile("cp.async.bulk.global.shared::cta.bulk_group [%0], [%1], %2;" :: "l"(dst), "r"(src), "r"(bytes) : "memory");
}
__device__ __forceinline__ void wg_fence() { asm volatile("wgmma.fence.sync.aligned;" ::: "memory"); }
__device__ __forceinline__ void wg_commit() { asm volatile("wgmma.commit_group.sync.aligned;" ::: "memory"); }
template <int N> __device__ __forceinline__ void wg_wait() { asm volatile("wgmma.wait_group.sync.aligned %0;" :: "n"(N) : "memory"); }
__device__ __forceinline__ void proxy_fence() { asm volatile("fence.proxy.async.global;" ::: "memory"); }
#ifndef LIGHT
#define LIGHT 1
#endif
__device__ __forceinline__ void smem_fence() {
  if (LIGHT == 2) return;
  if (LIGHT) asm volatile("mbarrier.init.shared::cta.b64 [%0], 1;" :: "r"(base + OFF_BAR + 248) : "memory");
  else asm volatile("fence.proxy.async.shared::cta;" ::: "memory");
}
__device__ __forceinline__ void publish(int i) {
  asm volatile("cp.async.bulk.commit_group;" ::: "memory");
  asm volatile("cp.async.bulk.wait_group 0;" ::: "memory");
  asm volatile("red.relaxed.gpu.global.inc.u32 [%0], 0xffffffff;" :: "l"(&g_cnt[i * 32]) : "memory");
}
__device__ __forceinline__ void spin_ge(int i, unsigned target) {
  asm volatile("{\n.reg .pred p;\n.reg .u32 n, v;\nmov.u32 n, 0;\nLAB_SPIN:\n"
               "ld.relaxed.gpu.global.u32 v, [%0];\nsetp.ge.u32 p, v, %1;\n@p bra DONE;\n"
               "add.u32 n, n, 1;\nsetp.lt.u32 p, n, 4000000;\n@p bra LAB_SPIN;\ntrap;\nDONE:\n}" :: "l"(&g_cnt[i * 32]), "r"(target) : "memory");
}
__device__ __forceinline__ unsigned ld_relaxed(int i) { unsigned v; asm volatile("ld.relaxed.gpu.global.u32 %0, [%1];" : "=r"(v) : "l"(&g_cnt[i * 32]) : "memory"); return v; }
__device__ __forceinline__ bool elect() {
  uint32_t r; asm volatile("{\n.reg .pred p;\nelect.sync _|p, 0xffffffff;\nselp.u32 %0, 1, 0, p;\n}" : "=r"(r)); return r != 0;
}
__device__ __forceinline__ void wait_until(uint32_t tn) { while ((int)(clock() - tn) < 0) __nanosleep(20); }
__device__ __forceinline__ void store_paced(unsigned char* dst, int dstep, uint32_t src, int sstep, int n, int gap) {
  uint32_t tn = clock();
#pragma unroll 1
  for (int i = 0; i < n; i++) { wait_until(tn); bulk_s2g(dst, src, 1792); dst += dstep; src += sstep; tn += gap; }
}
__device__ __forceinline__ uint4 lds128(uint32_t a) { uint4 v; asm volatile("ld.shared.v4.u32 {%0,%1,%2,%3}, [%4];" : "=r"(v.x), "=r"(v.y), "=r"(v.z), "=r"(v.w) : "r"(a) : "memory"); return v; }
__device__ __forceinline__ uint32_t lds32(uint32_t a) { uint32_t v; asm volatile("ld.shared.u32 %0, [%1];" : "=r"(v) : "r"(a) : "memory"); return v; }
__device__ __forceinline__ void sts128(uint32_t p, uint32_t a, uint32_t b, uint32_t c, uint32_t d) { asm volatile("st.shared.v4.u32 [%0], {%1,%2,%3,%4};" :: "r"(p), "r"(a), "r"(b), "r"(c), "r"(d) : "memory"); }
__device__ __forceinline__ void sts64(uint32_t p, float a, float b) { asm volatile("st.shared.v2.f32 [%0], {%1,%2};" :: "r"(p), "f"(a), "f"(b) : "memory"); }
__device__ __forceinline__ void named_sync(int id, int n) { asm volatile("bar.sync %0, %1;" :: "r"(id), "r"(n) : "memory"); }
__device__ __forceinline__ void named_arrive(int id, int n) { asm volatile("bar.arrive %0, %1;" :: "r"(id), "r"(n) : "memory"); }
__device__ __forceinline__ constexpr uint32_t dlo(uint32_t off, uint32_t lbo) { return ((base + off) >> 4) | (lbo >> 4 << 16); }
__device__ __forceinline__ uint32_t pack2(float lo, float hi) { uint32_t r; asm("cvt.rn.bf16x2.f32 %0, %1, %2;" : "=r"(r) : "f"(hi), "f"(lo)); return r; }
__device__ __forceinline__ float bf_lo(uint32_t v) { return __uint_as_float(v << 16); }
__device__ __forceinline__ float bf_hi(uint32_t v) { return __uint_as_float(v & 0xffff0000u); }
__device__ __forceinline__ float rbf(float x) { return bf_lo(pack2(x, 0.f)); }
__device__ __forceinline__ uint32_t hsub2(uint32_t a, uint32_t b) { uint32_t r; asm("sub.rn.bf16x2 %0, %1, %2;" : "=r"(r) : "r"(a), "r"(b)); return r; }
__device__ __forceinline__ uint32_t hadd2(uint32_t a, uint32_t b) { uint32_t r; asm("add.rn.bf16x2 %0, %1, %2;" : "=r"(r) : "r"(a), "r"(b)); return r; }
__device__ __forceinline__ uint32_t hmul2(uint32_t a, uint32_t b) { uint32_t r; asm("mul.rn.bf16x2 %0, %1, %2;" : "=r"(r) : "r"(a), "r"(b)); return r; }
__device__ __forceinline__ uint32_t hfma2(uint32_t a, uint32_t b, uint32_t c) { uint32_t r; asm("fma.rn.bf16x2 %0, %1, %2, %3;" : "=r"(r) : "r"(a), "r"(b), "r"(c)); return r; }
__device__ __forceinline__ float tanh_fast(float x) { float r; asm("tanh.approx.f32 %0, %1;" : "=f"(r) : "f"(x)); return r; }
__device__ __forceinline__ float rcp_fast(float x) { float r; asm("rcp.approx.ftz.f32 %0, %1;" : "=f"(r) : "f"(x)); return r; }
__device__ __forceinline__ float ex2_fast(float x) { float r; asm("ex2.approx.ftz.f32 %0, %1;" : "=f"(r) : "f"(x)); return r; }
__device__ __forceinline__ void stsm4(uint32_t addr, uint32_t a, uint32_t b, uint32_t c, uint32_t d) {
  asm volatile("stmatrix.sync.aligned.m8n8.x4.shared.b16 [%0], {%1,%2,%3,%4};" :: "r"(addr), "r"(a), "r"(b), "r"(c), "r"(d) : "memory");
}
__device__ __forceinline__ void stsm2(uint32_t addr, uint32_t a, uint32_t b) {
  asm volatile("stmatrix.sync.aligned.m8n8.x2.shared.b16 [%0], {%1,%2};" :: "r"(addr), "r"(a), "r"(b) : "memory");
}
__device__ __forceinline__ void load_row(uint32_t (&r)[14], const unsigned char* p, int t) {
#pragma unroll
  for (int i = 0; i < 3; i++)
    asm volatile("ld.global.nc.L1::no_allocate.v4.u32 {%0,%1,%2,%3}, [%4];" : "=r"(r[4 * i]), "=r"(r[4 * i + 1]), "=r"(r[4 * i + 2]), "=r"(r[4 * i + 3]) : "l"(p + i * 64 + t * 16));
  asm volatile("ld.global.nc.L1::no_allocate.v2.u32 {%0,%1}, [%2];" : "=r"(r[12]), "=r"(r[13]) : "l"(p + 192 + t * 8));
}

template <int N> __device__ __forceinline__ void fresh(float (&a)[N]) {
#pragma unroll
  for (int i = 0; i < N; i++) asm volatile("" : "=f"(a[i]));
}
__device__ __forceinline__ void pin(uint32_t (&a)[4]) { asm volatile("" : "+r"(a[0]), "+r"(a[1]), "+r"(a[2]), "+r"(a[3])); }
constexpr int B_EMPTY = 64, B_F0 = 128, B_F1 = 136, B_F2 = 144, B_F3 = 152, B_HALO = 160, B_RT = 176, B_RES = 184, B_TS = 192, B_F1B = 200;
constexpr int N_GO = 6, N_DONE = 7;
__device__ __forceinline__ void arrive_if(int id, bool on) {
  asm volatile("{\n.reg .pred p;\nsetp.ne.u32 p, %1, 0;\n@p bar.arrive %0, 256;\n}" :: "r"(id), "r"((uint32_t)on) : "memory");
}
template <int TA, class Hook>
__device__ __forceinline__ void stage(float (&acc)[56], uint32_t ah, uint32_t bh, int sb, int sa, uint32_t par, uint32_t& ok, bool first, bool rel, Hook hook) {
  if (!ok) mbar_wait(bars + sb * 8, par);
  wg_fence();
#pragma unroll
  for (int k = 0; k < 4; k++) {
    wgmma_n112<TA, 1>(acc, dlo(sa * SLOT + k * (TA ? 2048 : 256), TA ? 8192 : 128), ah, dlo(sb * SLOT + 8192 + k * 3584, 1792), bh, k || !first);
    if (k == 1) ok = mbar_try(bars + ((sb + 1) & 7) * 8, sb == 7 ? par ^ 1 : par);
    hook(k);
  }
  wg_commit();
  wg_wait<1>();
  if (rel) mbar_arrive(bars + B_EMPTY + ((sb + 7) & 7) * 8);
}

template <uint32_t BYTES>
__device__ __forceinline__ void produce(int c, int cend, int rot, const CUtensorMap* mp, int c0, int c1, int s1, int c3, int s3, int tr = 0) {
#pragma unroll 1
  for (; c < cend; c++) {
    const uint32_t fb = base + OFF_BAR + (c & 7) * 8, dst = base + (BYTES ? 8192 : 0) + ((c + rot) & 7) * SLOT;
    mbar_wait(fb + B_EMPTY, ((c >> 3) & 1) ^ 1);
#ifdef DBG_TRACE
    if (BYTES) { const uint32_t t0 = 0; OBS(1, 32 + tr + c); }
#endif
    if (BYTES) mbar_expect_tx(fb, BYTES);
    tma4d(dst, mp, c0, c1, c3, fb);
    c1 += s1; c3 += s3;
  }
}

struct Params {
  const unsigned char *x, *wqkv, *wo, *w1, *w2;
  const unsigned short *b1, *b2;
  unsigned char* out;
  uint32_t dw, dx, db, dk;
#ifdef TUNE
  int tune[NTUNE];
#endif
};

__global__ void __launch_bounds__(NTHREADS, 1)
fused_kernel(const __grid_constant__ CUtensorMap m_w1, const __grid_constant__ CUtensorMap m_w2, const __grid_constant__ CUtensorMap m_b14,
             const __grid_constant__ CUtensorMap m_a8, const __grid_constant__ CUtensorMap m_x, const Params p) {
  extern __shared__ __align__(1024) unsigned char smem_raw[];
  const uint32_t t0 = clock();
  const int tid = threadIdx.x, lane = tid & 31, b = blockIdx.x;
  const int g = lane >> 2, t = lane & 3, r8 = lane & 7, mi = lane >> 3;
  const int tg = (tid & 128) + b;
  const unsigned char* xrow = p.x + ((tg >> 1) * 16 + (tg & 1) + 2 * g) * (D_ * 2) + ((tid >> 5) & 3) * 224;
  uint32_t H[14];
  if (tid < 128) load_row(H, xrow, t);
  const int warp = __shfl_sync(0xffffffffu, tid >> 5, 0);
  const int dt = b & 3, mt = b >> 2;
  const bool g1 = b < 112;
  const int ft = mt, d1 = dt;
  if (warp >= 8) {
    if (warp == 8) {
      if (elect()) {
        if (smem_u32(smem_raw) != base) asm volatile("trap;");
#pragma unroll
        for (int i = 0; i < 26; i++) mbar_init(bars + i * 8, i * 8 == B_F1 && !g1 ? 3 : 1);
        asm volatile("fence.mbarrier_init.release.cluster;" ::: "memory");
      }
      __syncwarp();
      named_arrive(12, 160); named_arrive(13, 160);
    }
    named_sync(15, 128);
    asm volatile("setmaxnreg.dec.sync.aligned.u32 40;");
    if (warp == 8) {
      unsigned tk = 0;
      if (elect()) {
        asm volatile("prefetch.tensormap [%0];" :: "l"(&m_w1) : "memory");
        asm volatile("prefetch.tensormap [%0];" :: "l"(&m_a8) : "memory");
        if (g1) {
#pragma unroll 1
          for (int c = 0; c < 8; c++) { wait_until(t0 + DLY_W + c * TPW); tma4d(base + c * SLOT, &m_w1, ft * 64, 0, c * 4, bars + c * 8); }
          produce<0>(8, 32, 0, &m_w1, ft * 64, 0, 0, 32, 4);
        } else {
          const int bytes = (dt < 3 ? 32 : 16) * 2688;
          wait_until(t0 + DLY_R);
          mbar_expect_tx(bars + B_RT, bytes);
          bulk_g2s(base, p.wqkv + ((mt & 3) * 112 + dt * 32) * 2688, bytes, bars + B_RT);
        }
        mbar_wait(bars + B_F1, 0);
        produce<0>(0, 7, 0, &m_a8, 0, 0, 8, G_XN + mt * 8, 0);
        mbar_wait(bars + B_EMPTY + 5 * 8, 0);
        produce<0>(21, 49, 2, &m_w2, mt * 64, 0, 0, 0, 64);
        mbar_wait(bars + B_F3, 0);
        OBS(1, 22);
        produce<0>(49, 56, 2, &m_a8, 0, 0, 8, G_O + mt * 8, 0);
        tk = atomicInc(&g_cnt[C_TICKET * 32], 0xffffffffu);
      }
      if (__any_sync(0xffffffffu, tk == 127)) {
#pragma unroll 1
        for (int i = lane; i < C_END; i += 32) g_cnt[i * 32] = 0;
      }
    } else if (warp == 9) {
      if (elect()) {
        asm volatile("prefetch.tensormap [%0];" :: "l"(&m_b14) : "memory");
        asm volatile("prefetch.tensormap [%0];" :: "l"(&m_w2) : "memory");
        asm volatile("prefetch.tensormap [%0];" :: "l"(&m_x) : "memory");
        if (g1) {
          spin_ge(C_H, 128);
          OBS(1, 16);
          produce<SLOT>(0, STG_S, 0, &m_b14, 0, d1 * 14, 0, G_H, 8);
          mbar_arrive(bars + B_TS);
          produce<SLOT>(STG_S, 16, 0, &m_b14, 0, d1 * 14, 0, G_H + STG_S * 8, 8);
          mbar_wait(bars + B_F0, 0);
          OBS(1, 17);
          produce<SLOT>(16, 32, 0, &m_b14, 0, d1 * 14, 0, G_H + 128, 8);
        }
        mbar_wait(bars + B_F1, 0);
        OBS(1, 18);
        produce<SLOT>(0, 7, 0, &m_b14, 0, dt * 14, 0, G_W, 8, 32);
        mbar_wait(bars + B_F1B, 0);
        produce<BT>(7, 21, 0, &m_b14, 0, dt * 14, 0, G_W + 56, 8, 32);
        mbar_wait(bars + B_F2, 0);
        OBS(1, 20);
        produce<SLOT>(21, 56, 0, &m_b14, 0, dt * 14, 0, G_U, 8, 32);
      }
    } else if (warp == 10) {
      uint32_t tn = t0 + PF0;
      const unsigned char* src = p.w1 + PFS * 458752 + b * 3584 + lane * 128;
      bool useen = false;
#pragma unroll 1
      for (int i = PFS; i < 32; i++) {
        if (!useen && i >= POLL0) {
          while ((int)(clock() - tn) < 0 && !useen) useen = ld_relaxed(C_U) >= 128;
          if (useen && lane == 0) mbar_arrive(bars + B_F2);
        }
        wait_until(tn);
        if (i == 16) src = p.w2 + b * 3584 + lane * 128;
        if (lane < 28) asm volatile("prefetch.global.L2 [%0];" :: "l"(src) : "memory");
        __syncwarp();
        src += 458752;
        tn += i < 16 ? PACE1 : PACE2;
      }
      if (!useen) { spin_ge(C_U, 128); if (lane == 0) mbar_arrive(bars + B_F2); }
      spin_ge(C_O + mt, PS_O ? 16 : 4);
      if (lane == 0) mbar_arrive(bars + B_F3);
    } else {
#pragma unroll 1
      for (int i = 0; i < 4; i++) {
        const int v = MODE_B ? i : i ^ (i >> 1);
        unsigned char* dst = g_scr + (((v & 1) ? G_H : G_XN) + (i >> 1) * 128 + b) * GRP;
        asm volatile("" : "+l"(dst));
        if (i < 2 || MODE_B) named_sync(i == 3 ? 9 : (i == 2 ? 8 : (i ? 10 : 14)), 160);
        else if (i == 2) { named_sync(8, 160); named_sync(9, 160); }
        const bool slow = i > 1 + MODE_B && g1;
        if (slow) mbar_wait(bars + B_TS, 0);
        smem_fence();
        if (elect()) {
          if (slow) store_paced(dst, 1792, base + OFF_KV + v * GRP, 1792, 4, v == 3 ? PS_H : PS_N);
          else bulk_s2g(dst, base + OFF_KV + v * GRP, GRP);
          if (i) publish(v == 2 ? C_W : C_H + (i >> 1));
        }
        __syncwarp();
        OBS(lane == 0 && (v & 1), 3 + (i >> 1));
      }
      spin_ge(C_W, 144);
      if (lane == 0) mbar_arrive(bars + B_F1);
      spin_ge(C_W2, 16);
      if (lane == 0) mbar_arrive(bars + B_F1B);
      if (mt == 0) {
#pragma unroll
        for (int i = 0; i < 14; i++) sts128(base + OFF_KV + (i / 7) * KV + (i % 7) * 512 + lane * 16, 0, 0, 0, 0);
        smem_fence();
        __syncwarp();
        if (lane < 2) mbar_arrive(bars + B_HALO + lane * 8);
      }
#pragma unroll 1
      for (int i = 0; i < 2; i++) {
        unsigned char* hg = g_scr + (G_HALO + b) * GRP + i * 3584;
        named_sync(i ? 0 : 11, 64);
        smem_fence();
        if (mt < 31 && elect()) { bulk_s2g(hg, base + OFF_KV + i * KV + 8 * 1792, 3584); publish(C_HALO + b); }
        OBS(lane == 0, i ? 15 : 23);
        if (mt > 0) {
          spin_ge(C_HALO + b - 4, i + 1);
          if (elect()) { mbar_expect_tx(bars + B_HALO + i * 8, 3584); bulk_g2s(base + OFF_KV + i * KV, hg - 4 * GRP, 3584, bars + B_HALO + i * 8); }
        }
        __syncwarp();
      }
      named_sync(11, 64);
      if (elect()) { mbar_expect_tx(bars + B_RES, BT); tma4d(base + OFF_KV, &m_x, dt * 112, 0, mt * 64, bars + B_RES); }
    }
  } else {
    const int wg = warp >> 2, w4 = warp & 3;
    const bool rel = (tid & 127) == 0;
    if (wg) { wait_until(t0 + DLY_B); load_row(H, xrow, t); }
    {
      const uint32_t part = base + OFF_PART + wg * 512 + g * 32, st = base + OFF_KV + wg * BT + (w4 * 14 + mi) * 128 + r8 * 16;
#pragma unroll
      for (int ln = 0; ln < 2; ln++) {
        float s0 = 0.f, s1 = 0.f, q0 = 0.f, q1 = 0.f;
#pragma unroll
        for (int j = 0; j < 14; j++) { const float a = bf_lo(H[j]), c = bf_hi(H[j]); s0 += a; s1 += c; q0 = fmaf(a, a, q0); q1 = fmaf(c, c, q1); }
        s0 += s1; q0 += q1;
#pragma unroll
        for (int o = 1; o < 4; o <<= 1) { s0 += __shfl_xor_sync(0xffffffffu, s0, o); q0 += __shfl_xor_sync(0xffffffffu, q0, o); }
        if (t == 0) sts64(part + ln * 256 + w4 * 8, s0, q0);
        OBS(tid == 0 && ln == 0, 0);
        named_sync(1 + wg, 128);
        const uint4 u = lds128(part + ln * 256), v = lds128(part + ln * 256 + 16);
        const float mean = ((__uint_as_float(u.x) + __uint_as_float(u.z)) + (__uint_as_float(v.x) + __uint_as_float(v.z))) * (1.0f / D_);
        const float sq = (__uint_as_float(u.y) + __uint_as_float(u.w)) + (__uint_as_float(v.y) + __uint_as_float(v.w));
        float sd;
        asm("sqrt.approx.ftz.f32 %0, %1;" : "=f"(sd) : "f"(rbf(rbf(fmaxf(fmaf(-mean, mean, sq * (1.0f / D_)), 0.f)) + 1e-5f)));
        const float r = rcp_fast(rbf(sd)), rh = rbf(r);
        const uint32_t m2 = pack2(mean, mean), rh2 = pack2(rh, rh), rl2 = pack2(r - rh, r - rh);
#pragma unroll
        for (int j = 0; j < 14; j++) { const uint32_t d = hsub2(H[j], m2); H[j] = hfma2(d, rh2, hmul2(d, rl2)); }
#pragma unroll
        for (int i = 0; i < 3; i++) stsm4(st + ln * GRP + i * 512, H[4 * i], H[4 * i + 1], H[4 * i + 2], H[4 * i + 3]);
        stsm2(st + ln * GRP + 1536, H[12], H[13]);
        named_arrive(ln ? 10 - wg : 14 - 6 * wg, 160);
      }
      OBS(rel, 1 + wg);
    }
    named_sync(12 + wg, 160);
    asm volatile("setmaxnreg.inc.sync.aligned.u32 232;");
    uint32_t hb[2];
#pragma unroll
    for (int i = 0; i < 2; i++) {
      asm volatile("ld.relaxed.cta.global.u16 %0, [%1];" : "=r"(hb[i]) : "l"((wg ? p.b2 + mt * 64 : p.b1 + (g1 ? ft * 64 : 0)) + w4 * 16 + g + i * 8) : "memory");
    }
    if (!g1) {
      const int kg0 = (mt & 3) * 14 + dt * 4, nk = dt < 3 ? 4 : 2;
      mbar_wait(bars + B_RT, 0);
      OBS(tid == 0, 7);
      if (w4 < nk) {
        const int c = (r8 + mi + wg * 4) & 7;
        const uint32_t src = base + ((r8 >> 1) * 2 * nk + 2 * w4 + (r8 & 1)) * 2688 + c * 16, dst = base + (12 + w4) * GRP + c * 128 + r8 * 16;
#pragma unroll 1
        for (int m = 0; m < 3; m++) {
          uint4 v[7];
#pragma unroll
          for (int l = 0; l < 7; l++) v[l] = lds128(src + m * 896 + l * 128);
#pragma unroll
          for (int l = 0; l < 7; l++) sts128(dst + m * 4 * GRP + l * 1024, v[l].x, v[l].y, v[l].z, v[l].w);
        }
      }
      smem_fence();
      named_sync(0, 256);
      OBS(tid == 0, 5);
      if (warp == 0 && elect()) {
        mbar_expect_tx(bars + B_RT, nk * GRP);
        bulk_g2s(base, p.wo + kg0 * GRP, nk * GRP, bars + B_RT);
#pragma unroll
        for (int m = 0; m < 3; m++) {
          bulk_s2g(g_scr + (G_W + m * 56 + kg0) * GRP, base + (12 + (m + 1) % 3 * 4) * GRP, nk * GRP);
          if (m != 1) publish(m ? C_W2 : C_W);
        }
        mbar_arrive(bars + B_F1);
        OBS(1, 6);
      }
      if (wg) {
        mbar_wait(bars + B_RT, 1);
#pragma unroll 1
        for (int i = 0; i < nk; i++) {
          const uint32_t src = base + i * GRP + g * 896 + w4 * 224, st = base + (4 + i) * GRP + (w4 * 14 + mi) * 128 + r8 * 16;
#pragma unroll
          for (int j = 0; j < 3; j++) { const uint4 v = lds128(src + j * 64 + t * 16); stsm4(st + j * 512, v.x, v.y, v.z, v.w); }
          stsm2(st + 1536, lds32(src + 192 + t * 8), lds32(src + 196 + t * 8));
        }
        smem_fence();
        named_sync(2, 128);
        if (w4 == 0 && elect()) {
          bulk_s2g(g_scr + (G_WO + kg0) * GRP, base + 4 * GRP, nk * GRP);
          publish(C_U);
          mbar_arrive(bars + B_F1);
          OBS(1, 16);
        }
      }
      __syncwarp();
    }
    uint32_t ok = 0;
    auto nohook = [](int) {};
#ifdef DBG_OBS
#define OBS0(c, i) do { mbar_wait(bars + ((c) & 7) * 8, ((c) >> 3) & 1); ok = 1; OBS(rel, i); } while (0)
#else
#define OBS0(c, i) ok = 0
#endif
    const uint32_t gx = base + 8192 + (tid & 127) * 16;
    if (wg == 0) {
      float acc[56];
      const uint32_t ust = base + OFF_U + w4 * 3584 + (mi >> 1) * 128;
      if (g1) {
        if (w4 == 3 && TRIG1) {
          float z[4] = {};
          uint32_t tn = t0 + TRIG0;
#pragma unroll 1
          for (int n = 0; n < 64 && !mbar_try(bars + B_TS, 0); n++) {
            while ((int)(clock() - tn) < 0 && !mbar_try(bars + B_TS, 0));
            asm volatile("mma.sync.aligned.m16n8k16.row.col.f32.bf16.bf16.f32 {%0,%1,%2,%3}, {%4,%4,%4,%4}, {%4,%4}, {%0,%1,%2,%3};" : "+f"(z[0]), "+f"(z[1]), "+f"(z[2]), "+f"(z[3]) : "r"(threadIdx.y));
            tn += TRIG1 + __float_as_uint(z[0]);
          }
        }
#pragma unroll
        for (int i = 0; i < 56; i++) { acc[i] = bf_lo(hb[(i >> 1) & 1]); asm volatile("" : "+f"(acc[i])); }
        OBS0(0, 5);
#pragma unroll 1
        for (int r = 0; r < 4; r++)
#pragma unroll
          for (int c = 0; c < 8; c++) stage<1>(acc, p.dw, p.db, c, c, r & 1, ok, false, rel && (c || r), [&](int k) { if (c == 7 && k == 3 - HK) arrive_if(3, r == 3); });
        wg_wait<0>();
        if (rel) mbar_arrive(bars + B_EMPTY + 7 * 8);
        OBS(rel, 6);
#pragma unroll
        for (int n = 0; n < 14; n += 2) {
          uint32_t R[4];
#pragma unroll
          for (int j = 0; j < 4; j++) {
            const float a = acc[4 * n + 2 * j], c = acc[4 * n + 2 * j + 1];
            R[j] = pack2(fmaf(a, tanh_fast(a * fmaf(a * a, 0.0356774081f, 0.7978845608f)), a), fmaf(c, tanh_fast(c * fmaf(c * c, 0.0356774081f, 0.7978845608f)), c));
          }
          stsm4(ust + (mi & 1) * 1792 + r8 * 16 + n * 128, R[0], R[1], R[2], R[3]);
        }
        OBS(rel, 30);
        smem_fence();
        named_sync(1, 128);
        if (w4 == 0 && elect()) { tma_store(&m_b14, d1 * 14, G_U + ft * 8, base + OFF_U); publish(C_U); OBS(1, 7); }
        __syncwarp();
      } else named_arrive(3, 256);
      named_sync(4, 256);
      fresh(acc);
      OBS0(14, 9);
#pragma unroll
      for (int c = 14; c < 21; c++) stage<0>(acc, p.dx, p.db, c & 7, c - 14, (c >> 3) & 1, ok, c == 14, rel && c > 14, [&](int k) { if (c == 20 && k == 3 - HK) named_arrive(5, 256); });
      wg_wait<0>();
      if (rel) mbar_arrive(bars + B_EMPTY + 4 * 8);
      {
        uint32_t Q[8][4];
#pragma unroll
        for (int i = 0; i < 16; i++) {
          const int n = i - (i + 4) / 8;
#pragma unroll
          for (int h = 0; h < 2; h++) {
            const uint32_t v = pack2(acc[4 * n + 2 * h], acc[4 * n + 2 * h + 1]);
            Q[i >> 1][(i & 1) * 2 + h] = (i & 7) == 3 ? (t < 2 ? v : 0u) : ((i & 7) == 4 ? (t < 2 ? 0u : v) : v);
          }
        }
#pragma unroll
        for (int i = 0; i < 8; i++) pin(Q[i]);
        float Sc[4][40], O[4][16];
        mbar_wait(bars + B_HALO, 0);
        OBS(rel, 11);
#pragma unroll
        for (int hh = 0; hh < 4; hh++) fresh(Sc[hh]);
        wg_fence();
        named_sync(N_GO, 256);
#pragma unroll
        for (int k = 0; k < 2; k++)
#pragma unroll
          for (int hh = 0; hh < 4; hh++) {
            if (k == 1 && hh == 3) named_arrive(N_DONE, 256);
            wgmma_rs_n80<0>(Sc[hh], Q[hh * 2 + k], dlo(OFF_KV + (hh * 7 / 2 + 2 * k) * 128, 128), p.dk, k);
          }
        wg_commit();
        const bool e0 = 2 * t > g, e1 = 2 * t + 1 > g;
        const uint32_t em = (e0 ? 0xffffu : 0u) | (e1 ? 0xffff0000u : 0u);
        uint32_t L[4][2];
        wg_wait<0>();
        OBS(rel, 12);
        auto pick = [&](int w) {
#pragma unroll
          for (int hh = 0; hh < 4; hh++)
#pragma unroll
            for (int h = 0; h < 2; h++) {
              const int i = (2 * w + h) * 4 + 2 * h;
              L[hh][h] = pack2(e0 ? Sc[hh][i] : Sc[hh][i + 8], e1 ? Sc[hh][i + 1] : Sc[hh][i + 9]);
              asm volatile("" : "+r"(L[hh][h]));
            }
        };
        if (w4 == 0) pick(0); else if (w4 == 1) pick(1); else if (w4 == 2) pick(2); else pick(3);
        const bool edge = mt == 0 && w4 == 0;
        uint32_t A[4][5][4], sign = 0, low = lane < 16 ? ~0u : 0u;
        asm volatile("" : "+r"(low));
#pragma unroll
        for (int hh = 0; hh < 4; hh++) {
#pragma unroll
          for (int h = 0; h < 2; h++) {
            const uint32_t pk = pack2(bf_lo(L[hh][h]) * SCALE, bf_hi(L[hh][h]) * SCALE);
            const float l0 = edge && e0 ? -1e9f : bf_lo(pk), l1 = edge && e1 ? -1e9f : bf_hi(pk);
            float mx = fmaxf(l0, l1);
            mx = fmaxf(mx, __shfl_xor_sync(0xffffffffu, mx, 1));
            mx = fmaxf(mx, __shfl_xor_sync(0xffffffffu, mx, 2));
            const float p0 = ex2_fast((l0 - mx) * LOG2E), p1 = ex2_fast((l1 - mx) * LOG2E);
            float sm = p0 + p1;
            sm += __shfl_xor_sync(0xffffffffu, sm, 1);
            sm += __shfl_xor_sync(0xffffffffu, sm, 2);
            const float inv = rcp_fast(sm);
            const uint32_t pp = pack2(p0 * inv, p1 * inv);
#pragma unroll
            for (int j = 0; j < 5; j++) {
              const uint32_t m = j == w4 ? em : (j == w4 + 1 ? ~em : 0u);
              A[hh][j][3 * h] = pp & m & low; A[hh][j][1 + h] = pp & m & ~low;
            }
            sign |= pp;
          }
        }
#pragma unroll
        for (int hh = 0; hh < 4; hh++) fresh(O[hh]);
#pragma unroll
        for (int i = 0; i < 20; i++) pin(A[i / 5][i % 5]);
        OBS(rel, 13);
        mbar_wait(bars + B_HALO + 8 + (sign >> 31), 0);
        if (w4 == 0) named_arrive(11, 64);
        OBS(rel, 31);
        named_sync(N_GO, 256);
        wg_fence();
#pragma unroll
        for (int j = 0; j < 5; j++)
#pragma unroll
          for (int hh = 0; hh < 4; hh++) {
            if (j == 4 && hh == 2) named_arrive(N_DONE, 256);
            wgmma_rs_n32<1>(O[hh], A[hh][j], dlo(OFF_KV + KV + hh * 7 / 2 * 128 + j * 3584, 1792), p.db, j);
          }
        wg_commit();
        OBS(rel, 19);
        wg_wait<0>();
        OBS(rel, 21);
        const uint32_t ost = ust + (r8 >> 2) * 1792 + (((2 * r8) & 7) + ((mi & 1) ^ (r8 >> 2))) * 16;
#pragma unroll
        for (int n = 0; n < 14; n += 2) {
          uint32_t R[4];
#pragma unroll
          for (int j = 0; j < 4; j++) {
            const int m = n + (j >> 1), hb2 = m / 7 * 2, r = m % 7, h2 = (j & 1) * 2;
            if (r < 3) R[j] = pack2(O[hb2][4 * r + h2], O[hb2][4 * r + h2 + 1]);
            else if (r == 3) R[j] = pack2(t < 2 ? O[hb2][12 + h2] : O[hb2 + 1][h2], t < 2 ? O[hb2][13 + h2] : O[hb2 + 1][h2 + 1]);
            else R[j] = pack2(O[hb2 + 1][4 * (r - 3) + h2], O[hb2 + 1][4 * (r - 3) + h2 + 1]);
          }
          stsm4(ost + n * 128, R[0], R[1], R[2], R[3]);
        }
        OBS(rel, 29);
        smem_fence();
        if (PS_O) {
          __syncwarp();
          OBS(rel, 14);
          if (elect()) {
            wait_until(clock() + w4 * PS_O);
            store_paced(g_scr + (G_O + mt * 8 + w4 * 2) * GRP + dt * 1792, GRP, base + OFF_U + w4 * 3584, 1792, 2, 4 * PS_O);
            publish(C_O + mt);
          }
        } else {
          named_sync(1, 128);
          OBS(rel, 14);
          if (w4 == 0 && elect()) { tma_store(&m_b14, dt * 14, G_O + mt * 8, base + OFF_U); publish(C_O + mt); }
        }
        OBS(rel, 120);
        __syncwarp();
      }
      const int ro = (mt * 64 + w4 * 16 + g) * (D_ * 2) + dt * 224;
      uint32_t X[28], G[28];
      mbar_wait(bars + B_RES, 0);
#pragma unroll
      for (int h = 0; h < 2; h++) {
        const uint32_t a = base + OFF_KV + (w4 * 16 + h * 8 + g) * 224;
#pragma unroll
        for (int i = 0; i < 3; i++) { const uint4 v = lds128(a + i * 64 + t * 16); X[h * 14 + 4 * i] = v.x; X[h * 14 + 4 * i + 1] = v.y; X[h * 14 + 4 * i + 2] = v.z; X[h * 14 + 4 * i + 3] = v.w; }
        X[h * 14 + 12] = lds32(a + 192 + t * 8); X[h * 14 + 13] = lds32(a + 196 + t * 8);
      }
      unsigned char *outp = p.out + ro + t * 16, *outq = p.out + ro + 192 + t * 8;
      asm volatile("" : "+l"(outp), "+l"(outq));
      named_sync(8, 256);
      fresh(acc);
      OBS0(49, 25);
#pragma unroll
      for (int c = 49; c < 56; c++) stage<0>(acc, p.dx, p.db, c & 7, (c + 2) & 7, 0, ok, c == 49, false, nohook);
      named_sync(9, 256);
#pragma unroll
      for (int j = 0; j < 28; j += 4) { const uint4 v = lds128(gx + j * 512); G[j] = v.x; G[j + 1] = v.y; G[j + 2] = v.z; G[j + 3] = v.w; }
      wg_wait<0>();
      OBS(rel, 27);
#pragma unroll
      for (int i = 0; i < 4; i++)
#pragma unroll
        for (int h = 0; h < 2; h++) {
          uint32_t R[4];
#pragma unroll
          for (int j = 0; j < (i < 3 ? 4 : 2); j++) {
            const int n = 4 * i + j;
            R[j] = hadd2(X[h * 14 + n], hmul2(pack2(acc[4 * n + 2 * h], acc[4 * n + 2 * h + 1]), G[2 * n + h]));
          }
          if (i < 3) asm volatile("st.global.v4.u32 [%0], {%1,%2,%3,%4};" :: "l"(outp + h * 8 * D_ * 2 + i * 64), "r"(R[0]), "r"(R[1]), "r"(R[2]), "r"(R[3]) : "memory");
          else asm volatile("st.global.v2.u32 [%0], {%1,%2};" :: "l"(outq + h * 8 * D_ * 2), "r"(R[0]), "r"(R[1]) : "memory");
        }
      OBS(rel, 28);
#ifdef DBG_OBS
      named_sync(1, 128);
      { uint32_t v = lds32(base + OFF_OBS + tid * 4); if (tid == 126) v = t0; if (tid == 127) asm volatile("mov.u32 %0, %%smid;" : "=r"(v)); g_obs[b * 128 + tid] = v; }
#endif
    } else {
      if (g1 && w4 == 1) { mbar_wait(bars + B_TS, 0); spin_ge(C_H + 1, 128); if (lane == 0) mbar_arrive(bars + B_F0); __syncwarp(); }
      {
        float ka[56], va[56];
        const uint32_t kst = base + OFF_KV + (2 + 2 * w4 + (mi & 1)) * 1792 + (mi >> 1) * 128 + r8 * 16;
        auto put = [&](const float (&a)[56], uint32_t dst, int n) {
          stsm4(dst + n * 128, pack2(a[4 * n], a[4 * n + 1]), pack2(a[4 * n + 2], a[4 * n + 3]), pack2(a[4 * n + 4], a[4 * n + 5]), pack2(a[4 * n + 6], a[4 * n + 7])); };
        named_sync(3, 256);
        fresh(ka);
        OBS0(0, 8);
#pragma unroll
        for (int c = 0; c < 7; c++) stage<0>(ka, p.dx, p.db, c, c, 0, ok, c == 0, rel && c, nohook);
        fresh(va);
#pragma unroll
        for (int c = 7; c < 14; c++)
          stage<0>(va, p.dx, p.db, c & 7, c - 7, c >> 3, ok, c == 7, rel, [&](int k) {
            if (c > 7 && (c - 8) * 4 + k < 7) put(ka, kst, (c - 8) * 8 + k * 2);
            if (c == 9 && k == 3 && w4 == 3) named_arrive(11, 64);
            if (c == 13 && k == 3 - HK) named_arrive(4, 256); });
        wg_wait<0>();
        if (rel) mbar_arrive(bars + B_EMPTY + 5 * 8);
#pragma unroll
        for (int n = 0; n < 14; n += 2) put(va, kst + KV, n);
        if (w4 == 3) named_arrive(0, 64);
        smem_fence();
      }
      float acc[56];
#pragma unroll
      for (int i = 0; i < 2; i++) { hb[i] = hmul2(hb[i] * 0x10001u, 0x3f003f00u); asm volatile("" : "+r"(hb[i])); }
#pragma unroll
      for (int i = 0; i < 56; i++) { acc[i] = 0.f; asm volatile("" : "+f"(acc[i])); }
      named_sync(5, 256);
      OBS0(21, 10);
#pragma unroll 1
      for (int r = 0; ; r++) {
#pragma unroll
        for (int j = 0; j < 8; j++) {
          const bool site = j == SA % 8 || j == SB % 8, yield = (j == SA % 8 && r == SA / 8) || (j == SB % 8 && r == SB / 8);
          stage<1>(acc, p.dw, p.db, (j + 5) & 7, (j + 7) & 7, (r + (j > 2)) & 1, ok, false, rel && (j || r), [&](int k) {
            if (k == 3 - HK) { if (site) arrive_if(N_GO, yield); if (j == 3) arrive_if(8, r == 3); } });
          if (site && yield) named_sync(N_DONE, 256);
          if (j == 3 && r == 3) goto gemm2_done;
        }
      }
      gemm2_done:
      wg_wait<0>();
      OBS(rel, 24);
#pragma unroll
      for (int j = 0; j < 28; j += 4) {
        uint32_t R[4];
#pragma unroll
        for (int i = 0; i < 4; i++) {
          const uint32_t hh = hfma2(pack2(acc[2 * (j + i)], acc[2 * (j + i) + 1]), 0x3e803e80u, hb[i & 1]);
          const float a = bf_lo(hh), c = bf_hi(hh);
          R[i] = pack2(fmaf(a, tanh_fast(a), a), fmaf(c, tanh_fast(c), c));
        }
        sts128(gx + j * 512, R[0], R[1], R[2], R[3]);
      }
      OBS(rel, 26);
      named_arrive(9, 256);
    }
  }
}

typedef CUresult (*EncFn)(CUtensorMap*, CUtensorMapDataType, cuuint32_t, void*, const cuuint64_t*, const cuuint64_t*, const cuuint32_t*,
                          const cuuint32_t*, CUtensorMapInterleave, CUtensorMapSwizzle, CUtensorMapL2promotion, CUtensorMapFloatOOBfill);
void enc(EncFn f, CUtensorMap* m, const void* ptr, const cuuint64_t (&gd)[4], const cuuint64_t (&gs)[3], const cuuint32_t (&bx)[4], CUtensorMapSwizzle sw) {
  cuuint32_t es[4] = {1, 1, 1, 1};
  f(m, CU_TENSOR_MAP_DATA_TYPE_BFLOAT16, 4, (void*)ptr, gd, gs, bx, es, CU_TENSOR_MAP_INTERLEAVE_NONE, sw,
    CU_TENSOR_MAP_L2_PROMOTION_L2_128B, CU_TENSOR_MAP_FLOAT_OOB_FILL_NONE);
}
}

extern "C" void kernel_launch(void* const* d_in, const int* in_sizes, int n_in, void* d_out, int out_size) {
  (void)in_sizes; (void)n_in; (void)out_size;
  void* fp = nullptr;
  cudaDriverEntryPointQueryResult qr;
  cudaGetDriverEntryPoint("cuTensorMapEncodeTiled", &fp, cudaEnableDefault, &qr);
  EncFn f = (EncFn)fp;
  CUtensorMap m_w1, m_w2, m_b14, m_a8, m_x;
  void* scr = nullptr;
  cudaGetSymbolAddress(&scr, g_scr);
  enc(f, &m_w1, d_in[4], {F_, 8, 2, S_ / 16}, {F_ * 4, F_ * 2, F_ * 32}, {64, 8, 2, 4}, CU_TENSOR_MAP_SWIZZLE_128B);
  enc(f, &m_w2, d_in[6], {S_, 1, 1, F_}, {S_ * 2, S_ * 2, S_ * 2}, {64, 1, 1, 64}, CU_TENSOR_MAP_SWIZZLE_128B);
  enc(f, &m_b14, scr, {64, 56, 1, G_END}, {128, GRP, GRP}, {64, 14, 1, 8}, CU_TENSOR_MAP_SWIZZLE_NONE);
  enc(f, &m_a8, scr, {64, 56, 1, G_END}, {128, GRP, GRP}, {64, 8, 1, 8}, CU_TENSOR_MAP_SWIZZLE_NONE);
  enc(f, &m_x, d_in[0], {D_, 1, 1, S_}, {D_ * 2, D_ * 2, D_ * 2}, {112, 1, 1, 64}, CU_TENSOR_MAP_SWIZZLE_NONE);
  Params p;
  p.x = (const unsigned char*)d_in[0]; p.wqkv = (const unsigned char*)d_in[1]; p.wo = (const unsigned char*)d_in[2];
  p.w1 = (const unsigned char*)d_in[4]; p.b1 = (const unsigned short*)d_in[5];
  p.w2 = (const unsigned char*)d_in[6]; p.b2 = (const unsigned short*)d_in[7];
  p.out = (unsigned char*)d_out;
  p.dw = 0x40000040u; p.dx = 64; p.db = 8; p.dk = 112;
#ifdef TUNE
  for (int i = 0; i < NTUNE; i++) p.tune[i] = tune_vals[i];
#endif
  cudaFuncSetAttribute(fused_kernel, cudaFuncAttributeMaxDynamicSharedMemorySize, SMEM_BYTES);
  fused_kernel<<<128, NTHREADS, SMEM_BYTES, cudaStreamPerThread>>>(m_w1, m_w2, m_b14, m_a8, m_x, p);
}
```

```cpp
#include <cuda_runtime.h>
#include <cuda.h>
#include <cuda_bf16.h>
#include <stdint.h>

template<int TA, int TB> __device__ __forceinline__ void wgmma_n112(float (&d)[56], uint32_t al, uint32_t ah, uint32_t bl, uint32_t bh, int sc) {
  asm volatile("{\n.reg .pred p;\n.reg .b64 a, b;\nsetp.ne.b32 p, %60, 0;\nmov.b64 a, {%56, %57};\nmov.b64 b, {%58, %59};\n"
    "wgmma.mma_async.sync.aligned.m64n112k16.f32.bf16.bf16 {%0, %1, %2, %3, %4, %5, %6, %7, %8, %9, %10, %11, %12, %13, %14, %15, %16, %17, %18, %19, %20, %21, %22, %23, %24, %25, %26, %27, %28, %29, %30, %31, %32, %33, %34, %35, %36, %37, %38, %39, %40, %41, %42, %43, %44, %45, %46, %47, %48, %49, %50, %51, %52, %53, %54, %55}, a, b, p, 1, 1, %61, %62;\n}\n"
    : "+f"(d[0]), "+f"(d[1]), "+f"(d[2]), "+f"(d[3]), "+f"(d[4]), "+f"(d[5]), "+f"(d[6]), "+f"(d[7]), "+f"(d[8]), "+f"(d[9]), "+f"(d[10]), "+f"(d[11]), "+f"(d[12]), "+f"(d[13]), "+f"(d[14]), "+f"(d[15]), "+f"(d[16]), "+f"(d[17]), "+f"(d[18]), "+f"(d[19]), "+f"(d[20]), "+f"(d[21]), "+f"(d[22]), "+f"(d[23]), "+f"(d[24]), "+f"(d[25]), "+f"(d[26]), "+f"(d[27]), "+f"(d[28]), "+f"(d[29]), "+f"(d[30]), "+f"(d[31]), "+f"(d[32]), "+f"(d[33]), "+f"(d[34]), "+f"(d[35]), "+f"(d[36]), "+f"(d[37]), "+f"(d[38]), "+f"(d[39]), "+f"(d[40]), "+f"(d[41]), "+f"(d[42]), "+f"(d[43]), "+f"(d[44]), "+f"(d[45]), "+f"(d[46]), "+f"(d[47]), "+f"(d[48]), "+f"(d[49]), "+f"(d[50]), "+f"(d[51]), "+f"(d[52]), "+f"(d[53]), "+f"(d[54]), "+f"(d[55])
    : "r"(al), "r"(ah), "r"(bl), "r"(bh), "r"(sc), "n"(TA), "n"(TB));
}

template<int TB> __device__ __forceinline__ void wgmma_rs_n80(float (&d)[40], const uint32_t (&a)[4], uint32_t bl, uint32_t bh, int sc) {
  asm volatile("{\n.reg .pred p;\n.reg .b64 b;\nsetp.ne.b32 p, %46, 0;\nmov.b64 b, {%44, %45};\n"
    "wgmma.mma_async.sync.aligned.m64n80k16.f32.bf16.bf16 {%0, %1, %2, %3, %4, %5, %6, %7, %8, %9, %10, %11, %12, %13, %14, %15, %16, %17, %18, %19, %20, %21, %22, %23, %24, %25, %26, %27, %28, %29, %30, %31, %32, %33, %34, %35, %36, %37, %38, %39}, {%40, %41, %42, %43}, b, p, 1, 1, %47;\n}\n"
    : "+f"(d[0]), "+f"(d[1]), "+f"(d[2]), "+f"(d[3]), "+f"(d[4]), "+f"(d[5]), "+f"(d[6]), "+f"(d[7]), "+f"(d[8]), "+f"(d[9]), "+f"(d[10]), "+f"(d[11]), "+f"(d[12]), "+f"(d[13]), "+f"(d[14]), "+f"(d[15]), "+f"(d[16]), "+f"(d[17]), "+f"(d[18]), "+f"(d[19]), "+f"(d[20]), "+f"(d[21]), "+f"(d[22]), "+f"(d[23]), "+f"(d[24]), "+f"(d[25]), "+f"(d[26]), "+f"(d[27]), "+f"(d[28]), "+f"(d[29]), "+f"(d[30]), "+f"(d[31]), "+f"(d[32]), "+f"(d[33]), "+f"(d[34]), "+f"(d[35]), "+f"(d[36]), "+f"(d[37]), "+f"(d[38]), "+f"(d[39])
    : "r"(a[0]), "r"(a[1]), "r"(a[2]), "r"(a[3]), "r"(bl), "r"(bh), "r"(sc), "n"(TB));
}

template<int TB> __device__ __forceinline__ void wgmma_rs_n32(float (&d)[16], const uint32_t (&a)[4], uint32_t bl, uint32_t bh, int sc) {
  asm volatile("{\n.reg .pred p;\n.reg .b64 b;\nsetp.ne.b32 p, %22, 0;\nmov.b64 b, {%20, %21};\n"
    "wgmma.mma_async.sync.aligned.m64n32k16.f32.bf16.bf16 {%0, %1, %2, %3, %4, %5, %6, %7, %8, %9, %10, %11, %12, %13, %14, %15}, {%16, %17, %18, %19}, b, p, 1, 1, %23;\n}\n"
    : "+f"(d[0]), "+f"(d[1]), "+f"(d[2]), "+f"(d[3]), "+f"(d[4]), "+f"(d[5]), "+f"(d[6]), "+f"(d[7]), "+f"(d[8]), "+f"(d[9]), "+f"(d[10]), "+f"(d[11]), "+f"(d[12]), "+f"(d[13]), "+f"(d[14]), "+f"(d[15])
    : "r"(a[0]), "r"(a[1]), "r"(a[2]), "r"(a[3]), "r"(bl), "r"(bh), "r"(sc), "n"(TB));
}

namespace {
constexpr int S_ = 2048, D_ = 448, F_ = 1792;
constexpr int SLOT = 22528, BT = 14336;
constexpr int OFF_KV = 8 * SLOT;
constexpr int KV = 10 * 1792;
constexpr int OFF_PART = OFF_KV + 2 * BT;
constexpr int OFF_U = OFF_KV + 10 * 3584;
constexpr int OFF_BAR = OFF_U + BT;
constexpr uint32_t base = 1024, bars = base + OFF_BAR;
constexpr int OFF_OBS = OFF_BAR + 256;
constexpr int SMEM_BYTES = OFF_OBS + 768;
#ifdef TUNE
#define TV(i) p.tune[i]
const char* tune_names[] = {"DLY_B", "DLY_W", "TPW", "DLY_R", "PF0", "PACE1", "PACE2", "TRIG0", "TRIG1", "SY_H", "MODE_B", "PFN", "STG_S", "PS_H", "PS_N", "PF1", "PACE0", "SY_U", "SY_B"};
int tune_vals[19] = {900, 4300, 210, 1600, 2800, 420, 400, 3300, 900, 0, 1000, 0, 2, 0, 300, 0, 350, 1400, 0};
constexpr int NTUNE = 19;
#define DLY_B TV(0)
#define DLY_W TV(1)
#define TPW TV(2)
#define DLY_R TV(3)
#define PF0 TV(4)
#define PACE1 TV(5)
#define PACE2 TV(6)
#define TRIG0 TV(7)
#define TRIG1 TV(8)
#define SY_H TV(9)
#define SY_U TV(17)
#define SY_B TV(18)
#define MODE_B TV(10)
#define PFN TV(11)
#define PF1 TV(15)
#define PACE0 TV(16)
#define STG_S TV(12)
#define PS_H TV(13)
#define PS_N TV(14)
#else
#ifndef DLY_B
#define DLY_B 900
#endif
#ifndef DLY_W
#define DLY_W 4300
#endif
#ifndef TPW
#define TPW 210
#endif
#ifndef DLY_R
#define DLY_R 1600
#endif
#ifndef PF0
#define PF0 2800
#endif
#ifndef PACE1
#define PACE1 420
#endif
#ifndef PACE2
#define PACE2 400
#endif
#ifndef TRIG0
#define TRIG0 3300
#endif
#ifndef TRIG1
#define TRIG1 900
#endif
#ifndef SY_H
#define SY_H 0
#endif
#ifndef SY_U
#define SY_U 1400
#endif
#ifndef SY_B
#define SY_B 0
#endif
#ifndef PFN
#define PFN 0
#endif
#ifndef PF1
#define PF1 0
#endif
#ifndef PACE0
#define PACE0 350
#endif
#ifndef MODE_B
#define MODE_B 1000
#endif
#ifndef STG_S
#define STG_S 2
#endif
#ifndef PS_H
#define PS_H 0
#endif
#ifndef PS_N
#define PS_N 300
#endif
#endif
#ifndef SA
#define SA 0
#endif
#ifndef SB
#define SB 7
#endif
#ifndef PVS
#define PVS 0
#endif
#ifndef UH
#define UH 1
#endif
#ifndef EARLY
#define EARLY 1
#endif
#ifndef PFS
#define PFS 0
#endif
#ifndef PS_O
#define PS_O 130
#endif
#ifndef HK
#define HK 1
#endif
#ifndef HE
#define HE 1
#endif
#ifdef DBG_OBS
__device__ int g_obs[128 * 128];
#define OBS(c, i) asm volatile("{\n.reg .pred p;\n.reg .u32 k;\nsetp.ne.u32 p, %1, 0;\nmov.u32 k, %%clock;\nsub.u32 k, k, %2;\n@p st.shared.u32 [%0], k;\n}" :: "r"(base + OFF_OBS + (i) * 4), "r"((uint32_t)(c)), "r"(t0) : "memory")
#else
#define OBS(c, i) do {} while (0)
#endif
constexpr int NTHREADS = 384;
constexpr float LOG2E = 1.4426950408889634f;

constexpr int GRP = 7168;
constexpr int G_H = 0, G_XN = 256, G_O = 512, G_W = 768, G_U = G_W + 168, G_WO = G_U + 224, G_HALO = G_WO + 56, G_END = G_HALO + 128;
constexpr int SCR_BYTES = G_END * GRP;
__device__ __align__(1024) unsigned char g_scr[SCR_BYTES];
constexpr int C_TICKET = 0, C_W = 1, C_H = 2, C_U = 4, C_W2 = 5, C_O = 8, C_HALO = 40, C_END = 168;
__device__ __align__(128) unsigned g_cnt[C_END * 32];

__device__ __forceinline__ uint32_t smem_u32(const void* p) { return (uint32_t)__cvta_generic_to_shared(p); }
__device__ __forceinline__ void mbar_init(uint32_t bar, uint32_t cnt) { asm volatile("mbarrier.init.shared::cta.b64 [%0], %1;" :: "r"(bar), "r"(cnt)); }
__device__ __forceinline__ void mbar_expect_tx(uint32_t bar, uint32_t bytes) { asm volatile("mbarrier.arrive.expect_tx.shared::cta.b64 _, [%0], %1;" :: "r"(bar), "r"(bytes) : "memory"); }
__device__ __forceinline__ void mbar_arrive(uint32_t bar) { asm volatile("mbarrier.arrive.shared::cta.b64 _, [%0];" :: "r"(bar) : "memory"); }
__device__ __forceinline__ void mbar_wait(uint32_t bar, uint32_t parity) {
  asm volatile("{\n.reg .pred p;\n.reg .u32 n;\nmov.u32 n, 0;\nLAB_WAIT:\n"
               "mbarrier.try_wait.parity.shared::cta.b64 p, [%0], %1;\n@p bra DONE;\n"
               "add.u32 n, n, 1;\nsetp.lt.u32 p, n, 4000000;\n@p bra LAB_WAIT;\ntrap;\nDONE:\n}" :: "r"(bar), "r"(parity) : "memory");
}
__device__ __forceinline__ uint32_t mbar_try(uint32_t bar, uint32_t parity) {
  uint32_t ok;
  asm volatile("{\n.reg .pred p;\nmbarrier.test_wait.parity.shared::cta.b64 p, [%1], %2;\nselp.u32 %0, 1, 0, p;\n}" : "=r"(ok) : "r"(bar), "r"(parity) : "memory");
  return ok;
}
__device__ __forceinline__ void tma4d(uint32_t dst, const CUtensorMap* m, int c0, int c1, int c3, uint32_t bar) {
  asm volatile("cp.async.bulk.tensor.4d.shared::cluster.global.mbarrier::complete_tx::bytes [%0], [%1, {%3, %4, %6, %5}], [%2];"
               :: "r"(dst), "l"(m), "r"(bar), "r"(c0), "r"(c1), "r"(c3), "r"(0) : "memory");
}
__device__ __forceinline__ void tma_store(const CUtensorMap* m, int c1, int c3, uint32_t src) {
  asm volatile("cp.async.bulk.tensor.4d.global.shared::cta.bulk_group [%0, {%4, %2, %4, %3}], [%1];" :: "l"(m), "r"(src), "r"(c1), "r"(c3), "r"(0) : "memory");
}
__device__ __forceinline__ void bulk_g2s(uint32_t dst, const void* src, uint32_t bytes, uint32_t bar) {
  asm volatile("cp.async.bulk.shared::cluster.global.mbarrier::complete_tx::bytes [%0], [%1], %2, [%3];" :: "r"(dst), "l"(src), "r"(bytes), "r"(bar) : "memory");
}
__device__ __forceinline__ void bulk_s2g(void* dst, uint32_t src, uint32_t bytes) {
  asm volatile("cp.async.bulk.global.shared::cta.bulk_group [%0], [%1], %2;" :: "l"(dst), "r"(src), "r"(bytes) : "memory");
}
__device__ __forceinline__ void wg_fence() { asm volatile("wgmma.fence.sync.aligned;" ::: "memory"); }
__device__ __forceinline__ void wg_commit() { asm volatile("wgmma.commit_group.sync.aligned;" ::: "memory"); }
template <int N> __device__ __forceinline__ void wg_wait() { asm volatile("wgmma.wait_group.sync.aligned %0;" :: "n"(N) : "memory"); }
__device__ __forceinline__ void proxy_fence() { asm volatile("fence.proxy.async.global;" ::: "memory"); }
#ifndef LIGHT
#define LIGHT 1
#endif
__device__ __forceinline__ void smem_fence() {
  if (LIGHT == 2) return;
  if (LIGHT) asm volatile("mbarrier.init.shared::cta.b64 [%0], 1;" :: "r"(base + OFF_BAR + 248) : "memory");
  else asm volatile("fence.proxy.async.shared::cta;" ::: "memory");
}
__device__ __forceinline__ uint32_t gtime() { uint32_t v; asm volatile("mov.u32 %0, %%globaltimer_lo;" : "=r"(v)); return v; }
__device__ __forceinline__ void publish(int i, bool timed = false) {
  asm volatile("cp.async.bulk.commit_group;" ::: "memory");
  if (timed) asm volatile("red.relaxed.gpu.global.max.u32 [%0], %1;" :: "l"(&g_cnt[i * 32 + 1]), "r"(gtime()) : "memory");
  asm volatile("cp.async.bulk.wait_group 0;" ::: "memory");
  asm volatile("red.relaxed.gpu.global.inc.u32 [%0], 0xffffffff;" :: "l"(&g_cnt[i * 32]) : "memory");
}
__device__ __forceinline__ void spin_ge(int i, unsigned target) {
  asm volatile("{\n.reg .pred p;\n.reg .u32 n, v;\nmov.u32 n, 0;\nLAB_SPIN:\n"
               "ld.relaxed.gpu.global.u32 v, [%0];\nsetp.ge.u32 p, v, %1;\n@p bra DONE;\n"
               "add.u32 n, n, 1;\nsetp.lt.u32 p, n, 4000000;\n@p bra LAB_SPIN;\ntrap;\nDONE:\n}" :: "l"(&g_cnt[i * 32]), "r"(target) : "memory");
}
__device__ __forceinline__ void spin_timed(int i, unsigned target, int delay) {
  uint32_t last;
  asm volatile("{\n.reg .pred p;\n.reg .u32 n, v;\nmov.u32 n, 0;\nLAB_SPIN:\n"
               "ld.relaxed.gpu.global.v2.u32 {v, %0}, [%1];\nsetp.ge.u32 p, v, %2;\n@p bra DONE;\n"
               "add.u32 n, n, 1;\nsetp.lt.u32 p, n, 4000000;\n@p bra LAB_SPIN;\ntrap;\nDONE:\n}" : "=r"(last) : "l"(&g_cnt[i * 32]), "r"(target) : "memory");
  while (gtime() - last < (uint32_t)delay);
}
__device__ __forceinline__ unsigned ld_relaxed(int i) { unsigned v; asm volatile("ld.relaxed.gpu.global.u32 %0, [%1];" : "=r"(v) : "l"(&g_cnt[i * 32]) : "memory"); return v; }
__device__ __forceinline__ bool elect() {
  uint32_t r; asm volatile("{\n.reg .pred p;\nelect.sync _|p, 0xffffffff;\nselp.u32 %0, 1, 0, p;\n}" : "=r"(r)); return r != 0;
}
__device__ __forceinline__ void wait_until(uint32_t tn) { while ((int)(clock() - tn) < 0) __nanosleep(20); }
__device__ __forceinline__ void store_paced(unsigned char* dst, int dstep, uint32_t src, int sstep, int n, int gap, int bytes = 1792) {
  uint32_t tn = clock();
#pragma unroll 1
  for (int i = 0; i < n; i++) { wait_until(tn); bulk_s2g(dst, src, bytes); dst += dstep; src += sstep; tn += gap; }
}
__device__ __forceinline__ uint4 lds128(uint32_t a) { uint4 v; asm volatile("ld.shared.v4.u32 {%0,%1,%2,%3}, [%4];" : "=r"(v.x), "=r"(v.y), "=r"(v.z), "=r"(v.w) : "r"(a) : "memory"); return v; }
__device__ __forceinline__ uint32_t lds32(uint32_t a) { uint32_t v; asm volatile("ld.shared.u32 %0, [%1];" : "=r"(v) : "r"(a) : "memory"); return v; }
__device__ __forceinline__ void sts128(uint32_t p, uint32_t a, uint32_t b, uint32_t c, uint32_t d) { asm volatile("st.shared.v4.u32 [%0], {%1,%2,%3,%4};" :: "r"(p), "r"(a), "r"(b), "r"(c), "r"(d) : "memory"); }
__device__ __forceinline__ void sts64(uint32_t p, float a, float b) { asm volatile("st.shared.v2.f32 [%0], {%1,%2};" :: "r"(p), "f"(a), "f"(b) : "memory"); }
__device__ __forceinline__ void named_sync(int id, int n) { asm volatile("bar.sync %0, %1;" :: "r"(id), "r"(n) : "memory"); }
__device__ __forceinline__ void named_arrive(int id, int n) { asm volatile("bar.arrive %0, %1;" :: "r"(id), "r"(n) : "memory"); }
__device__ __forceinline__ constexpr uint32_t dlo(uint32_t off, uint32_t lbo) { return ((base + off) >> 4) | (lbo >> 4 << 16); }
__device__ __forceinline__ uint32_t pack2(float lo, float hi) { uint32_t r; asm("cvt.rn.bf16x2.f32 %0, %1, %2;" : "=r"(r) : "f"(hi), "f"(lo)); return r; }
__device__ __forceinline__ float bf_lo(uint32_t v) { return __uint_as_float(v << 16); }
__device__ __forceinline__ float bf_hi(uint32_t v) { return __uint_as_float(v & 0xffff0000u); }
__device__ __forceinline__ float rbf(float x) { return bf_lo(pack2(x, 0.f)); }
__device__ __forceinline__ uint32_t hsub2(uint32_t a, uint32_t b) { uint32_t r; asm("sub.rn.bf16x2 %0, %1, %2;" : "=r"(r) : "r"(a), "r"(b)); return r; }
__device__ __forceinline__ uint32_t hadd2(uint32_t a, uint32_t b) { uint32_t r; asm("add.rn.bf16x2 %0, %1, %2;" : "=r"(r) : "r"(a), "r"(b)); return r; }
__device__ __forceinline__ uint32_t hmax2(uint32_t a, uint32_t b) { uint32_t r; asm("max.bf16x2 %0, %1, %2;" : "=r"(r) : "r"(a), "r"(b)); return r; }
__device__ __forceinline__ uint32_t hmul2(uint32_t a, uint32_t b) { uint32_t r; asm("mul.rn.bf16x2 %0, %1, %2;" : "=r"(r) : "r"(a), "r"(b)); return r; }
__device__ __forceinline__ uint32_t hfma2(uint32_t a, uint32_t b, uint32_t c) { uint32_t r; asm("fma.rn.bf16x2 %0, %1, %2, %3;" : "=r"(r) : "r"(a), "r"(b), "r"(c)); return r; }
__device__ __forceinline__ float tanh_fast(float x) { float r; asm("tanh.approx.f32 %0, %1;" : "=f"(r) : "f"(x)); return r; }
__device__ __forceinline__ float rcp_fast(float x) { float r; asm("rcp.approx.ftz.f32 %0, %1;" : "=f"(r) : "f"(x)); return r; }
__device__ __forceinline__ float ex2_fast(float x) { float r; asm("ex2.approx.ftz.f32 %0, %1;" : "=f"(r) : "f"(x)); return r; }
__device__ __forceinline__ void stsm4(uint32_t addr, uint32_t a, uint32_t b, uint32_t c, uint32_t d) {
  asm volatile("stmatrix.sync.aligned.m8n8.x4.shared.b16 [%0], {%1,%2,%3,%4};" :: "r"(addr), "r"(a), "r"(b), "r"(c), "r"(d) : "memory");
}
__device__ __forceinline__ void stsm2(uint32_t addr, uint32_t a, uint32_t b) {
  asm volatile("stmatrix.sync.aligned.m8n8.x2.shared.b16 [%0], {%1,%2};" :: "r"(addr), "r"(a), "r"(b) : "memory");
}
__device__ __forceinline__ void load_row(uint32_t (&r)[14], const unsigned char* p, int t) {
#pragma unroll
  for (int i = 0; i < 3; i++)
    asm volatile("ld.global.nc.L1::no_allocate.v4.u32 {%0,%1,%2,%3}, [%4];" : "=r"(r[4 * i]), "=r"(r[4 * i + 1]), "=r"(r[4 * i + 2]), "=r"(r[4 * i + 3]) : "l"(p + i * 64 + t * 16));
  asm volatile("ld.global.nc.L1::no_allocate.v2.u32 {%0,%1}, [%2];" : "=r"(r[12]), "=r"(r[13]) : "l"(p + 192 + t * 8));
}

template <int N> __device__ __forceinline__ void fresh(float (&a)[N]) {
#pragma unroll
  for (int i = 0; i < N; i++) asm volatile("" : "=f"(a[i]));
}
__device__ __forceinline__ void pin(uint32_t (&a)[4]) { asm volatile("" : "+r"(a[0]), "+r"(a[1]), "+r"(a[2]), "+r"(a[3])); }
constexpr int B_EMPTY = 64, B_F0 = 128, B_F1 = 136, B_F2 = 144, B_F3 = 152, B_HALO = 160, B_RT = 176, B_RES = 184, B_TS = 192, B_F1B = 200;
constexpr int N_GO = 6, N_DONE = 7;
__device__ __forceinline__ void arrive_if(int id, bool on) {
  asm volatile("{\n.reg .pred p;\nsetp.ne.u32 p, %1, 0;\n@p bar.arrive %0, 256;\n}" :: "r"(id), "r"((uint32_t)on) : "memory");
}
template <int TA, class Hook>
__device__ __forceinline__ void stage(float (&acc)[56], uint32_t ah, uint32_t bh, int sb, int sa, uint32_t par, uint32_t& ok, bool first, bool rel, Hook hook) {
  if (!ok) mbar_wait(bars + sb * 8, par);
  wg_fence();
#pragma unroll
  for (int k = 0; k < 4; k++) {
    wgmma_n112<TA, 1>(acc, dlo(sa * SLOT + k * (TA ? 2048 : 256), TA ? 8192 : 128), ah, dlo(sb * SLOT + 8192 + k * 3584, 1792), bh, k || !first);
    if (k == 1) ok = mbar_try(bars + ((sb + 1) & 7) * 8, sb == 7 ? par ^ 1 : par);
    hook(k);
  }
  wg_commit();
  wg_wait<1>();
  if (rel) mbar_arrive(bars + B_EMPTY + ((sb + 7) & 7) * 8);
}

template <uint32_t BYTES>
__device__ __forceinline__ void produce(int c, int cend, int rot, const CUtensorMap* mp, int c0, int c1, int s1, int c3, int s3, int tr = 0) {
#pragma unroll 1
  for (; c < cend; c++) {
    const uint32_t fb = base + OFF_BAR + (c & 7) * 8, dst = base + (BYTES ? 8192 : 0) + ((c + rot) & 7) * SLOT;
    mbar_wait(fb + B_EMPTY, ((c >> 3) & 1) ^ 1);
#ifdef DBG_TRACE
    if (BYTES) { const uint32_t t0 = 0; OBS(1, 32 + tr + c); }
#endif
    if (BYTES) mbar_expect_tx(fb, BYTES);
    tma4d(dst, mp, c0, c1, c3, fb);
    c1 += s1; c3 += s3;
  }
}

struct Params {
  const unsigned char *x, *wqkv, *wo, *w1, *w2;
  const unsigned short *b1, *b2;
  unsigned char* out;
  uint32_t dw, dx, db, dk;
#ifdef TUNE
  int tune[NTUNE];
#endif
};

__global__ void __launch_bounds__(NTHREADS, 1)
fused_kernel(const __grid_constant__ CUtensorMap m_w1, const __grid_constant__ CUtensorMap m_w2, const __grid_constant__ CUtensorMap m_b14,
             const __grid_constant__ CUtensorMap m_a8, const __grid_constant__ CUtensorMap m_x, const __grid_constant__ CUtensorMap m_b7, const Params p) {
  extern __shared__ __align__(1024) unsigned char smem_raw[];
  const uint32_t t0 = clock();
  const int tid = threadIdx.x, lane = tid & 31, b = blockIdx.x;
  const int g = lane >> 2, t = lane & 3, r8 = lane & 7, mi = lane >> 3;
  const int tg = (tid & 128) + b;
  const unsigned char* xrow = p.x + ((tg >> 1) * 16 + (tg & 1) + 2 * g) * (D_ * 2) + ((tid >> 5) & 3) * 224;
  uint32_t H[14];
  if (tid < 128) load_row(H, xrow, t);
  const int warp = __shfl_sync(0xffffffffu, tid >> 5, 0);
  const int dt = b & 3, mt = b >> 2;
  const bool g1 = b < 112;
  const int ft = mt, d1 = dt;
  if (warp >= 8) {
    if (warp == 8) {
      if (elect()) {
        if (smem_u32(smem_raw) != base) asm volatile("trap;");
#pragma unroll
        for (int i = 0; i < 26; i++) mbar_init(bars + i * 8, i * 8 == B_F1 && !g1 ? 3 : 1);
        asm volatile("fence.mbarrier_init.release.cluster;" ::: "memory");
      }
      __syncwarp();
      named_arrive(12, 160); named_arrive(13, 160);
    }
    named_sync(15, 128);
    asm volatile("setmaxnreg.dec.sync.aligned.u32 40;");
    if (warp == 8) {
      unsigned tk = 0;
      if (elect()) {
        asm volatile("prefetch.tensormap [%0];" :: "l"(&m_w1) : "memory");
        asm volatile("prefetch.tensormap [%0];" :: "l"(&m_a8) : "memory");
        asm volatile("prefetch.tensormap [%0];" :: "l"(&m_b7) : "memory");
        if (g1) {
#pragma unroll 1
          for (int c = 0; c < 8; c++) { wait_until(t0 + DLY_W + c * TPW); tma4d(base + c * SLOT, &m_w1, ft * 64, 0, c * 4, bars + c * 8); }
          produce<0>(8, 32, 0, &m_w1, ft * 64, 0, 0, 32, 4);
        } else {
          const int bytes = (dt < 3 ? 32 : 16) * 2688;
          wait_until(t0 + DLY_R);
          mbar_expect_tx(bars + B_RT, bytes);
          bulk_g2s(base, p.wqkv + ((mt & 3) * 112 + dt * 32) * 2688, bytes, bars + B_RT);
        }
        mbar_wait(bars + B_F1, 0);
        produce<0>(0, 7, 0, &m_a8, 0, 0, 8, G_XN + mt * 8, 0);
        mbar_wait(bars + B_EMPTY + 5 * 8, 0);
        produce<0>(21, 49, 2, &m_w2, mt * 64, 0, 0, 0, 64);
        mbar_wait(bars + B_F3, 0);
        OBS(1, 22);
        produce<0>(49, 56, 2, &m_a8, 0, 0, 8, G_O + mt * 8, 0);
        tk = atomicInc(&g_cnt[C_TICKET * 32], 0xffffffffu);
      }
      if (__any_sync(0xffffffffu, tk == 127)) {
#pragma unroll 1
        for (int i = lane; i < C_END; i += 32) *(uint2*)&g_cnt[i * 32] = make_uint2(0, 0);
      }
    } else if (warp == 9) {
      if (elect()) {
        asm volatile("prefetch.tensormap [%0];" :: "l"(&m_b14) : "memory");
        asm volatile("prefetch.tensormap [%0];" :: "l"(&m_w2) : "memory");
        asm volatile("prefetch.tensormap [%0];" :: "l"(&m_x) : "memory");
        if (g1) {
          spin_timed(C_H, 128, SY_H);
          OBS(1, 16);
          produce<SLOT>(0, STG_S, 0, &m_b14, 0, d1 * 14, 0, G_H, 8);
          mbar_arrive(bars + B_TS);
          produce<SLOT>(STG_S, 16, 0, &m_b14, 0, d1 * 14, 0, G_H + STG_S * 8, 8);
          mbar_wait(bars + B_F0, 0);
          OBS(1, 17);
          produce<SLOT>(16, 32, 0, &m_b14, 0, d1 * 14, 0, G_H + 128, 8);
        }
        mbar_wait(bars + B_F1, 0);
        OBS(1, 18);
        produce<SLOT>(0, 7, 0, &m_b14, 0, dt * 14, 0, G_W, 8, 32);
        mbar_wait(bars + B_F1B, 0);
        produce<BT>(7, 21, 0, &m_b14, 0, dt * 14, 0, G_W + 56, 8, 32);
        mbar_wait(bars + B_F2, 0);
        OBS(1, 20);
        produce<SLOT>(21, 56, 0, &m_b14, 0, dt * 14, 0, G_U, 8, 32);
      }
    } else if (warp == 10) {
      uint32_t tn = t0 + PF0;
      const unsigned char* src = p.w1 + PFS * 458752 + b * 3584 + lane * 128;
#pragma unroll 1
      for (int i = PFS; i < 32; i++) {
        wait_until(tn);
        if (i == 16) src = p.w2 + b * 3584 + lane * 128;
        if (lane < 28) asm volatile("prefetch.global.L2 [%0];" :: "l"(src) : "memory");
        __syncwarp();
        src += 458752;
        tn += i < PFN ? PACE0 : (i < 16 ? PACE1 : PACE2);
        if (i + 1 == PFN) tn = t0 + PF1;
      }
      spin_timed(C_U, 128, SY_U);
      if (lane == 0) mbar_arrive(bars + B_F2);
      spin_ge(C_O + mt, PS_O ? 16 : 4);
      if (lane == 0) mbar_arrive(bars + B_F3);
    } else {
      unsigned char* dst = g_scr + (G_H + b) * GRP;
      asm volatile("" : "+l"(dst));
      named_sync(14, 160);
      smem_fence();
      if (elect()) bulk_s2g(dst + G_XN * GRP, base + OFF_KV, GRP);
      named_sync(10, 160);
      smem_fence();
      if (elect()) { bulk_s2g(dst, base + OFF_KV + GRP, GRP); publish(C_H, SY_H); OBS(1, 3); }
      named_sync(9, 160);
      smem_fence();
      if (elect()) {
        if (g1) mbar_wait(bars + B_TS, 0);
        store_paced(dst + 128 * GRP, 1792, base + OFF_KV + 3 * GRP, 1792, 4, g1 ? PS_H : 0);
        publish(C_H + 1);
        OBS(1, 4);
        store_paced(dst + (G_XN + 128) * GRP, 1792, base + OFF_KV + 2 * GRP, 1792, 4, g1 ? PS_N : 0);
        publish(C_W);
      }
      __syncwarp();
      spin_ge(C_W, 144);
      if (lane == 0) mbar_arrive(bars + B_F1);
      spin_ge(C_W2, 16);
      if (lane == 0) mbar_arrive(bars + B_F1B);
      if (mt == 0) {
#pragma unroll
        for (int i = 0; i < 14; i++) sts128(base + OFF_KV + (i / 7) * KV + (i % 7) * 512 + lane * 16, 0, 0, 0, 0);
        smem_fence();
        __syncwarp();
        if (lane < 2) mbar_arrive(bars + B_HALO + lane * 8);
      }
      const unsigned have = EARLY && mt > 0 ? ld_relaxed(C_HALO + b - 4) : 0;
      if (UH && g1) {
        named_sync(14, 160);
        smem_fence();
        if (elect()) tma_store(&m_b7, d1 * 14, G_U + ft * 8, base + OFF_U);
        named_sync(10, 160);
        smem_fence();
        if (elect()) { tma_store(&m_b7, d1 * 14 + 7, G_U + ft * 8, base + OFF_U + GRP); publish(C_U, SY_U); OBS(1, 7); }
        __syncwarp();
      }
#pragma unroll 1
      for (int i = 0; i < 2; i++) {
        unsigned char* hg = g_scr + (G_HALO + b) * GRP + i * 3584;
        named_sync(i ? 0 : 11, 64);
        smem_fence();
        if (mt < 31 && elect()) { bulk_s2g(hg, base + OFF_KV + i * KV + 8 * 1792, 3584); publish(C_HALO + b); }
        OBS(lane == 0, i ? 15 : 23);
        if (mt > 0) {
          if (have <= i) spin_ge(C_HALO + b - 4, i + 1);
          if (elect()) { mbar_expect_tx(bars + B_HALO + i * 8, 3584); bulk_g2s(base + OFF_KV + i * KV, hg - 4 * GRP, 3584, bars + B_HALO + i * 8); }
        }
        __syncwarp();
      }
      named_sync(11, 64);
      if (elect()) { mbar_expect_tx(bars + B_RES, BT); tma4d(base + OFF_KV, &m_x, dt * 112, 0, mt * 64, bars + B_RES); }
    }
  } else {
    const int wg = warp >> 2, w4 = warp & 3;
    const bool rel = (tid & 127) == 0;
    if (wg) {
      wait_until(t0 + DLY_B);
      if (t < 2 && w4 * 2 + t < 7) asm volatile("prefetch.global.L2 [%0];" :: "l"(xrow + w4 * 32 + t * 128) : "memory");
      wait_until(t0 + MODE_B);
      load_row(H, xrow, t);
    }
    {
      const uint32_t part = base + OFF_PART + wg * 512 + g * 32, st = base + OFF_KV + wg * BT + (w4 * 14 + mi) * 128 + r8 * 16;
#pragma unroll
      for (int ln = 0; ln < 2; ln++) {
        float s0 = 0.f, s1 = 0.f, q0 = 0.f, q1 = 0.f;
#pragma unroll
        for (int j = 0; j < 14; j++) { const float a = bf_lo(H[j]), c = bf_hi(H[j]); s0 += a; s1 += c; q0 = fmaf(a, a, q0); q1 = fmaf(c, c, q1); }
        s0 += s1; q0 += q1;
#pragma unroll
        for (int o = 1; o < 4; o <<= 1) { s0 += __shfl_xor_sync(0xffffffffu, s0, o); q0 += __shfl_xor_sync(0xffffffffu, q0, o); }
        if (t == 0) sts64(part + ln * 256 + w4 * 8, s0, q0);
        OBS(tid == 0 && ln == 0, 0);
        named_sync(1 + wg, 128);
        const uint4 u = lds128(part + ln * 256), v = lds128(part + ln * 256 + 16);
        const float mean = ((__uint_as_float(u.x) + __uint_as_float(u.z)) + (__uint_as_float(v.x) + __uint_as_float(v.z))) * (1.0f / D_);
        const float sq = (__uint_as_float(u.y) + __uint_as_float(u.w)) + (__uint_as_float(v.y) + __uint_as_float(v.w));
        float sd;
        asm("sqrt.approx.ftz.f32 %0, %1;" : "=f"(sd) : "f"(rbf(rbf(fmaxf(fmaf(-mean, mean, sq * (1.0f / D_)), 0.f)) + 1e-5f)));
        const float r = rcp_fast(rbf(sd)), rh = rbf(r);
        const uint32_t m2 = pack2(mean, mean), rh2 = pack2(rh, rh), rl2 = pack2(r - rh, r - rh);
#pragma unroll
        for (int j = 0; j < 14; j++) { const uint32_t d = hsub2(H[j], m2); H[j] = hfma2(d, rh2, hmul2(d, rl2)); }
#pragma unroll
        for (int i = 0; i < 3; i++) stsm4(st + ln * GRP + i * 512, H[4 * i], H[4 * i + 1], H[4 * i + 2], H[4 * i + 3]);
        stsm2(st + ln * GRP + 1536, H[12], H[13]);
        if (ln || !wg) named_arrive(ln ? 10 - wg : 14, 160);
      }
      OBS(rel, 1 + wg);
    }
    named_sync(12 + wg, 160);
    asm volatile("setmaxnreg.inc.sync.aligned.u32 232;");
    uint32_t hb[2];
#pragma unroll
    for (int i = 0; i < 2; i++) {
      asm volatile("ld.relaxed.cta.global.u16 %0, [%1];" : "=r"(hb[i]) : "l"((wg ? p.b2 + mt * 64 : p.b1 + (g1 ? ft * 64 : 0)) + w4 * 16 + g + i * 8) : "memory");
    }
    if (!g1) {
      const int kg0 = (mt & 3) * 14 + dt * 4, nk = dt < 3 ? 4 : 2;
      mbar_wait(bars + B_RT, 0);
      OBS(tid == 0, 7);
      if (w4 < nk) {
        const int c = (r8 + mi + wg * 4) & 7;
        const uint32_t src = base + ((r8 >> 1) * 2 * nk + 2 * w4 + (r8 & 1)) * 2688 + c * 16, dst = base + (12 + w4) * GRP + c * 128 + r8 * 16;
#pragma unroll 1
        for (int m = 0; m < 3; m++) {
          uint4 v[7];
#pragma unroll
          for (int l = 0; l < 7; l++) v[l] = lds128(src + m * 896 + l * 128);
#pragma unroll
          for (int l = 0; l < 7; l++) sts128(dst + m * 4 * GRP + l * 1024, v[l].x, v[l].y, v[l].z, v[l].w);
        }
      }
      smem_fence();
      named_sync(0, 256);
      OBS(tid == 0, 5);
      if (warp == 0 && elect()) {
        mbar_expect_tx(bars + B_RT, nk * GRP);
        bulk_g2s(base, p.wo + kg0 * GRP, nk * GRP, bars + B_RT);
#pragma unroll
        for (int m = 0; m < 3; m++) {
          bulk_s2g(g_scr + (G_W + m * 56 + kg0) * GRP, base + (12 + (m + 1) % 3 * 4) * GRP, nk * GRP);
          if (m != 1) publish(m ? C_W2 : C_W);
        }
        mbar_arrive(bars + B_F1);
        OBS(1, 6);
      }
      if (wg) {
        mbar_wait(bars + B_RT, 1);
#pragma unroll 1
        for (int i = 0; i < nk; i++) {
          const uint32_t src = base + i * GRP + g * 896 + w4 * 224, st = base + (4 + i) * GRP + (w4 * 14 + mi) * 128 + r8 * 16;
#pragma unroll
          for (int j = 0; j < 3; j++) { const uint4 v = lds128(src + j * 64 + t * 16); stsm4(st + j * 512, v.x, v.y, v.z, v.w); }
          stsm2(st + 1536, lds32(src + 192 + t * 8), lds32(src + 196 + t * 8));
        }
        smem_fence();
        named_sync(2, 128);
        if (w4 == 0 && elect()) {
          bulk_s2g(g_scr + (G_WO + kg0) * GRP, base + 4 * GRP, nk * GRP);
          publish(C_U);
          mbar_arrive(bars + B_F1);
          OBS(1, 16);
        }
      }
      __syncwarp();
    }
    uint32_t ok = 0;
    auto nohook = [](int) {};
#ifdef DBG_OBS
#define OBS0(c, i) do { mbar_wait(bars + ((c) & 7) * 8, ((c) >> 3) & 1); ok = 1; OBS(rel, i); } while (0)
#else
#define OBS0(c, i) ok = 0
#endif
    const uint32_t gx = base + 8192 + (tid & 127) * 16;
    if (wg == 0) {
      float acc[56];
      const uint32_t ust = base + OFF_U + w4 * 3584 + (mi >> 1) * 128;
      if (g1) {
        if (w4 == 3 && TRIG1) {
          float z[4] = {};
          uint32_t tn = t0 + TRIG0;
#pragma unroll 1
          for (int n = 0; n < 64 && !mbar_try(bars + B_TS, 0); n++) {
            while ((int)(clock() - tn) < 0 && !mbar_try(bars + B_TS, 0));
            asm volatile("mma.sync.aligned.m16n8k16.row.col.f32.bf16.bf16.f32 {%0,%1,%2,%3}, {%4,%4,%4,%4}, {%4,%4}, {%0,%1,%2,%3};" : "+f"(z[0]), "+f"(z[1]), "+f"(z[2]), "+f"(z[3]) : "r"(threadIdx.y));
            tn += TRIG1 + __float_as_uint(z[0]);
          }
        }
#pragma unroll
        for (int i = 0; i < 56; i++) { acc[i] = bf_lo(hb[(i >> 1) & 1]); asm volatile("" : "+f"(acc[i])); }
        OBS0(0, 5);
#pragma unroll 1
        for (int r = 0; r < 4; r++)
#pragma unroll
          for (int c = 0; c < 8; c++) stage<1>(acc, p.dw, p.db, c, c, r & 1, ok, false, rel && (c || r), [&](int k) { if (c == 7 && k == 3 - HK) arrive_if(3, r == 3); });
        wg_wait<0>();
        if (rel) mbar_arrive(bars + B_EMPTY + 7 * 8);
        OBS(rel, 6);
        auto gelu2 = [](float a, float c) {
          return pack2(fmaf(a, tanh_fast(a * fmaf(a * a, 0.0356774081f, 0.7978845608f)), a), fmaf(c, tanh_fast(c * fmaf(c * c, 0.0356774081f, 0.7978845608f)), c)); };
#if UH
        const uint32_t us = base + OFF_U + (w4 * 2 + (mi & 1)) * 896 + (mi >> 1) * 128 + r8 * 16;
#pragma unroll 1
        for (int hf = 0; hf < 2; hf++) {
          uint32_t R[14];
#pragma unroll
          for (int j = 0; j < 14; j++) R[j] = gelu2(acc[2 * j], acc[2 * j + 1]);
#pragma unroll
          for (int j = 0; j < 3; j++) stsm4(us + hf * GRP + j * 256, R[4 * j], R[4 * j + 1], R[4 * j + 2], R[4 * j + 3]);
          stsm2(us + hf * GRP + 768, R[12], R[13]);
          named_arrive(hf ? 10 : 14, 160);
#pragma unroll
          for (int j = 0; j < 28; j++) acc[j] = acc[28 + j];
        }
        OBS(rel, 30);
#else
#pragma unroll
        for (int n = 0; n < 14; n += 2)
          stsm4(ust + (mi & 1) * 1792 + r8 * 16 + n * 128, gelu2(acc[4 * n], acc[4 * n + 1]), gelu2(acc[4 * n + 2], acc[4 * n + 3]), gelu2(acc[4 * n + 4], acc[4 * n + 5]), gelu2(acc[4 * n + 6], acc[4 * n + 7]));
        OBS(rel, 30);
        smem_fence();
        named_sync(1, 128);
        if (w4 == 0 && elect()) { tma_store(&m_b14, d1 * 14, G_U + ft * 8, base + OFF_U); publish(C_U, SY_U); OBS(1, 7); }
        __syncwarp();
#endif
      } else named_arrive(3, 256);
      named_sync(4, 256);
      fresh(acc);
      OBS0(14, 9);
#pragma unroll
      for (int c = 14; c < 21; c++) stage<0>(acc, p.dx, p.db, c & 7, c - 14, (c >> 3) & 1, ok, c == 14, rel && c > 14, [&](int k) { if (SA >= 0 && c == 20 && k == 3 - HK) named_arrive(5, 256); });
      if (SA < 0) smem_fence();
      wg_wait<0>();
      if (rel) mbar_arrive(bars + B_EMPTY + 4 * 8);
      {
        uint32_t Q[8][4];
#pragma unroll
        for (int i = 0; i < 16; i++) {
          const int n = i - (i + 4) / 8;
#pragma unroll
          for (int h = 0; h < 2; h++) {
            const uint32_t v = pack2(acc[4 * n + 2 * h], acc[4 * n + 2 * h + 1]);
            Q[i >> 1][(i & 1) * 2 + h] = (i & 7) == 3 ? (t < 2 ? v : 0u) : ((i & 7) == 4 ? (t < 2 ? 0u : v) : v);
          }
        }
#pragma unroll
        for (int i = 0; i < 8; i++) pin(Q[i]);
        float Sc[4][40], O[4][16];
        mbar_wait(bars + B_HALO, 0);
        OBS(rel, 11);
#pragma unroll
        for (int hh = 0; hh < 4; hh++) fresh(Sc[hh]);
        wg_fence();
        if (SA >= 0) named_sync(N_GO, 256);
#pragma unroll
        for (int k = 0; k < 2; k++)
#pragma unroll
          for (int hh = 0; hh < 4; hh++) {
            if (k == 1 && hh == (SA < 0 ? 2 : 3)) named_arrive(SA < 0 ? 5 : N_DONE, 256);
            wgmma_rs_n80<0>(Sc[hh], Q[hh * 2 + k], dlo(OFF_KV + (hh * 7 / 2 + 2 * k) * 128, 128), p.dk, k);
          }
        wg_commit();
        const bool e0 = 2 * t > g, e1 = 2 * t + 1 > g;
        const uint32_t em = (e0 ? 0xffffu : 0u) | (e1 ? 0xffff0000u : 0u);
        uint32_t L[4][2], M[5], edge = mt == 0 && w4 == 0 ? em : 0u, low = lane < 16 ? ~0u : 0u;
#pragma unroll
        for (int j = 0; j < 5; j++) { M[j] = j == w4 ? em : (j == w4 + 1 ? ~em : 0u); asm volatile("" : "+r"(M[j])); }
        asm volatile("" : "+r"(low), "+r"(edge));
        wg_wait<0>();
        OBS(rel, 12);
        auto pick = [&](int w) {
#pragma unroll
          for (int hh = 0; hh < 4; hh++)
#pragma unroll
            for (int h = 0; h < 2; h++) {
              const int i = (2 * w + h) * 4 + 2 * h;
              L[hh][h] = pack2(e0 ? Sc[hh][i] : Sc[hh][i + 8], e1 ? Sc[hh][i + 1] : Sc[hh][i + 9]);
              asm volatile("" : "+r"(L[hh][h]));
            }
        };
        if (w4 == 0) pick(0); else if (w4 == 1) pick(1); else if (w4 == 2) pick(2); else pick(3);
        uint32_t A[4][5][4], sign = 0;
#pragma unroll
        for (int hh = 0; hh < 4; hh++) {
          uint32_t l[2];
#pragma unroll
          for (int h = 0; h < 2; h++) l[h] = (hfma2(L[hh][h], 0x3e423e42u, hmul2(L[hh][h], 0xb9f7b9f7u)) & ~edge) | (0xce6ece6eu & edge);
          uint32_t mx = hmax2(__byte_perm(l[0], l[1], 0x5410), __byte_perm(l[0], l[1], 0x7632));
          mx = hmax2(mx, __shfl_xor_sync(0xffffffffu, mx, 1));
          mx = hmax2(mx, __shfl_xor_sync(0xffffffffu, mx, 2));
#pragma unroll
          for (int h = 0; h < 2; h++) {
            const float m = (h ? bf_hi(mx) : bf_lo(mx)) * -LOG2E;
            const float p0 = ex2_fast(fmaf(bf_lo(l[h]), LOG2E, m)), p1 = ex2_fast(fmaf(bf_hi(l[h]), LOG2E, m));
            float sm = p0 + p1;
            sm += __shfl_xor_sync(0xffffffffu, sm, 1);
            sm += __shfl_xor_sync(0xffffffffu, sm, 2);
            const float inv = rcp_fast(sm);
            const uint32_t pp = pack2(p0 * inv, p1 * inv);
#pragma unroll
            for (int j = 0; j < 5; j++) { A[hh][j][3 * h] = pp & M[j] & low; A[hh][j][1 + h] = pp & M[j] & ~low; }
            sign |= pp;
          }
        }
#pragma unroll
        for (int hh = 0; hh < 4; hh++) fresh(O[hh]);
#pragma unroll
        for (int i = 0; i < 20; i++) pin(A[i / 5][i % 5]);
        OBS(rel, 13);
        mbar_wait(bars + B_HALO + 8 + (sign >> 31), 0);
        if (w4 == 0) named_arrive(11, 64);
        OBS(rel, 31);
        named_sync(N_GO, 256);
        wg_fence();
        const uint32_t ost = ust + (r8 >> 2) * 1792 + (((2 * r8) & 7) + ((mi & 1) ^ (r8 >> 2))) * 16;
        auto opair = [&](int m, int h2) {
          const int hb2 = m / 7 * 2, r = m % 7;
          if (r < 3) return pack2(O[hb2][4 * r + h2], O[hb2][4 * r + h2 + 1]);
          if (r == 3) return pack2(t < 2 ? O[hb2][12 + h2] : O[hb2 + 1][h2], t < 2 ? O[hb2][13 + h2] : O[hb2 + 1][h2 + 1]);
          return pack2(O[hb2 + 1][4 * (r - 3) + h2], O[hb2 + 1][4 * (r - 3) + h2 + 1]);
        };
        auto oput = [&](int n) { stsm4(ost + n * 128, opair(n, 0), opair(n, 2), opair(n + 1, 0), opair(n + 1, 2)); };
        auto pv = [&](int hh, int j) { wgmma_rs_n32<1>(O[hh], A[hh][j], dlo(OFF_KV + KV + hh * 7 / 2 * 128 + j * 3584, 1792), p.db, j); };
#if PVS
#pragma unroll
        for (int i = 0; i < 10; i++) pv(i & 1, i >> 1);
        wg_commit();
#pragma unroll
        for (int i = 0; i < 4; i++) pv(2 + (i & 1), i >> 1);
        wg_commit();
        wg_wait<1>();
#pragma unroll
        for (int i = 4; i < 10; i++) {
          if (i == 8) named_arrive(N_DONE, 256);
          pv(2 + (i & 1), i >> 1);
          if (i < 7) oput((i - 4) * 2);
        }
        wg_commit();
        OBS(rel, 19);
        wg_wait<0>();
        OBS(rel, 21);
#pragma unroll
        for (int n = 6; n < 14; n += 2) oput(n);
#else
#pragma unroll
        for (int i = 0; i < 20; i++) { if (i == 18) named_arrive(N_DONE, 256); pv(i & 3, i >> 2); }
        wg_commit();
        OBS(rel, 19);
        wg_wait<0>();
        OBS(rel, 21);
#pragma unroll
        for (int n = 0; n < 14; n += 2) oput(n);
#endif
        OBS(rel, 29);
        smem_fence();
        if (PS_O) {
          __syncwarp();
          OBS(rel, 14);
          if (elect()) {
            wait_until(clock() + w4 * PS_O);
            store_paced(g_scr + (G_O + mt * 8 + w4 * 2) * GRP + dt * 1792, GRP, base + OFF_U + w4 * 3584, 1792, 2, 4 * PS_O);
            publish(C_O + mt);
          }
        } else {
          named_sync(1, 128);
          OBS(rel, 14);
          if (w4 == 0 && elect()) { tma_store(&m_b14, dt * 14, G_O + mt * 8, base + OFF_U); publish(C_O + mt); }
        }
        OBS(rel, 120);
        __syncwarp();
      }
      const int ro = (mt * 64 + w4 * 16 + g) * (D_ * 2) + dt * 224;
      uint32_t X[28], G[28];
      mbar_wait(bars + B_RES, 0);
#pragma unroll
      for (int h = 0; h < 2; h++) {
        const uint32_t a = base + OFF_KV + (w4 * 16 + h * 8 + g) * 224;
#pragma unroll
        for (int i = 0; i < 3; i++) { const uint4 v = lds128(a + i * 64 + t * 16); X[h * 14 + 4 * i] = v.x; X[h * 14 + 4 * i + 1] = v.y; X[h * 14 + 4 * i + 2] = v.z; X[h * 14 + 4 * i + 3] = v.w; }
        X[h * 14 + 12] = lds32(a + 192 + t * 8); X[h * 14 + 13] = lds32(a + 196 + t * 8);
      }
      unsigned char *outp = p.out + ro + t * 16, *outq = p.out + ro + 192 + t * 8;
      asm volatile("" : "+l"(outp), "+l"(outq));
      named_sync(8, 256);
      fresh(acc);
      OBS0(49, 25);
#pragma unroll
      for (int c = 49; c < 56; c++) stage<0>(acc, p.dx, p.db, c & 7, (c + 2) & 7, 0, ok, c == 49, false, nohook);
      named_sync(9, 256);
#pragma unroll
      for (int j = 0; j < 28; j += 4) { const uint4 v = lds128(gx + j * 512); G[j] = v.x; G[j + 1] = v.y; G[j + 2] = v.z; G[j + 3] = v.w; }
      wg_wait<0>();
      OBS(rel, 27);
#pragma unroll
      for (int i = 0; i < 4; i++)
#pragma unroll
        for (int h = 0; h < 2; h++) {
          uint32_t R[4];
#pragma unroll
          for (int j = 0; j < (i < 3 ? 4 : 2); j++) {
            const int n = 4 * i + j;
            R[j] = hadd2(X[h * 14 + n], hmul2(pack2(acc[4 * n + 2 * h], acc[4 * n + 2 * h + 1]), G[2 * n + h]));
          }
          if (i < 3) asm volatile("st.global.v4.u32 [%0], {%1,%2,%3,%4};" :: "l"(outp + h * 8 * D_ * 2 + i * 64), "r"(R[0]), "r"(R[1]), "r"(R[2]), "r"(R[3]) : "memory");
          else asm volatile("st.global.v2.u32 [%0], {%1,%2};" :: "l"(outq + h * 8 * D_ * 2), "r"(R[0]), "r"(R[1]) : "memory");
        }
      OBS(rel, 28);
#ifdef DBG_OBS
      named_sync(1, 128);
      { uint32_t v = lds32(base + OFF_OBS + tid * 4); if (tid == 126) v = t0; if (tid == 127) asm volatile("mov.u32 %0, %%smid;" : "=r"(v)); g_obs[b * 128 + tid] = v; }
#endif
    } else {
      if (g1 && w4 == 1) {
        if (!EARLY || ld_relaxed(C_H + 1) < 128) { mbar_wait(bars + B_TS, 0); spin_ge(C_H + 1, 128); }
        if (lane == 0) mbar_arrive(bars + B_F0);
        __syncwarp();
      }
      {
        float ka[56], va[56];
        const uint32_t kst = base + OFF_KV + (2 + 2 * w4 + (mi & 1)) * 1792 + (mi >> 1) * 128 + r8 * 16;
        auto put = [&](const float (&a)[56], uint32_t dst, int n) {
          stsm4(dst + n * 128, pack2(a[4 * n], a[4 * n + 1]), pack2(a[4 * n + 2], a[4 * n + 3]), pack2(a[4 * n + 4], a[4 * n + 5]), pack2(a[4 * n + 6], a[4 * n + 7])); };
        named_sync(3, 256);
        fresh(ka);
        OBS0(0, 8);
#pragma unroll
        for (int c = 0; c < 7; c++) stage<0>(ka, p.dx, p.db, c, c, 0, ok, c == 0, rel && c, nohook);
        fresh(va);
#pragma unroll
        for (int c = 7; c < 14; c++)
          stage<0>(va, p.dx, p.db, c & 7, c - 7, c >> 3, ok, c == 7, rel, [&](int k) {
            if (c > 7 && (c - 8) * 4 + k < 7) put(ka, kst, (c - 8) * 8 + k * 2);
            if (c == 9 && k == 3 && w4 == 3) named_arrive(11, 64);
            if (c == 13 && k == 3 - HK) named_arrive(4, 256); });
        wg_wait<0>();
        if (rel) mbar_arrive(bars + B_EMPTY + 5 * 8);
#pragma unroll
        for (int n = 0; n < 14; n += 2) put(va, kst + KV, n);
        if (w4 == 3) named_arrive(0, 64);
        smem_fence();
      }
      float acc[56];
#pragma unroll
      for (int i = 0; i < 2; i++) { hb[i] = hmul2(hb[i] * 0x10001u, 0x3f003f00u); asm volatile("" : "+r"(hb[i])); }
#pragma unroll
      for (int i = 0; i < 56; i++) { acc[i] = 0.f; asm volatile("" : "+f"(acc[i])); }
      named_sync(5, 256);
      OBS0(21, 10);
#pragma unroll 1
      for (int r = 0; ; r++) {
#pragma unroll
        for (int j = 0; j < 8; j++) {
          const bool site = j == SA % 8 || j == SB % 8, yield = (j == SA % 8 && r == SA / 8) || (j == SB % 8 && r == SB / 8);
          stage<1>(acc, p.dw, p.db, (j + 5) & 7, (j + 7) & 7, (r + (j > 2)) & 1, ok, false, rel && (j || r), [&](int k) {
            if (k == 3 - HK) { if (site) arrive_if(N_GO, yield); if (j == 3) arrive_if(8, r == 3); } });
          if (site && yield) named_sync(N_DONE, 256);
          if (j == 3 && r == 3) goto gemm2_done;
        }
      }
      gemm2_done:
      wg_wait<0>();
      OBS(rel, 24);
#pragma unroll
      for (int j = 0; j < 28; j += 4) {
        uint32_t R[4];
#pragma unroll
        for (int i = 0; i < 4; i++) {
          const uint32_t hh = hfma2(pack2(acc[2 * (j + i)], acc[2 * (j + i) + 1]), 0x3e803e80u, hb[i & 1]);
          const float a = bf_lo(hh), c = bf_hi(hh);
          R[i] = pack2(fmaf(a, tanh_fast(a), a), fmaf(c, tanh_fast(c), c));
        }
        sts128(gx + j * 512, R[0], R[1], R[2], R[3]);
      }
      OBS(rel, 26);
      named_arrive(9, 256);
    }
  }
}

typedef CUresult (*EncFn)(CUtensorMap*, CUtensorMapDataType, cuuint32_t, void*, const cuuint64_t*, const cuuint64_t*, const cuuint32_t*,
                          const cuuint32_t*, CUtensorMapInterleave, CUtensorMapSwizzle, CUtensorMapL2promotion, CUtensorMapFloatOOBfill);
void enc(EncFn f, CUtensorMap* m, const void* ptr, const cuuint64_t (&gd)[4], const cuuint64_t (&gs)[3], const cuuint32_t (&bx)[4], CUtensorMapSwizzle sw) {
  cuuint32_t es[4] = {1, 1, 1, 1};
  f(m, CU_TENSOR_MAP_DATA_TYPE_BFLOAT16, 4, (void*)ptr, gd, gs, bx, es, CU_TENSOR_MAP_INTERLEAVE_NONE, sw,
    CU_TENSOR_MAP_L2_PROMOTION_L2_128B, CU_TENSOR_MAP_FLOAT_OOB_FILL_NONE);
}
}

extern "C" void kernel_launch(void* const* d_in, const int* in_sizes, int n_in, void* d_out, int out_size) {
  (void)in_sizes; (void)n_in; (void)out_size;
  void* fp = nullptr;
  cudaDriverEntryPointQueryResult qr;
  cudaGetDriverEntryPoint("cuTensorMapEncodeTiled", &fp, cudaEnableDefault, &qr);
  EncFn f = (EncFn)fp;
  CUtensorMap m_w1, m_w2, m_b14, m_a8, m_x, m_b7;
  void* scr = nullptr;
  cudaGetSymbolAddress(&scr, g_scr);
  enc(f, &m_w1, d_in[4], {F_, 8, 2, S_ / 16}, {F_ * 4, F_ * 2, F_ * 32}, {64, 8, 2, 4}, CU_TENSOR_MAP_SWIZZLE_128B);
  enc(f, &m_w2, d_in[6], {S_, 1, 1, F_}, {S_ * 2, S_ * 2, S_ * 2}, {64, 1, 1, 64}, CU_TENSOR_MAP_SWIZZLE_128B);
  enc(f, &m_b14, scr, {64, 56, 1, G_END}, {128, GRP, GRP}, {64, 14, 1, 8}, CU_TENSOR_MAP_SWIZZLE_NONE);
  enc(f, &m_b7, scr, {64, 56, 1, G_END}, {128, GRP, GRP}, {64, 7, 1, 8}, CU_TENSOR_MAP_SWIZZLE_NONE);
  enc(f, &m_a8, scr, {64, 56, 1, G_END}, {128, GRP, GRP}, {64, 8, 1, 8}, CU_TENSOR_MAP_SWIZZLE_NONE);
  enc(f, &m_x, d_in[0], {D_, 1, 1, S_}, {D_ * 2, D_ * 2, D_ * 2}, {112, 1, 1, 64}, CU_TENSOR_MAP_SWIZZLE_NONE);
  Params p;
  p.x = (const unsigned char*)d_in[0]; p.wqkv = (const unsigned char*)d_in[1]; p.wo = (const unsigned char*)d_in[2];
  p.w1 = (const unsigned char*)d_in[4]; p.b1 = (const unsigned short*)d_in[5];
  p.w2 = (const unsigned char*)d_in[6]; p.b2 = (const unsigned short*)d_in[7];
  p.out = (unsigned char*)d_out;
  p.dw = 0x40000040u; p.dx = 64; p.db = 8; p.dk = 112;
#ifdef TUNE
  for (int i = 0; i < NTUNE; i++) p.tune[i] = tune_vals[i];
#endif
  cudaFuncSetAttribute(fused_kernel, cudaFuncAttributeMaxDynamicSharedMemorySize, SMEM_BYTES);
  fused_kernel<<<128, NTHREADS, SMEM_BYTES, cudaStreamPerThread>>>(m_w1, m_w2, m_b14, m_a8, m_x, m_b7, p);
}
```

```cpp
#include <cuda_runtime.h>
#include <cuda.h>
#include <cuda_bf16.h>
#include <stdint.h>

template<int TA, int TB> __device__ __forceinline__ void wgmma_n112(float (&d)[56], uint32_t al, uint32_t ah, uint32_t bl, uint32_t bh, int sc) {
  asm volatile("{\n.reg .pred p;\n.reg .b64 a, b;\nsetp.ne.b32 p, %60, 0;\nmov.b64 a, {%56, %57};\nmov.b64 b, {%58, %59};\n"
    "wgmma.mma_async.sync.aligned.m64n112k16.f32.bf16.bf16 {%0, %1, %2, %3, %4, %5, %6, %7, %8, %9, %10, %11, %12, %13, %14, %15, %16, %17, %18, %19, %20, %21, %22, %23, %24, %25, %26, %27, %28, %29, %30, %31, %32, %33, %34, %35, %36, %37, %38, %39, %40, %41, %42, %43, %44, %45, %46, %47, %48, %49, %50, %51, %52, %53, %54, %55}, a, b, p, 1, 1, %61, %62;\n}\n"
    : "+f"(d[0]), "+f"(d[1]), "+f"(d[2]), "+f"(d[3]), "+f"(d[4]), "+f"(d[5]), "+f"(d[6]), "+f"(d[7]), "+f"(d[8]), "+f"(d[9]), "+f"(d[10]), "+f"(d[11]), "+f"(d[12]), "+f"(d[13]), "+f"(d[14]), "+f"(d[15]), "+f"(d[16]), "+f"(d[17]), "+f"(d[18]), "+f"(d[19]), "+f"(d[20]), "+f"(d[21]), "+f"(d[22]), "+f"(d[23]), "+f"(d[24]), "+f"(d[25]), "+f"(d[26]), "+f"(d[27]), "+f"(d[28]), "+f"(d[29]), "+f"(d[30]), "+f"(d[31]), "+f"(d[32]), "+f"(d[33]), "+f"(d[34]), "+f"(d[35]), "+f"(d[36]), "+f"(d[37]), "+f"(d[38]), "+f"(d[39]), "+f"(d[40]), "+f"(d[41]), "+f"(d[42]), "+f"(d[43]), "+f"(d[44]), "+f"(d[45]), "+f"(d[46]), "+f"(d[47]), "+f"(d[48]), "+f"(d[49]), "+f"(d[50]), "+f"(d[51]), "+f"(d[52]), "+f"(d[53]), "+f"(d[54]), "+f"(d[55])
    : "r"(al), "r"(ah), "r"(bl), "r"(bh), "r"(sc), "n"(TA), "n"(TB));
}

template<int TB> __device__ __forceinline__ void wgmma_rs_n80(float (&d)[40], const uint32_t (&a)[4], uint32_t bl, uint32_t bh, int sc) {
  asm volatile("{\n.reg .pred p;\n.reg .b64 b;\nsetp.ne.b32 p, %46, 0;\nmov.b64 b, {%44, %45};\n"
    "wgmma.mma_async.sync.aligned.m64n80k16.f32.bf16.bf16 {%0, %1, %2, %3, %4, %5, %6, %7, %8, %9, %10, %11, %12, %13, %14, %15, %16, %17, %18, %19, %20, %21, %22, %23, %24, %25, %26, %27, %28, %29, %30, %31, %32, %33, %34, %35, %36, %37, %38, %39}, {%40, %41, %42, %43}, b, p, 1, 1, %47;\n}\n"
    : "+f"(d[0]), "+f"(d[1]), "+f"(d[2]), "+f"(d[3]), "+f"(d[4]), "+f"(d[5]), "+f"(d[6]), "+f"(d[7]), "+f"(d[8]), "+f"(d[9]), "+f"(d[10]), "+f"(d[11]), "+f"(d[12]), "+f"(d[13]), "+f"(d[14]), "+f"(d[15]), "+f"(d[16]), "+f"(d[17]), "+f"(d[18]), "+f"(d[19]), "+f"(d[20]), "+f"(d[21]), "+f"(d[22]), "+f"(d[23]), "+f"(d[24]), "+f"(d[25]), "+f"(d[26]), "+f"(d[27]), "+f"(d[28]), "+f"(d[29]), "+f"(d[30]), "+f"(d[31]), "+f"(d[32]), "+f"(d[33]), "+f"(d[34]), "+f"(d[35]), "+f"(d[36]), "+f"(d[37]), "+f"(d[38]), "+f"(d[39])
    : "r"(a[0]), "r"(a[1]), "r"(a[2]), "r"(a[3]), "r"(bl), "r"(bh), "r"(sc), "n"(TB));
}

template<int TB> __device__ __forceinline__ void wgmma_rs_n32(float (&d)[16], const uint32_t (&a)[4], uint32_t bl, uint32_t bh, int sc) {
  asm volatile("{\n.reg .pred p;\n.reg .b64 b;\nsetp.ne.b32 p, %22, 0;\nmov.b64 b, {%20, %21};\n"
    "wgmma.mma_async.sync.aligned.m64n32k16.f32.bf16.bf16 {%0, %1, %2, %3, %4, %5, %6, %7, %8, %9, %10, %11, %12, %13, %14, %15}, {%16, %17, %18, %19}, b, p, 1, 1, %23;\n}\n"
    : "+f"(d[0]), "+f"(d[1]), "+f"(d[2]), "+f"(d[3]), "+f"(d[4]), "+f"(d[5]), "+f"(d[6]), "+f"(d[7]), "+f"(d[8]), "+f"(d[9]), "+f"(d[10]), "+f"(d[11]), "+f"(d[12]), "+f"(d[13]), "+f"(d[14]), "+f"(d[15])
    : "r"(a[0]), "r"(a[1]), "r"(a[2]), "r"(a[3]), "r"(bl), "r"(bh), "r"(sc), "n"(TB));
}

template<int TB> __device__ __forceinline__ void wgmma_rs_n112(float (&d)[56], const uint32_t (&a)[4], uint32_t bl, uint32_t bh, int sc) {
  asm volatile("{\n.reg .pred p;\n.reg .b64 b;\nsetp.ne.b32 p, %62, 0;\nmov.b64 b, {%60, %61};\n"
    "wgmma.mma_async.sync.aligned.m64n112k16.f32.bf16.bf16 {%0, %1, %2, %3, %4, %5, %6, %7, %8, %9, %10, %11, %12, %13, %14, %15, %16, %17, %18, %19, %20, %21, %22, %23, %24, %25, %26, %27, %28, %29, %30, %31, %32, %33, %34, %35, %36, %37, %38, %39, %40, %41, %42, %43, %44, %45, %46, %47, %48, %49, %50, %51, %52, %53, %54, %55}, {%56, %57, %58, %59}, b, p, 1, 1, %63;\n}\n"
    : "+f"(d[0]), "+f"(d[1]), "+f"(d[2]), "+f"(d[3]), "+f"(d[4]), "+f"(d[5]), "+f"(d[6]), "+f"(d[7]), "+f"(d[8]), "+f"(d[9]), "+f"(d[10]), "+f"(d[11]), "+f"(d[12]), "+f"(d[13]), "+f"(d[14]), "+f"(d[15]), "+f"(d[16]), "+f"(d[17]), "+f"(d[18]), "+f"(d[19]), "+f"(d[20]), "+f"(d[21]), "+f"(d[22]), "+f"(d[23]), "+f"(d[24]), "+f"(d[25]), "+f"(d[26]), "+f"(d[27]), "+f"(d[28]), "+f"(d[29]), "+f"(d[30]), "+f"(d[31]), "+f"(d[32]), "+f"(d[33]), "+f"(d[34]), "+f"(d[35]), "+f"(d[36]), "+f"(d[37]), "+f"(d[38]), "+f"(d[39]), "+f"(d[40]), "+f"(d[41]), "+f"(d[42]), "+f"(d[43]), "+f"(d[44]), "+f"(d[45]), "+f"(d[46]), "+f"(d[47]), "+f"(d[48]), "+f"(d[49]), "+f"(d[50]), "+f"(d[51]), "+f"(d[52]), "+f"(d[53]), "+f"(d[54]), "+f"(d[55])
    : "r"(a[0]), "r"(a[1]), "r"(a[2]), "r"(a[3]), "r"(bl), "r"(bh), "r"(sc), "n"(TB));
}

namespace {
constexpr int S_ = 2048, D_ = 448, F_ = 1792;
constexpr int SLOT = 22528, BT = 14336;
constexpr int OFF_KV = 8 * SLOT;
constexpr int OFF_X = OFF_KV - 7 * 8192;
constexpr int KV = 10 * 1792;
constexpr int OFF_PART = OFF_KV + 2 * BT;
constexpr int OFF_U = OFF_KV + 10 * 3584;
constexpr int OFF_BAR = OFF_U + BT;
constexpr uint32_t base = 1024, bars = base + OFF_BAR;
constexpr int OFF_OBS = OFF_BAR + 256;
constexpr int SMEM_BYTES = OFF_OBS + 768;
#ifdef TUNE
#define TV(i) p.tune[i]
const char* tune_names[] = {"DLY_B", "DLY_X", "DLY_W", "TPW", "DLY_R", "PF0", "PACE1", "PACE2", "SY_H", "SY_U", "SY_B", "PS_H", "NP_H", "PH_H", "NP_U", "PH_U", "PFN", "PF1", "PACE0", "PFR", "PACER", "DLY_Q", "DLY_D", "DLY_E", "PFD", "PQ"};
int tune_vals[] = {1000, 1000, 3600, 210, 0, 1900, 420, 400, 800, 1400, 1200, 150, 3, 230, 0, 300, 0, 0, 350, 99, 350, 1800, 0, 1500, 0, 200};
constexpr int NTUNE = 26;
#define DLY_B TV(0)
#define DLY_X TV(1)
#define DLY_W TV(2)
#define TPW TV(3)
#define DLY_R TV(4)
#define PF0 TV(5)
#define PACE1 TV(6)
#define PACE2 TV(7)
#define SY_H TV(8)
#define SY_U TV(9)
#define SY_B TV(10)
#define PS_H TV(11)
#define NP_H TV(12)
#define PH_H TV(13)
#define NP_U TV(14)
#define PH_U TV(15)
#define PFN TV(16)
#define PF1 TV(17)
#define PACE0 TV(18)
#define PFR TV(19)
#define PACER TV(20)
#define DLY_Q TV(21)
#define DLY_D TV(22)
#define DLY_E TV(23)
#define PFD TV(24)
#define PQ TV(25)
#else
#ifndef DLY_B
#define DLY_B 1000
#endif
#ifndef DLY_X
#define DLY_X 1000
#endif
#ifndef DLY_W
#define DLY_W 3300
#endif
#ifndef TPW
#define TPW 210
#endif
#ifndef DLY_R
#define DLY_R 0
#endif
#ifndef PF0
#define PF0 1600
#endif
#ifndef PACE1
#define PACE1 420
#endif
#ifndef PACE2
#define PACE2 400
#endif
#ifndef SY_H
#define SY_H 800
#endif
#ifndef SY_U
#define SY_U 1400
#endif
#ifndef SY_B
#define SY_B 1000
#endif
#ifndef PS_H
#define PS_H 150
#endif
#ifndef NP_H
#define NP_H 3
#endif
#ifndef PH_H
#define PH_H 230
#endif
#ifndef NP_U
#define NP_U 0
#endif
#ifndef PH_U
#define PH_U 300
#endif
#ifndef PFN
#define PFN 0
#endif
#ifndef PF1
#define PF1 0
#endif
#ifndef PACE0
#define PACE0 350
#endif
#ifndef PFR
#define PFR 99
#endif
#ifndef PACER
#define PACER 350
#endif
#ifndef DLY_Q
#define DLY_Q 1500
#endif
#ifndef DLY_D
#define DLY_D 0
#endif
#ifndef DLY_E
#define DLY_E 900
#endif
#ifndef PFD
#define PFD 0
#endif
#ifndef PQ
#define PQ 170
#endif
#endif
#ifndef SA
#define SA 0
#endif
#ifndef SB
#define SB 7
#endif
#ifndef PVS
#define PVS 0
#endif
#ifndef UH
#define UH 1
#endif
#ifndef EARLY
#define EARLY 1
#endif
#ifndef PU0
#define PU0 1200
#endif
#ifndef ANA
#define ANA 1
#endif
#ifndef PS_O
#define PS_O 130
#endif
#ifndef HK
#define HK 1
#endif
#ifndef HE
#define HE 1
#endif
#ifdef DBG_OBS
__device__ int g_obs[128 * 128];
#ifdef OBS_NS
#define OBS_CLK "%%globaltimer_lo"
#else
#define OBS_CLK "%%clock"
#endif
#define OBS(c, i) asm volatile("{\n.reg .pred p;\n.reg .u32 k;\nsetp.ne.u32 p, %1, 0;\nmov.u32 k, " OBS_CLK ";\nsub.u32 k, k, %2;\n@p st.shared.u32 [%0], k;\n}" :: "r"(base + OFF_OBS + (i) * 4), "r"((uint32_t)(c)), "r"(tz) : "memory")
#else
#define OBS(c, i) do {} while (0)
#endif
constexpr int NTHREADS = 384;
constexpr float LOG2E = 1.4426950408889634f;

constexpr int GRP = 7168;
constexpr int G_H = 0, G_O = 256, G_W = 512, G_U = G_W + 168, G_WO = G_U + 224, G_HALO = G_WO + 56, G_END = G_HALO + 128;
constexpr int SCR_BYTES = G_END * GRP;
__device__ __align__(1024) unsigned char g_scr[SCR_BYTES];
constexpr int C_TICKET = 0, C_W = 1, C_H = 2, C_U = 4, C_W2 = 5, C_O = 8, C_HALO = 40, C_END = 168;
__device__ __align__(128) unsigned g_cnt[C_END * 32];

__device__ __forceinline__ uint32_t smem_u32(const void* p) { return (uint32_t)__cvta_generic_to_shared(p); }
__device__ __forceinline__ void mbar_init(uint32_t bar, uint32_t cnt) { asm volatile("mbarrier.init.shared::cta.b64 [%0], %1;" :: "r"(bar), "r"(cnt)); }
__device__ __forceinline__ void mbar_expect_tx(uint32_t bar, uint32_t bytes) { asm volatile("mbarrier.arrive.expect_tx.shared::cta.b64 _, [%0], %1;" :: "r"(bar), "r"(bytes) : "memory"); }
__device__ __forceinline__ void mbar_arrive(uint32_t bar) { asm volatile("mbarrier.arrive.shared::cta.b64 _, [%0];" :: "r"(bar) : "memory"); }
__device__ __forceinline__ void mbar_wait(uint32_t bar, uint32_t parity) {
  asm volatile("{\n.reg .pred p;\n.reg .u32 n;\nmov.u32 n, 0;\nLAB_WAIT:\n"
               "mbarrier.try_wait.parity.shared::cta.b64 p, [%0], %1;\n@p bra DONE;\n"
               "add.u32 n, n, 1;\nsetp.lt.u32 p, n, 4000000;\n@p bra LAB_WAIT;\ntrap;\nDONE:\n}" :: "r"(bar), "r"(parity) : "memory");
}
__device__ __forceinline__ uint32_t mbar_try(uint32_t bar, uint32_t parity) {
  uint32_t ok;
  asm volatile("{\n.reg .pred p;\nmbarrier.test_wait.parity.shared::cta.b64 p, [%1], %2;\nselp.u32 %0, 1, 0, p;\n}" : "=r"(ok) : "r"(bar), "r"(parity) : "memory");
  return ok;
}
__device__ __forceinline__ void tma4d(uint32_t dst, const CUtensorMap* m, int c0, int c1, int c3, uint32_t bar) {
  asm volatile("cp.async.bulk.tensor.4d.shared::cluster.global.mbarrier::complete_tx::bytes [%0], [%1, {%3, %4, %6, %5}], [%2];"
               :: "r"(dst), "l"(m), "r"(bar), "r"(c0), "r"(c1), "r"(c3), "r"(0) : "memory");
}
__device__ __forceinline__ void tma_store(const CUtensorMap* m, int c1, int c3, uint32_t src) {
  asm volatile("cp.async.bulk.tensor.4d.global.shared::cta.bulk_group [%0, {%4, %2, %4, %3}], [%1];" :: "l"(m), "r"(src), "r"(c1), "r"(c3), "r"(0) : "memory");
}
__device__ __forceinline__ void bulk_g2s(uint32_t dst, const void* src, uint32_t bytes, uint32_t bar) {
  asm volatile("cp.async.bulk.shared::cluster.global.mbarrier::complete_tx::bytes [%0], [%1], %2, [%3];" :: "r"(dst), "l"(src), "r"(bytes), "r"(bar) : "memory");
}
__device__ __forceinline__ void bulk_s2g(void* dst, uint32_t src, uint32_t bytes) {
  asm volatile("cp.async.bulk.global.shared::cta.bulk_group [%0], [%1], %2;" :: "l"(dst), "r"(src), "r"(bytes) : "memory");
}
__device__ __forceinline__ void wg_fence() { asm volatile("wgmma.fence.sync.aligned;" ::: "memory"); }
__device__ __forceinline__ void wg_commit() { asm volatile("wgmma.commit_group.sync.aligned;" ::: "memory"); }
template <int N> __device__ __forceinline__ void wg_wait() { asm volatile("wgmma.wait_group.sync.aligned %0;" :: "n"(N) : "memory"); }
__device__ __forceinline__ void proxy_fence() { asm volatile("fence.proxy.async.global;" ::: "memory"); }
#ifndef LIGHT
#define LIGHT 1
#endif
__device__ __forceinline__ void smem_fence() {
  if (LIGHT == 2) return;
  if (LIGHT) asm volatile("mbarrier.init.shared::cta.b64 [%0], 1;" :: "r"(base + OFF_BAR + 248) : "memory");
  else asm volatile("fence.proxy.async.shared::cta;" ::: "memory");
}
__device__ __forceinline__ uint32_t gtime() { uint32_t v; asm volatile("mov.u32 %0, %%globaltimer_lo;" : "=r"(v)); return v; }
__device__ __forceinline__ void publish(int i, bool timed = false) {
  asm volatile("cp.async.bulk.commit_group;" ::: "memory");
  if (timed) asm volatile("red.relaxed.gpu.global.max.u32 [%0], %1;" :: "l"(&g_cnt[i * 32 + 1]), "r"(gtime()) : "memory");
  asm volatile("cp.async.bulk.wait_group 0;" ::: "memory");
  asm volatile("red.relaxed.gpu.global.inc.u32 [%0], 0xffffffff;" :: "l"(&g_cnt[i * 32]) : "memory");
}
__device__ __forceinline__ void spin_ge(int i, unsigned target) {
  asm volatile("{\n.reg .pred p;\n.reg .u32 n, v;\nmov.u32 n, 0;\nLAB_SPIN:\n"
               "ld.relaxed.gpu.global.u32 v, [%0];\nsetp.ge.u32 p, v, %1;\n@p bra DONE;\n"
               "add.u32 n, n, 1;\nsetp.lt.u32 p, n, 4000000;\n@p bra LAB_SPIN;\ntrap;\nDONE:\n}" :: "l"(&g_cnt[i * 32]), "r"(target) : "memory");
}
__device__ __forceinline__ unsigned ld_relaxed(int i) { unsigned v; asm volatile("ld.relaxed.gpu.global.u32 %0, [%1];" : "=r"(v) : "l"(&g_cnt[i * 32]) : "memory"); return v; }
__device__ __forceinline__ bool elect() {
  uint32_t r; asm volatile("{\n.reg .pred p;\nelect.sync _|p, 0xffffffff;\nselp.u32 %0, 1, 0, p;\n}" : "=r"(r)); return r != 0;
}
__device__ __forceinline__ void wait_until(uint32_t tn) { while ((int)(clock() - tn) < 0) __nanosleep(20); }
__device__ __forceinline__ void store_paced(unsigned char* dst, int dstep, uint32_t src, int sstep, int n, int gap, int bytes = 1792) {
  uint32_t tn = clock();
#pragma unroll 1
  for (int i = 0; i < n; i++) { wait_until(tn); bulk_s2g(dst, src, bytes); dst += dstep; src += sstep; tn += gap; }
}
__device__ __forceinline__ uint4 lds128(uint32_t a) { uint4 v; asm volatile("ld.shared.v4.u32 {%0,%1,%2,%3}, [%4];" : "=r"(v.x), "=r"(v.y), "=r"(v.z), "=r"(v.w) : "r"(a) : "memory"); return v; }
__device__ __forceinline__ uint32_t lds32(uint32_t a) { uint32_t v; asm volatile("ld.shared.u32 %0, [%1];" : "=r"(v) : "r"(a) : "memory"); return v; }
__device__ __forceinline__ void sts128(uint32_t p, uint32_t a, uint32_t b, uint32_t c, uint32_t d) { asm volatile("st.shared.v4.u32 [%0], {%1,%2,%3,%4};" :: "r"(p), "r"(a), "r"(b), "r"(c), "r"(d) : "memory"); }
__device__ __forceinline__ void sts64(uint32_t p, float a, float b) { asm volatile("st.shared.v2.f32 [%0], {%1,%2};" :: "r"(p), "f"(a), "f"(b) : "memory"); }
__device__ __forceinline__ void named_sync(int id, int n) { asm volatile("bar.sync %0, %1;" :: "r"(id), "r"(n) : "memory"); }
__device__ __forceinline__ void named_arrive(int id, int n) { asm volatile("bar.arrive %0, %1;" :: "r"(id), "r"(n) : "memory"); }
__device__ __forceinline__ constexpr uint32_t dlo(uint32_t off, uint32_t lbo) { return ((base + off) >> 4) | (lbo >> 4 << 16); }
__device__ __forceinline__ uint32_t pack2(float lo, float hi) { uint32_t r; asm("cvt.rn.bf16x2.f32 %0, %1, %2;" : "=r"(r) : "f"(hi), "f"(lo)); return r; }
__device__ __forceinline__ float bf_lo(uint32_t v) { return __uint_as_float(v << 16); }
__device__ __forceinline__ float bf_hi(uint32_t v) { return __uint_as_float(v & 0xffff0000u); }
__device__ __forceinline__ float rbf(float x) { return bf_lo(pack2(x, 0.f)); }
__device__ __forceinline__ uint32_t hsub2(uint32_t a, uint32_t b) { uint32_t r; asm("sub.rn.bf16x2 %0, %1, %2;" : "=r"(r) : "r"(a), "r"(b)); return r; }
__device__ __forceinline__ uint32_t hadd2(uint32_t a, uint32_t b) { uint32_t r; asm("add.rn.bf16x2 %0, %1, %2;" : "=r"(r) : "r"(a), "r"(b)); return r; }
__device__ __forceinline__ uint32_t hmax2(uint32_t a, uint32_t b) { uint32_t r; asm("max.bf16x2 %0, %1, %2;" : "=r"(r) : "r"(a), "r"(b)); return r; }
__device__ __forceinline__ uint32_t hmul2(uint32_t a, uint32_t b) { uint32_t r; asm("mul.rn.bf16x2 %0, %1, %2;" : "=r"(r) : "r"(a), "r"(b)); return r; }
__device__ __forceinline__ uint32_t hfma2(uint32_t a, uint32_t b, uint32_t c) { uint32_t r; asm("fma.rn.bf16x2 %0, %1, %2, %3;" : "=r"(r) : "r"(a), "r"(b), "r"(c)); return r; }
__device__ __forceinline__ float tanh_fast(float x) { float r; asm("tanh.approx.f32 %0, %1;" : "=f"(r) : "f"(x)); return r; }
__device__ __forceinline__ float rcp_fast(float x) { float r; asm("rcp.approx.ftz.f32 %0, %1;" : "=f"(r) : "f"(x)); return r; }
__device__ __forceinline__ float ex2_fast(float x) { float r; asm("ex2.approx.ftz.f32 %0, %1;" : "=f"(r) : "f"(x)); return r; }
__device__ __forceinline__ void mma16816(float (&c)[4], uint32_t a0, uint32_t a1, uint32_t a2, uint32_t a3, uint32_t b0, uint32_t b1) {
  asm volatile("mma.sync.aligned.m16n8k16.row.col.f32.bf16.bf16.f32 {%0,%1,%2,%3}, {%4,%5,%6,%7}, {%8,%9}, {%0,%1,%2,%3};"
               : "+f"(c[0]), "+f"(c[1]), "+f"(c[2]), "+f"(c[3]) : "r"(a0), "r"(a1), "r"(a2), "r"(a3), "r"(b0), "r"(b1));
}
__device__ __forceinline__ void ldsm4(uint32_t (&r)[4], uint32_t addr) {
  asm volatile("ldmatrix.sync.aligned.m8n8.x4.shared.b16 {%0,%1,%2,%3}, [%4];" : "=r"(r[0]), "=r"(r[1]), "=r"(r[2]), "=r"(r[3]) : "r"(addr) : "memory");
}
__device__ __forceinline__ void stsm4(uint32_t addr, uint32_t a, uint32_t b, uint32_t c, uint32_t d) {
  asm volatile("stmatrix.sync.aligned.m8n8.x4.shared.b16 [%0], {%1,%2,%3,%4};" :: "r"(addr), "r"(a), "r"(b), "r"(c), "r"(d) : "memory");
}
__device__ __forceinline__ void stsm2(uint32_t addr, uint32_t a, uint32_t b) {
  asm volatile("stmatrix.sync.aligned.m8n8.x2.shared.b16 [%0], {%1,%2};" :: "r"(addr), "r"(a), "r"(b) : "memory");
}
__device__ __forceinline__ void load_row(uint32_t (&r)[14], const unsigned char* p, int t) {
#pragma unroll
  for (int i = 0; i < 3; i++)
    asm volatile("ld.global.nc.L1::no_allocate.v4.u32 {%0,%1,%2,%3}, [%4];" : "=r"(r[4 * i]), "=r"(r[4 * i + 1]), "=r"(r[4 * i + 2]), "=r"(r[4 * i + 3]) : "l"(p + i * 64 + t * 16));
  asm volatile("ld.global.nc.L1::no_allocate.v2.u32 {%0,%1}, [%2];" : "=r"(r[12]), "=r"(r[13]) : "l"(p + 192 + t * 8));
}
__device__ __forceinline__ void lds_row(uint32_t* r, uint32_t a, int t) {
#pragma unroll
  for (int i = 0; i < 3; i++) { const uint4 v = lds128(a + i * 64 + t * 16); r[4 * i] = v.x; r[4 * i + 1] = v.y; r[4 * i + 2] = v.z; r[4 * i + 3] = v.w; }
  asm volatile("ld.shared.v2.u32 {%0,%1}, [%2];" : "=r"(r[12]), "=r"(r[13]) : "r"(a + 192 + t * 8) : "memory");
}

struct LnC { uint32_t m, rh, rl; float r; };
__device__ __forceinline__ LnC ln_consts(float mean, float var) {
  float sd;
  asm("sqrt.approx.ftz.f32 %0, %1;" : "=f"(sd) : "f"(rbf(rbf(var) + 1e-5f)));
  const float r = rcp_fast(rbf(sd)), rh = rbf(r);
  return {pack2(mean, mean), pack2(rh, rh), pack2(r - rh, r - rh), r};
}
__device__ __forceinline__ float variance(float mean, float sq) { return fmaxf(fmaf(-mean, mean, sq * (1.0f / D_)), 0.f); }
__device__ __forceinline__ uint32_t ln_apply(uint32_t x, const LnC& c) { const uint32_t d = hsub2(x, c.m); return hfma2(d, c.rh, hmul2(d, c.rl)); }

template <int N> __device__ __forceinline__ void fresh(float (&a)[N]) {
#pragma unroll
  for (int i = 0; i < N; i++) asm volatile("" : "=f"(a[i]));
}
__device__ __forceinline__ void pin(uint32_t (&a)[4]) { asm volatile("" : "+r"(a[0]), "+r"(a[1]), "+r"(a[2]), "+r"(a[3])); }
constexpr int B_EMPTY = 64, B_F0 = 128, B_F1 = 136, B_F2 = 144, B_F3 = 152, B_HALO = 160, B_RT = 176, B_RES = 184, B_TS = 192, B_F1B = 200, B_XF = 208, B_X = 216, S_FLAG = 224;
constexpr int N_GO = 6, N_DONE = 7;
__device__ __forceinline__ void watch_flag(int slot, int i, unsigned target) {
  asm volatile("{\n.reg .pred p;\n.reg .u32 n, v, t;\nmov.u32 n, 0;\nLAB_SPIN:\n"
               "ld.relaxed.gpu.global.v2.u32 {v, t}, [%1];\nsetp.ge.u32 p, v, %2;\n@p st.volatile.shared.v2.u32 [%0], {v, t};\n"
               "ld.volatile.shared.u32 v, [%0];\nsetp.ne.u32 p, v, 0;\n@p bra DONE;\n"
               "add.u32 n, n, 1;\nsetp.lt.u32 p, n, 4000000;\n@p bra LAB_SPIN;\ntrap;\nDONE:\n}" :: "r"(bars + S_FLAG + slot * 8), "l"(&g_cnt[i * 32]), "r"(target) : "memory");
}
__device__ __forceinline__ void wait_flag(int slot, int delay) {
  uint32_t v, last;
  do asm volatile("ld.volatile.shared.v2.u32 {%0, %1}, [%2];" : "=r"(v), "=r"(last) : "r"(bars + S_FLAG + slot * 8) : "memory"); while (!v);
  while (gtime() - last < (uint32_t)delay);
}
__device__ __forceinline__ void arrive_if(int id, bool on) {
  asm volatile("{\n.reg .pred p;\nsetp.ne.u32 p, %1, 0;\n@p bar.arrive %0, 256;\n}" :: "r"(id), "r"((uint32_t)on) : "memory");
}
template <int TA, class Hook>
__device__ __forceinline__ void stage(float (&acc)[56], uint32_t ah, uint32_t bh, int sb, uint32_t par, uint32_t& ok, int& g_tr, bool first, bool rel, Hook hook, const uint32_t (*X)[4] = nullptr) {
  if (!ok) mbar_wait(bars + sb * 8, par);
  wg_fence();
#pragma unroll
  for (int k = 0; k < 4; k++) {
    if constexpr (TA == 2) wgmma_rs_n112<1>(acc, X[k], dlo(sb * SLOT + 8192 + k * 3584, 1792), bh, k || !first);
    else wgmma_n112<TA, 1>(acc, dlo(sb * SLOT + k * (TA ? 2048 : 256), TA ? 8192 : 128), ah, dlo(sb * SLOT + 8192 + k * 3584, 1792), bh, k || !first);
    if (k == 1) ok = mbar_try(bars + ((sb + 1) & 7) * 8, sb == 7 ? par ^ 1 : par);
    hook(k);
  }
  wg_commit();
  wg_wait<1>();
#if DBG_TRACE == 2
  { const uint32_t tz = 0; OBS((threadIdx.x & 127) == 0, g_tr); g_tr++; }
#endif
  if (rel) mbar_arrive(bars + B_EMPTY + ((sb + 7) & 7) * 8);
}

template <uint32_t BYTES>
__device__ __forceinline__ void produce(int c, int cend, int rot, const CUtensorMap* mp, int c0, int c1, int s1, int c3, int s3, int tr = 0) {
#pragma unroll 1
  for (; c < cend; c++) {
    const uint32_t fb = base + OFF_BAR + (c & 7) * 8, dst = base + (BYTES ? 8192 : 0) + ((c + rot) & 7) * SLOT;
    mbar_wait(fb + B_EMPTY, ((c >> 3) & 1) ^ 1);
#if DBG_TRACE == 1
    if (BYTES) { const uint32_t tz = 0; OBS(1, 32 + tr + c); }
#endif
    if (BYTES) mbar_expect_tx(fb, BYTES);
    tma4d(dst, mp, c0, c1, c3, fb);
    c1 += s1; c3 += s3;
  }
}

struct Params {
  const unsigned char *x, *wqkv, *wo, *w1, *w2;
  const unsigned short *b1, *b2;
  unsigned char* out;
  uint32_t dw, dx, db, dk;
#ifdef TUNE
  int tune[NTUNE];
#endif
};

__global__ void __launch_bounds__(NTHREADS, 1)
fused_kernel(const Params p, const __grid_constant__ CUtensorMap m_w1, const __grid_constant__ CUtensorMap m_w2, const __grid_constant__ CUtensorMap m_b14,
             const __grid_constant__ CUtensorMap m_a8, const __grid_constant__ CUtensorMap m_b7, const __grid_constant__ CUtensorMap m_xt) {
  extern __shared__ __align__(1024) unsigned char smem_raw[];
  const uint32_t t0 = clock();
#ifdef DBG_OBS
  uint32_t tz; asm volatile("mov.u32 %0, " OBS_CLK ";" : "=r"(tz));
#endif
  const int tid = threadIdx.x, lane = tid & 31, b = blockIdx.x;
  const int g = lane >> 2, t = lane & 3, r8 = lane & 7, mi = lane >> 3;
  uint32_t H[14];
  if (tid < 128) load_row(H, p.x + (b * 16 + g) * (D_ * 2) + (tid >> 5) * 224, t);
  const int warp = __shfl_sync(0xffffffffu, tid >> 5, 0);
  const int dt = b & 3, mt = b >> 2;
  const bool g1 = b < 112;
  const int ft = mt, d1 = dt;
  if (warp >= 8) {
    if (warp == 8) {
      if (elect()) {
        if (smem_u32(smem_raw) != base) asm volatile("trap;");
#pragma unroll
        for (int i = 0; i < 28; i++) mbar_init(bars + i * 8, i * 8 == B_XF ? 8 : (i * 8 == B_F1 && !g1 ? 2 : 1));
        sts128(bars + S_FLAG, 0, 0, 0, 0);
        asm volatile("fence.mbarrier_init.release.cluster;" ::: "memory");
      }
      __syncwarp();
      named_arrive(12, 160); named_arrive(13, 160);
    }
    named_sync(15, 128);
    asm volatile("setmaxnreg.dec.sync.aligned.u32 80;");
    if (warp == 8) {
      unsigned tk = 0;
      if (elect()) {
        wait_until(t0 + DLY_B);
        mbar_expect_tx(bars + B_F2, GRP);
        bulk_g2s(base + OFF_U, p.x + (b * 2 + 1) * GRP, GRP, bars + B_F2);
        asm volatile("prefetch.tensormap [%0];" :: "l"(&m_xt) : "memory");
        wait_until(t0 + DLY_X);
        mbar_expect_tx(bars + B_X, 7 * 8192);
        asm volatile("cp.async.bulk.tensor.5d.shared::cluster.global.mbarrier::complete_tx::bytes [%0], [%1, {%4, %4, %4, %3, %4}], [%2];"
                     :: "r"(base + OFF_X), "l"(&m_xt), "r"(bars + B_X), "r"(mt * 4), "r"(0) : "memory");
        wait_until(t0 + DLY_D);
        asm volatile("prefetch.tensormap [%0];" :: "l"(&m_w1) : "memory");
        asm volatile("prefetch.tensormap [%0];" :: "l"(&m_b14) : "memory");
        if (g1) {
#pragma unroll 1
          for (int c = 0; c < 8; c++) {
            wait_until(t0 + DLY_W + c * TPW);
            if (c == 6) mbar_wait(bars + B_XF, 0);
            tma4d(base + c * SLOT, &m_w1, ft * 64, 0, c * 8, bars + c * 8);
          }
          produce<0>(8, 16, 0, &m_w1, ft * 64, 0, 0, 64, 8);
          produce<0>(16, 32, 0, &m_w1, ft * 64, 8, 0, 0, 8);
        } else {
          const int n = dt < 3 ? 16 : 8;
          mbar_expect_tx(bars + B_RT, n * 5376);
#pragma unroll 1
          for (int i = 0; i < n; i++) { wait_until(t0 + DLY_Q + i * PQ); bulk_g2s(base + i * 5376, p.wqkv + ((mt & 3) * 56 + dt * 16 + i) * 5376, 5376, bars + B_RT); }
        }
        if (PFD) {
          asm volatile("prefetch.tensormap [%0];" :: "l"(&m_b7) : "memory");
          asm volatile("prefetch.tensormap [%0];" :: "l"(&m_w2) : "memory");
          asm volatile("prefetch.tensormap [%0];" :: "l"(&m_a8) : "memory");
        }
        mbar_wait(bars + B_EMPTY + 5 * 8, 1);
        mbar_wait(bars + B_EMPTY + 5 * 8, 0);
        produce<0>(21, 49, 0, &m_w2, mt * 64, 0, 0, 0, 64);
        mbar_wait(bars + B_F3, 0);
        OBS(1, 22);
        produce<0>(49, 56, 0, &m_a8, 0, 0, 8, G_O + mt * 8, 0);
        tk = atomicInc(&g_cnt[C_TICKET * 32], 0xffffffffu);
      }
      if (__any_sync(0xffffffffu, tk == 127)) {
#pragma unroll 1
        for (int i = lane; i < C_END; i += 32) *(uint2*)&g_cnt[i * 32] = make_uint2(0, 0);
      }
    } else if (warp == 9) {
      if (elect()) {
        if (ld_relaxed(C_H) + ld_relaxed(C_H + 1) > 256) asm volatile("trap;");
        if (!PFD) {
          wait_until(t0 + DLY_E);
          asm volatile("prefetch.tensormap [%0];" :: "l"(&m_b7) : "memory");
          asm volatile("prefetch.tensormap [%0];" :: "l"(&m_w2) : "memory");
          asm volatile("prefetch.tensormap [%0];" :: "l"(&m_a8) : "memory");
        }
        if (g1) {
          if (NP_H == 0) watch_flag(0, C_H, 128);
          wait_flag(0, SY_H);
          OBS(1, 16);
          produce<SLOT>(0, 5, 0, &m_b14, 0, d1 * 14, 0, G_H, 8);
          mbar_wait(bars + B_XF, 0);
          produce<SLOT>(5, 16, 0, &m_b14, 0, d1 * 14, 0, G_H + 40, 8);
          mbar_wait(bars + B_F0, 0);
          OBS(1, 17);
          produce<SLOT>(16, 32, 0, &m_b14, 0, d1 * 14, 0, G_H + 128, 8);
        }
        mbar_wait(bars + B_F1, 0);
        OBS(1, 18);
        produce<BT>(0, 7, 0, &m_b14, 0, dt * 14, 0, G_W, 8, 32);
        mbar_wait(bars + B_F1B, 0);
        produce<BT>(7, 21, 0, &m_b14, 0, dt * 14, 0, G_W + 56, 8, 32);
        wait_flag(1, SY_U);
        OBS(1, 20);
        produce<SLOT>(21, 56, 0, &m_b14, 0, dt * 14, 0, G_U, 8, 32);
      }
    } else if (warp == 10) {
      uint32_t tn = t0 + PF0;
      const unsigned char* src = p.w1 + (b + (b & ~7)) * 3584 + lane * 128;
#pragma unroll 1
      for (int i = 0; i < 32; i++) {
        if (i == PFR) {
#pragma unroll 1
          for (int j = 0; j < 3; j++) {
            wait_until(t0 + DLY_R + j * PACER);
            if (j * 32 + lane < 74) asm volatile("prefetch.global.L2 [%0];" :: "l"(p.wqkv + min(b * 74 + j * 32 + lane, 9407) * 128) : "memory");
          }
        }
        wait_until(tn);
        if (i == 8) src -= 16 * 458752 - 8 * 3584;
        if (i == 16) src = p.w2 + b * 3584 + lane * 128;
        if (lane < 28) asm volatile("prefetch.global.L2 [%0];" :: "l"(src) : "memory");
        __syncwarp();
        src += i < 16 ? 2 * 458752 : 458752;
        tn += i < PFN ? PACE0 : (i < 16 ? PACE1 : PACE2);
        if (i + 1 == PFN) tn = t0 + PF1;
      }
      watch_flag(1, C_U, 128);
      spin_ge(C_O + mt, 16);
      if (lane == 0) mbar_arrive(bars + B_F3);
    } else {
      unsigned char* dst = g_scr + (G_H + b) * GRP;
      asm volatile("" : "+l"(dst));
      named_sync(10, 160);
      smem_fence();
      if (elect()) { bulk_s2g(dst, base + OFF_KV, GRP); publish(C_H, true); OBS(1, 3); }
      named_sync(9, 160);
      smem_fence();
      if (elect()) {
        if (g1 && SY_B) { wait_flag(0, SY_B); store_paced(dst + 128 * GRP, 1792, base + OFF_KV + GRP, 1792, 4, PS_H); }
        else bulk_s2g(dst + 128 * GRP, base + OFF_KV + GRP, GRP);
        publish(C_H + 1);
        OBS(1, 4);
      }
      __syncwarp();
      if (g1) { spin_ge(C_H + 1, 128); if (lane == 0) mbar_arrive(bars + B_F0); }
      else {
        const int kg0 = (mt & 3) * 14 + dt * 4, nk = dt < 3 ? 4 : 2;
#pragma unroll 1
        for (int m = 0; m < 3; m++) {
          named_sync(m == 0 ? 14 : (m == 1 ? 10 : 9), 160);
          smem_fence();
          if (elect()) {
            if (m == 2) { mbar_expect_tx(bars + B_RT, nk * GRP); bulk_g2s(base, p.wo + kg0 * GRP, nk * GRP, bars + B_RT); }
            bulk_s2g(g_scr + (G_W + m * 56 + kg0) * GRP, base + (12 + m * 4) * GRP, nk * GRP);
            if (m != 1) publish(m ? C_W2 : C_W);
            OBS(m != 1, 5 + (m >> 1));
          }
          __syncwarp();
        }
      }
      spin_ge(C_W, 16);
      if (lane == 0) mbar_arrive(bars + B_F1);
      spin_ge(C_W2, 16);
      if (lane == 0) mbar_arrive(bars + B_F1B);
      if (mt == 0) {
#pragma unroll
        for (int i = 0; i < 14; i++) sts128(base + OFF_KV + (i / 7) * KV + (i % 7) * 512 + lane * 16, 0, 0, 0, 0);
        smem_fence();
        __syncwarp();
        if (lane < 2) mbar_arrive(bars + B_HALO + lane * 8);
      }
      const unsigned have = EARLY && mt > 0 ? ld_relaxed(C_HALO + b - 4) : 0;
      if (g1) {
        named_sync(14, 160);
        smem_fence();
        if (elect()) tma_store(&m_b7, d1 * 14, G_U + ft * 8, base + OFF_U);
        named_sync(10, 160);
        smem_fence();
        if (elect()) { tma_store(&m_b7, d1 * 14 + 7, G_U + ft * 8, base + OFF_U + GRP); publish(C_U, true); OBS(1, 7); }
        __syncwarp();
      }
#pragma unroll 1
      for (int i = 0; i < 2; i++) {
        unsigned char* hg = g_scr + (G_HALO + b) * GRP + i * 3584;
        named_sync(i ? 0 : 11, 64);
        smem_fence();
        if (mt < 31 && elect()) { bulk_s2g(hg, base + OFF_KV + i * KV + 8 * 1792, 3584); publish(C_HALO + b); }
        OBS(lane == 0, i ? 15 : 23);
        if (mt > 0) {
          if (have <= i) spin_ge(C_HALO + b - 4, i + 1);
          if (elect()) { mbar_expect_tx(bars + B_HALO + i * 8, 3584); bulk_g2s(base + OFF_KV + i * KV, hg - 4 * GRP, 3584, bars + B_HALO + i * 8); }
        }
        __syncwarp();
      }
    }
  } else {
    const int wg = warp >> 2, w4 = warp & 3;
    const bool rel = (tid & 127) == 0;
    named_sync(12 + wg, 160);
    if (wg) { mbar_wait(bars + B_F2, 0); lds_row(H, base + OFF_U + g * 896 + w4 * 224, t); }
    {
      const uint32_t part = base + OFF_PART + wg * 512 + g * 32, st = base + OFF_KV + wg * GRP + (w4 * 14 + mi) * 128 + r8 * 16;
#pragma unroll
      for (int ln = 0; ln < (ANA ? 1 : 2); ln++) {
        float s0 = 0.f, s1 = 0.f, q0 = 0.f, q1 = 0.f;
#pragma unroll
        for (int j = 0; j < 14; j++) { const float a = bf_lo(H[j]), c = bf_hi(H[j]); s0 += a; s1 += c; q0 = fmaf(a, a, q0); q1 = fmaf(c, c, q1); }
        s0 += s1; q0 += q1;
#pragma unroll
        for (int o = 1; o < 4; o <<= 1) { s0 += __shfl_xor_sync(0xffffffffu, s0, o); q0 += __shfl_xor_sync(0xffffffffu, q0, o); }
        if (t == 0) sts64(part + ln * 256 + w4 * 8, s0, q0);
        OBS(tid == 0 && ln == 0, 0);
        named_sync(1 + wg, 128);
        const uint4 u = lds128(part + ln * 256), v = lds128(part + ln * 256 + 16);
        const float mean = ((__uint_as_float(u.x) + __uint_as_float(u.z)) + (__uint_as_float(v.x) + __uint_as_float(v.z))) * (1.0f / D_);
        const float var = variance(mean, (__uint_as_float(u.y) + __uint_as_float(u.w)) + (__uint_as_float(v.y) + __uint_as_float(v.w)));
        const LnC l = ln_consts(mean, var);
#pragma unroll
        for (int j = 0; j < 14; j++) H[j] = ln_apply(H[j], l);
        if (ANA) {
          const LnC l2 = ln_consts((mean - bf_lo(l.m)) * l.r, var * l.r * l.r);
#pragma unroll
          for (int j = 0; j < 14; j++) H[j] = ln_apply(H[j], l2);
        }
      }
#pragma unroll
      for (int i = 0; i < 3; i++) stsm4(st + i * 512, H[4 * i], H[4 * i + 1], H[4 * i + 2], H[4 * i + 3]);
      stsm2(st + 1536, H[12], H[13]);
      named_arrive(10 - wg, 160);
      OBS(rel, 1 + wg);
    }
    uint32_t ok = 0;
    int trc = 0;
    auto nohook = [](int) {};
#ifdef DBG_OBS
#define OBS0(c, i) do { mbar_wait(bars + ((c) & 7) * 8, ((c) >> 3) & 1); ok = 1; OBS(rel, i); trc = (i) == 5 ? 32 : 64 + (c); } while (0)
#else
#define OBS0(c, i) ok = 0
#endif
    const uint32_t sx = base + OFF_KV + (tid & 127) * 16;
    if (wg == 0) {
      uint32_t hb[4], R[28];
#pragma unroll
      for (int i = 0; i < 4; i++)
        asm volatile("ld.relaxed.cta.global.u16 %0, [%1];" : "=r"(hb[i]) : "l"((i < 2 ? p.b1 + (g1 ? mt * 64 : 0) : p.b2 + mt * 64) + w4 * 16 + g + (i & 1) * 8) : "memory");
      mbar_wait(bars + B_X, 0);
#pragma unroll
      for (int i = 0; i < 8; i++) {
        const int h = i >> 2, j = i & 3, xi = h * 4 + (g >> 1), c = dt * 14 + (j < 3 ? 4 * j + t : 12 + (t >> 1));
        const uint4 v = lds128(base + OFF_X + (c >> 3) * 8192 + (w4 * 16 + (g & 1) * 8 + xi) * 128 + (((c ^ xi) & 7) << 4));
        if (j < 3) { R[h * 14 + 4 * j] = v.x; R[h * 14 + 4 * j + 1] = v.y; R[h * 14 + 4 * j + 2] = v.z; R[h * 14 + 4 * j + 3] = v.w; }
        else { R[h * 14 + 12] = t & 1 ? v.z : v.x; R[h * 14 + 13] = t & 1 ? v.w : v.y; }
      }
#pragma unroll
      for (int i = 0; i < 28; i++) asm volatile("" : "+r"(R[i]));
      if (lane == 0) mbar_arrive(bars + B_XF + R[27] * threadIdx.y);
      float acc[56];
      if (g1) {
#pragma unroll
        for (int i = 0; i < 56; i++) { acc[i] = bf_lo(hb[(i >> 1) & 1]); asm volatile("" : "+f"(acc[i])); }
        if (w4 < NP_H) { wait_until(clock() + w4 * PH_H); watch_flag(0, C_H, 128); }
        OBS0(0, 5);
#pragma unroll 1
        for (int r = 0; r < 4; r++)
#pragma unroll
          for (int c = 0; c < 8; c++) stage<1>(acc, p.dw, p.db, c, r & 1, ok, trc, false, rel && (c || r), [&](int k) { if (c == 7 && k == 3 - HK) arrive_if(3, r == 3); });
        wg_wait<0>();
        if (rel) mbar_arrive(bars + B_EMPTY + 7 * 8);
        OBS(rel, 6);
        const uint32_t us = base + OFF_U + (w4 * 2 + (mi & 1)) * 896 + (mi >> 1) * 128 + r8 * 16;
#pragma unroll
        for (int hf = 0; hf < 2; hf++) {
          uint32_t U[14];
#pragma unroll
          for (int j = 0; j < 14; j++) {
            const float a = acc[hf * 28 + 2 * j], c = acc[hf * 28 + 2 * j + 1];
            U[j] = pack2(fmaf(a, tanh_fast(a * fmaf(a * a, 0.0356774081f, 0.7978845608f)), a), fmaf(c, tanh_fast(c * fmaf(c * c, 0.0356774081f, 0.7978845608f)), c));
          }
#pragma unroll
          for (int j = 0; j < 3; j++) stsm4(us + hf * GRP + j * 256, U[4 * j], U[4 * j + 1], U[4 * j + 2], U[4 * j + 3]);
          stsm2(us + hf * GRP + 768, U[12], U[13]);
          named_arrive(hf ? 10 : 14, 160);
          if (!hf) mbar_wait(bars + B_X, 0);
        }
        OBS(rel, 30);
      } else {
        named_arrive(3, 256);
        const int kg0 = (mt & 3) * 14 + dt * 4, nk = dt < 3 ? 4 : 2;
        mbar_wait(bars + B_XF, 0);
        mbar_wait(bars + B_RT, 0);
        OBS(tid == 0, 7);
#pragma unroll 1
        for (int m = 1; m < 4; m++) {
          if (w4 < nk) {
            uint4 v[14];
#pragma unroll
            for (int l = 0; l < 14; l++) v[l] = lds128(base + (w4 * 8 + r8) * 2688 + (m % 3) * 896 + (l >> 1) * 128 + ((r8 + mi + (l & 1) * 4) & 7) * 16);
#pragma unroll
            for (int l = 0; l < 14; l++) sts128(base + (8 + m * 4 + w4) * GRP + (l >> 1) * 1024 + ((r8 + mi + (l & 1) * 4) & 7) * 128 + r8 * 16, v[l].x, v[l].y, v[l].z, v[l].w);
          }
          named_arrive(m == 1 ? 14 : (m == 2 ? 10 : 9), 160);
        }
        mbar_wait(bars + B_RT, 1);
#pragma unroll 1
        for (int i = 0; i < nk; i++) {
          uint32_t W[14];
          lds_row(W, base + i * GRP + g * 896 + w4 * 224, t);
          const uint32_t st = base + (4 + i) * GRP + (w4 * 14 + mi) * 128 + r8 * 16;
#pragma unroll
          for (int j = 0; j < 3; j++) stsm4(st + j * 512, W[4 * j], W[4 * j + 1], W[4 * j + 2], W[4 * j + 3]);
          stsm2(st + 1536, W[12], W[13]);
        }
        smem_fence();
        named_sync(1, 128);
        if (w4 == 0 && elect()) {
          bulk_s2g(g_scr + (G_WO + kg0) * GRP, base + 4 * GRP, nk * GRP);
          publish(C_U);
          mbar_arrive(bars + B_F1);
          OBS(1, 16);
        }
        __syncwarp();
      }
#pragma unroll
      for (int i = 0; i < 56; i++) { acc[i] = 0.f; asm volatile("" : "+f"(acc[i])); }
#pragma unroll
      for (int i = 2; i < 4; i++) { hb[i] = hmul2(hb[i] * 0x10001u, 0x3f003f00u); asm volatile("" : "+r"(hb[i])); }
      const int ro = (mt * 64 + w4 * 16 + g) * (D_ * 2) + dt * 224;
      unsigned char *outp = p.out + ro + t * 16, *outq = p.out + ro + 192 + t * 8;
      asm volatile("" : "+l"(outp), "+l"(outq));
      if (w4 < NP_U) { wait_until(clock() + PU0 + w4 * PH_U); watch_flag(1, C_U, 128); }
      named_sync(5, 256);
      OBS0(21, 10);
#pragma unroll 1
      for (int r = 0; ; r++) {
#pragma unroll
        for (int j = 0; j < 8; j++) {
          const bool site = j == SA % 8 || j == SB % 8, yield = (j == SA % 8 && r == SA / 8) || (j == SB % 8 && r == SB / 8);
          stage<1>(acc, p.dw, p.db, (j + 5) & 7, (r + (j > 2)) & 1, ok, trc, false, rel && (j || r), [&](int k) {
            if (k == 3 - HK) { if (site) arrive_if(N_GO, yield); if (j == 3) arrive_if(8, r == 3); } });
          if (site && yield) named_sync(N_DONE, 256);
          if (j == 3 && r == 3) goto gemm2_done;
        }
      }
      gemm2_done:
      wg_wait<0>();
      OBS(rel, 24);
      uint32_t G[28], dep = 0;
#pragma unroll
      for (int j = 0; j < 28; j++) {
        const uint32_t hh = hfma2(pack2(acc[2 * j], acc[2 * j + 1]), 0x3e803e80u, hb[2 + (j & 1)]);
        const float a = bf_lo(hh), c = bf_hi(hh);
        G[j] = pack2(fmaf(a, tanh_fast(a), a), fmaf(c, tanh_fast(c), c));
        dep |= G[j];
      }
      OBS(rel, 26);
      named_sync(12 + w4 + dep * threadIdx.y, 64);
#pragma unroll
      for (int i = 0; i < 4; i++) {
        const uint4 u = lds128(sx + i * 4096), v = i < 3 ? lds128(sx + i * 4096 + 2048) : u;
        const uint32_t Sv[8] = {u.x, u.y, u.z, u.w, v.x, v.y, v.z, v.w};
#pragma unroll
        for (int h = 0; h < 2; h++) {
          uint32_t Y[4];
#pragma unroll
          for (int j = 0; j < (i < 3 ? 4 : 2); j++) Y[j] = hadd2(R[h * 14 + 4 * i + j], hmul2(Sv[2 * j + h], G[8 * i + 2 * j + h]));
          if (i < 3) asm volatile("st.global.v4.u32 [%0], {%1,%2,%3,%4};" :: "l"(outp + h * 8 * D_ * 2 + i * 64), "r"(Y[0]), "r"(Y[1]), "r"(Y[2]), "r"(Y[3]) : "memory");
          else asm volatile("st.global.v2.u32 [%0], {%1,%2};" :: "l"(outq + h * 8 * D_ * 2), "r"(Y[0]), "r"(Y[1]) : "memory");
        }
      }
      OBS(rel, 28);
#ifdef DBG_OBS
      named_sync(1, 128);
      { uint32_t v = lds32(base + OFF_OBS + tid * 4); if (tid == 126) v = tz; if (tid == 127) asm volatile("mov.u32 %0, %%smid;" : "=r"(v)); g_obs[b * 128 + tid] = v; }
#endif
    } else {
      asm volatile("setmaxnreg.inc.sync.aligned.u32 256;");
      float ka[56];
      {
        uint32_t X[28][4];
      mbar_wait(bars + B_X, 0);
      OBS(rel, 29);
#pragma unroll
      for (int k = 0; k < 28; k++)
        ldsm4(X[k], base + OFF_X + (k >> 2) * 8192 + (w4 * 16 + (mi >> 1) * 8 + r8) * 128 + (((2 * (k & 3) + (mi & 1)) ^ r8) << 4));
      if (lane == 0) mbar_arrive(bars + B_XF + X[27][3] * threadIdx.y);
      float c0[2][4] = {}, c1[2][4] = {};
      uint32_t one[8];
#pragma unroll
      for (int j = 0; j < 8; j++) asm volatile("{\n.reg .u32 y;\nmov.u32 y, %%tid.y;\nmad.lo.u32 %0, y, %1, 0x3f803f80;\n}" : "=r"(one[j]) : "r"(lane + j));
#pragma unroll
      for (int k = 0; k < 28; k++) {
        mma16816(c0[k & 1], X[k][0], one[(k & 1) * 4], X[k][1], one[(k & 1) * 4 + 1], X[k][0], X[k][1]);
        mma16816(c1[k & 1], X[k][2], one[(k & 1) * 4 + 2], X[k][3], one[(k & 1) * 4 + 3], X[k][2], X[k][3]);
      }
      float st[4];
#pragma unroll
      for (int j = 0; j < 2; j++) {
        st[j] = __shfl_sync(0xffffffffu, (g & 1) ? c0[0][2 * j + 1] + c0[1][2 * j + 1] : c0[0][2 * j] + c0[1][2 * j], (lane & 28) | (g >> 1));
        st[2 + j] = __shfl_sync(0xffffffffu, (g & 1) ? c1[0][2 * j + 1] + c1[1][2 * j + 1] : c1[0][2 * j] + c1[1][2 * j], (lane & 28) | (g >> 1));
      }
      const float m0 = st[1] * (1.0f / D_), m1 = st[3] * (1.0f / D_);
      const LnC l0 = ln_consts(m0, variance(m0, st[0])), l1 = ln_consts(m1, variance(m1, st[2]));
#pragma unroll
      for (int k = 0; k < 28; k++) {
        const uint32_t y = ln_apply(X[k][1], l0);
        X[k][0] = ln_apply(X[k][0], l0); X[k][1] = ln_apply(X[k][2], l1); X[k][2] = y; X[k][3] = ln_apply(X[k][3], l1);
        pin(X[k]);
      }
      OBS(rel, 122);
        float va[56];
        const uint32_t kst = base + OFF_KV + (2 + 2 * w4 + (mi & 1)) * 1792 + (mi >> 1) * 128 + r8 * 16;
        auto put = [&](const float (&a)[56], uint32_t dst, int n) {
          stsm4(dst + n * 128, pack2(a[4 * n], a[4 * n + 1]), pack2(a[4 * n + 2], a[4 * n + 3]), pack2(a[4 * n + 4], a[4 * n + 5]), pack2(a[4 * n + 6], a[4 * n + 7])); };
        named_sync(3, 256);
        fresh(ka);
        OBS0(0, 8);
#pragma unroll
        for (int c = 0; c < 7; c++) stage<2>(ka, 0, p.db, c, 0, ok, trc, c == 0, rel && c, nohook, &X[c * 4]);
        fresh(va);
#pragma unroll
        for (int c = 7; c < 14; c++)
          stage<2>(va, 0, p.db, c & 7, c >> 3, ok, trc, c == 7, rel, [&](int k) {
            if (c > 7 && (c - 8) * 4 + k < 7) put(ka, kst, (c - 8) * 8 + k * 2);
            if (c == 9 && k == 3 && w4 == 3) named_arrive(11, 64); }, &X[(c - 7) * 4]);
        fresh(ka);
        OBS(rel, 9);
#pragma unroll
        for (int c = 14; c < 21; c++)
          stage<2>(ka, 0, p.db, c & 7, (c >> 3) & 1, ok, trc, c == 14, rel, [&](int k) {
            if (c > 14 && (c - 15) * 4 + k < 7) put(va, kst + KV, (c - 15) * 8 + k * 2);
            if (c == 16 && k == 3 && w4 == 3) named_arrive(0, 64);
            if (c == 20 && k == 3 - HK) named_arrive(5, 256); }, &X[(c - 14) * 4]);
        smem_fence();
        wg_wait<0>();
        if (rel) mbar_arrive(bars + B_EMPTY + 4 * 8);
      }
      {
        uint32_t Q[8][4];
#pragma unroll
        for (int i = 0; i < 16; i++) {
          const int n = i - (i + 4) / 8;
#pragma unroll
          for (int h = 0; h < 2; h++) {
            const uint32_t v = pack2(ka[4 * n + 2 * h], ka[4 * n + 2 * h + 1]);
            Q[i >> 1][(i & 1) * 2 + h] = (i & 7) == 3 ? (t < 2 ? v : 0u) : ((i & 7) == 4 ? (t < 2 ? 0u : v) : v);
          }
        }
#pragma unroll
        for (int i = 0; i < 8; i++) pin(Q[i]);
        float Sc[4][40], O[4][16];
        mbar_wait(bars + B_HALO, 0);
        OBS(rel, 11);
#pragma unroll
        for (int hh = 0; hh < 4; hh++) fresh(Sc[hh]);
        wg_fence();
        named_sync(N_GO, 256);
#pragma unroll
        for (int k = 0; k < 2; k++)
#pragma unroll
          for (int hh = 0; hh < 4; hh++) {
            if (k == 1 && hh == 3) named_arrive(N_DONE, 256);
            wgmma_rs_n80<0>(Sc[hh], Q[hh * 2 + k], dlo(OFF_KV + (hh * 7 / 2 + 2 * k) * 128, 128), p.dk, k);
          }
        wg_commit();
        const bool e0 = 2 * t > g, e1 = 2 * t + 1 > g;
        const uint32_t em = (e0 ? 0xffffu : 0u) | (e1 ? 0xffff0000u : 0u);
        uint32_t L[4][2], M[5], edge = mt == 0 && w4 == 0 ? em : 0u, low = lane < 16 ? ~0u : 0u;
#pragma unroll
        for (int j = 0; j < 5; j++) { M[j] = j == w4 ? em : (j == w4 + 1 ? ~em : 0u); asm volatile("" : "+r"(M[j])); }
        asm volatile("" : "+r"(low), "+r"(edge));
        wg_wait<0>();
        OBS(rel, 12);
        auto pick = [&](int w) {
#pragma unroll
          for (int hh = 0; hh < 4; hh++)
#pragma unroll
            for (int h = 0; h < 2; h++) {
              const int i = (2 * w + h) * 4 + 2 * h;
              L[hh][h] = pack2(e0 ? Sc[hh][i] : Sc[hh][i + 8], e1 ? Sc[hh][i + 1] : Sc[hh][i + 9]);
              asm volatile("" : "+r"(L[hh][h]));
            }
        };
        if (w4 == 0) pick(0); else if (w4 == 1) pick(1); else if (w4 == 2) pick(2); else pick(3);
        uint32_t A[4][5][4], sign = 0;
#pragma unroll
        for (int hh = 0; hh < 4; hh++) {
          uint32_t l[2];
#pragma unroll
          for (int h = 0; h < 2; h++) l[h] = (hfma2(L[hh][h], 0x3e423e42u, hmul2(L[hh][h], 0xb9f7b9f7u)) & ~edge) | (0xce6ece6eu & edge);
          uint32_t mx = hmax2(__byte_perm(l[0], l[1], 0x5410), __byte_perm(l[0], l[1], 0x7632));
          mx = hmax2(mx, __shfl_xor_sync(0xffffffffu, mx, 1));
          mx = hmax2(mx, __shfl_xor_sync(0xffffffffu, mx, 2));
#pragma unroll
          for (int h = 0; h < 2; h++) {
            const float m = (h ? bf_hi(mx) : bf_lo(mx)) * -LOG2E;
            const float p0 = ex2_fast(fmaf(bf_lo(l[h]), LOG2E, m)), p1 = ex2_fast(fmaf(bf_hi(l[h]), LOG2E, m));
            float sm = p0 + p1;
            sm += __shfl_xor_sync(0xffffffffu, sm, 1);
            sm += __shfl_xor_sync(0xffffffffu, sm, 2);
            const float inv = rcp_fast(sm);
            const uint32_t pp = pack2(p0 * inv, p1 * inv);
#pragma unroll
            for (int j = 0; j < 5; j++) { A[hh][j][3 * h] = pp & M[j] & low; A[hh][j][1 + h] = pp & M[j] & ~low; }
            sign |= pp;
          }
        }
#pragma unroll
        for (int hh = 0; hh < 4; hh++) fresh(O[hh]);
#pragma unroll
        for (int i = 0; i < 20; i++) pin(A[i / 5][i % 5]);
        OBS(rel, 13);
        mbar_wait(bars + B_HALO + 8 + (sign >> 31), 0);
        OBS(rel, 31);
        named_sync(N_GO, 256);
        wg_fence();
        const uint32_t ost = base + OFF_U + w4 * 3584 + (mi >> 1) * 128 + (r8 >> 2) * 1792 + (((2 * r8) & 7) + ((mi & 1) ^ (r8 >> 2))) * 16;
        auto opair = [&](int m, int h2) {
          const int hb2 = m / 7 * 2, r = m % 7;
          if (r < 3) return pack2(O[hb2][4 * r + h2], O[hb2][4 * r + h2 + 1]);
          if (r == 3) return pack2(t < 2 ? O[hb2][12 + h2] : O[hb2 + 1][h2], t < 2 ? O[hb2][13 + h2] : O[hb2 + 1][h2 + 1]);
          return pack2(O[hb2 + 1][4 * (r - 3) + h2], O[hb2 + 1][4 * (r - 3) + h2 + 1]);
        };
        auto oput = [&](int n) { stsm4(ost + n * 128, opair(n, 0), opair(n, 2), opair(n + 1, 0), opair(n + 1, 2)); };
        auto pv = [&](int hh, int j) { wgmma_rs_n32<1>(O[hh], A[hh][j], dlo(OFF_KV + KV + hh * 7 / 2 * 128 + j * 3584, 1792), p.db, j); };
#pragma unroll
        for (int i = 0; i < 20; i++) { if (i == 18) named_arrive(N_DONE, 256); pv(i & 3, i >> 2); }
        wg_commit();
        OBS(rel, 19);
        wg_wait<0>();
        OBS(rel, 21);
#pragma unroll
        for (int n = 0; n < 14; n += 2) oput(n);
        smem_fence();
        __syncwarp();
        OBS(rel, 14);
        if (elect()) {
          wait_until(clock() + w4 * PS_O);
          store_paced(g_scr + (G_O + mt * 8 + w4 * 2) * GRP + dt * 1792, GRP, base + OFF_U + w4 * 3584, 1792, 2, 4 * PS_O);
          publish(C_O + mt);
        }
        OBS(rel, 120);
        __syncwarp();
      }
      named_sync(8, 256);
      fresh(ka);
      OBS0(49, 25);
#pragma unroll
      for (int c = 49; c < 56; c++) stage<0>(ka, p.dx, p.db, c & 7, 0, ok, trc, c == 49, false, nohook);
      wg_wait<0>();
      OBS(rel, 27);
#pragma unroll
      for (int j = 0; j < 7; j++)
        sts128(sx + j * 2048, pack2(ka[8 * j], ka[8 * j + 1]), pack2(ka[8 * j + 2], ka[8 * j + 3]), pack2(ka[8 * j + 4], ka[8 * j + 5]), pack2(ka[8 * j + 6], ka[8 * j + 7]));
      named_arrive(12 + w4, 64);
    }
  }
}

typedef CUresult (*EncFn)(CUtensorMap*, CUtensorMapDataType, cuuint32_t, void*, const cuuint64_t*, const cuuint64_t*, const cuuint32_t*,
                          const cuuint32_t*, CUtensorMapInterleave, CUtensorMapSwizzle, CUtensorMapL2promotion, CUtensorMapFloatOOBfill);
void enc(EncFn f, CUtensorMap* m, const void* ptr, const cuuint64_t (&gd)[4], const cuuint64_t (&gs)[3], const cuuint32_t (&bx)[4], CUtensorMapSwizzle sw) {
  cuuint32_t es[4] = {1, 1, 1, 1};
  f(m, CU_TENSOR_MAP_DATA_TYPE_BFLOAT16, 4, (void*)ptr, gd, gs, bx, es, CU_TENSOR_MAP_INTERLEAVE_NONE, sw,
    CU_TENSOR_MAP_L2_PROMOTION_L2_128B, CU_TENSOR_MAP_FLOAT_OOB_FILL_NONE);
}
}

extern "C" void kernel_launch(void* const* d_in, const int* in_sizes, int n_in, void* d_out, int out_size) {
  (void)in_sizes; (void)n_in; (void)out_size;
  void* fp = nullptr;
  cudaDriverEntryPointQueryResult qr;
  cudaGetDriverEntryPoint("cuTensorMapEncodeTiled", &fp, cudaEnableDefault, &qr);
  EncFn f = (EncFn)fp;
  CUtensorMap m_w1, m_w2, m_b14, m_a8, m_b7, m_xt;
  void* scr = nullptr;
  cudaGetSymbolAddress(&scr, g_scr);
  enc(f, &m_w1, d_in[4], {F_, 16, 1, S_ / 16}, {F_ * 2, F_ * 2, F_ * 32}, {64, 8, 1, 8}, CU_TENSOR_MAP_SWIZZLE_128B);
  {
    cuuint64_t gd[5] = {64, 8, 2, S_ / 16, 7}, gs[4] = {D_ * 4, D_ * 2, D_ * 32, 128};
    cuuint32_t bx[5] = {64, 8, 2, 4, 7}, es[5] = {1, 1, 1, 1, 1};
    f(&m_xt, CU_TENSOR_MAP_DATA_TYPE_BFLOAT16, 5, d_in[0], gd, gs, bx, es, CU_TENSOR_MAP_INTERLEAVE_NONE, CU_TENSOR_MAP_SWIZZLE_128B,
      CU_TENSOR_MAP_L2_PROMOTION_L2_128B, CU_TENSOR_MAP_FLOAT_OOB_FILL_NONE);
  }
  enc(f, &m_w2, d_in[6], {S_, 1, 1, F_}, {S_ * 2, S_ * 2, S_ * 2}, {64, 1, 1, 64}, CU_TENSOR_MAP_SWIZZLE_128B);
  enc(f, &m_b14, scr, {64, 56, 1, G_END}, {128, GRP, GRP}, {64, 14, 1, 8}, CU_TENSOR_MAP_SWIZZLE_NONE);
  enc(f, &m_b7, scr, {64, 56, 1, G_END}, {128, GRP, GRP}, {64, 7, 1, 8}, CU_TENSOR_MAP_SWIZZLE_NONE);
  enc(f, &m_a8, scr, {64, 56, 1, G_END}, {128, GRP, GRP}, {64, 8, 1, 8}, CU_TENSOR_MAP_SWIZZLE_NONE);
  Params p;
  p.x = (const unsigned char*)d_in[0]; p.wqkv = (const unsigned char*)d_in[1]; p.wo = (const unsigned char*)d_in[2];
  p.w1 = (const unsigned char*)d_in[4]; p.b1 = (const unsigned short*)d_in[5];
  p.w2 = (const unsigned char*)d_in[6]; p.b2 = (const unsigned short*)d_in[7];
  p.out = (unsigned char*)d_out;
  p.dw = 0x40000040u; p.dx = 64; p.db = 8; p.dk = 112;
#ifdef TUNE
  for (int i = 0; i < NTUNE; i++) p.tune[i] = tune_vals[i];
#endif
  cudaFuncSetAttribute(fused_kernel, cudaFuncAttributeMaxDynamicSharedMemorySize, SMEM_BYTES);
  fused_kernel<<<128, NTHREADS, SMEM_BYTES, cudaStreamPerThread>>>(p, m_w1, m_w2, m_b14, m_a8, m_b7, m_xt);
}
```

```cpp
#include <cuda_runtime.h>
#include <cuda.h>
#include <cuda_bf16.h>
#include <stdint.h>

template<int TA, int TB> __device__ __forceinline__ void wgmma_n112(float (&d)[56], uint32_t al, uint32_t ah, uint32_t bl, uint32_t bh, int sc) {
  asm volatile("{\n.reg .pred p;\n.reg .b64 a, b;\nsetp.ne.b32 p, %60, 0;\nmov.b64 a, {%56, %57};\nmov.b64 b, {%58, %59};\n"
    "wgmma.mma_async.sync.aligned.m64n112k16.f32.bf16.bf16 {%0, %1, %2, %3, %4, %5, %6, %7, %8, %9, %10, %11, %12, %13, %14, %15, %16, %17, %18, %19, %20, %21, %22, %23, %24, %25, %26, %27, %28, %29, %30, %31, %32, %33, %34, %35, %36, %37, %38, %39, %40, %41, %42, %43, %44, %45, %46, %47, %48, %49, %50, %51, %52, %53, %54, %55}, a, b, p, 1, 1, %61, %62;\n}\n"
    : "+f"(d[0]), "+f"(d[1]), "+f"(d[2]), "+f"(d[3]), "+f"(d[4]), "+f"(d[5]), "+f"(d[6]), "+f"(d[7]), "+f"(d[8]), "+f"(d[9]), "+f"(d[10]), "+f"(d[11]), "+f"(d[12]), "+f"(d[13]), "+f"(d[14]), "+f"(d[15]), "+f"(d[16]), "+f"(d[17]), "+f"(d[18]), "+f"(d[19]), "+f"(d[20]), "+f"(d[21]), "+f"(d[22]), "+f"(d[23]), "+f"(d[24]), "+f"(d[25]), "+f"(d[26]), "+f"(d[27]), "+f"(d[28]), "+f"(d[29]), "+f"(d[30]), "+f"(d[31]), "+f"(d[32]), "+f"(d[33]), "+f"(d[34]), "+f"(d[35]), "+f"(d[36]), "+f"(d[37]), "+f"(d[38]), "+f"(d[39]), "+f"(d[40]), "+f"(d[41]), "+f"(d[42]), "+f"(d[43]), "+f"(d[44]), "+f"(d[45]), "+f"(d[46]), "+f"(d[47]), "+f"(d[48]), "+f"(d[49]), "+f"(d[50]), "+f"(d[51]), "+f"(d[52]), "+f"(d[53]), "+f"(d[54]), "+f"(d[55])
    : "r"(al), "r"(ah), "r"(bl), "r"(bh), "r"(sc), "n"(TA), "n"(TB));
}

template<int TB> __device__ __forceinline__ void wgmma_rs_n80(float (&d)[40], const uint32_t (&a)[4], uint32_t bl, uint32_t bh, int sc) {
  asm volatile("{\n.reg .pred p;\n.reg .b64 b;\nsetp.ne.b32 p, %46, 0;\nmov.b64 b, {%44, %45};\n"
    "wgmma.mma_async.sync.aligned.m64n80k16.f32.bf16.bf16 {%0, %1, %2, %3, %4, %5, %6, %7, %8, %9, %10, %11, %12, %13, %14, %15, %16, %17, %18, %19, %20, %21, %22, %23, %24, %25, %26, %27, %28, %29, %30, %31, %32, %33, %34, %35, %36, %37, %38, %39}, {%40, %41, %42, %43}, b, p, 1, 1, %47;\n}\n"
    : "+f"(d[0]), "+f"(d[1]), "+f"(d[2]), "+f"(d[3]), "+f"(d[4]), "+f"(d[5]), "+f"(d[6]), "+f"(d[7]), "+f"(d[8]), "+f"(d[9]), "+f"(d[10]), "+f"(d[11]), "+f"(d[12]), "+f"(d[13]), "+f"(d[14]), "+f"(d[15]), "+f"(d[16]), "+f"(d[17]), "+f"(d[18]), "+f"(d[19]), "+f"(d[20]), "+f"(d[21]), "+f"(d[22]), "+f"(d[23]), "+f"(d[24]), "+f"(d[25]), "+f"(d[26]), "+f"(d[27]), "+f"(d[28]), "+f"(d[29]), "+f"(d[30]), "+f"(d[31]), "+f"(d[32]), "+f"(d[33]), "+f"(d[34]), "+f"(d[35]), "+f"(d[36]), "+f"(d[37]), "+f"(d[38]), "+f"(d[39])
    : "r"(a[0]), "r"(a[1]), "r"(a[2]), "r"(a[3]), "r"(bl), "r"(bh), "r"(sc), "n"(TB));
}

__device__ __forceinline__ void wgmma_sp_n32(float (&d)[16], const uint32_t (&a)[4], uint32_t bl, uint32_t bh, uint32_t meta, int sc) {
  asm volatile("{\n.reg .pred p;\n.reg .b64 b;\nsetp.ne.b32 p, %23, 0;\nmov.b64 b, {%20, %21};\n"
    "wgmma.mma_async.sp.sync.aligned.m64n32k32.f32.bf16.bf16 {%0, %1, %2, %3, %4, %5, %6, %7, %8, %9, %10, %11, %12, %13, %14, %15}, {%16, %17, %18, %19}, b, %22, 0, p, 1, 1, 1;\n}\n"
    : "+f"(d[0]), "+f"(d[1]), "+f"(d[2]), "+f"(d[3]), "+f"(d[4]), "+f"(d[5]), "+f"(d[6]), "+f"(d[7]), "+f"(d[8]), "+f"(d[9]), "+f"(d[10]), "+f"(d[11]), "+f"(d[12]), "+f"(d[13]), "+f"(d[14]), "+f"(d[15])
    : "r"(a[0]), "r"(a[1]), "r"(a[2]), "r"(a[3]), "r"(bl), "r"(bh), "r"(meta), "r"(sc));
}

template<int TB> __device__ __forceinline__ void wgmma_rs_n112(float (&d)[56], const uint32_t (&a)[4], uint32_t bl, uint32_t bh, int sc) {
  asm volatile("{\n.reg .pred p;\n.reg .b64 b;\nsetp.ne.b32 p, %62, 0;\nmov.b64 b, {%60, %61};\n"
    "wgmma.mma_async.sync.aligned.m64n112k16.f32.bf16.bf16 {%0, %1, %2, %3, %4, %5, %6, %7, %8, %9, %10, %11, %12, %13, %14, %15, %16, %17, %18, %19, %20, %21, %22, %23, %24, %25, %26, %27, %28, %29, %30, %31, %32, %33, %34, %35, %36, %37, %38, %39, %40, %41, %42, %43, %44, %45, %46, %47, %48, %49, %50, %51, %52, %53, %54, %55}, {%56, %57, %58, %59}, b, p, 1, 1, %63;\n}\n"
    : "+f"(d[0]), "+f"(d[1]), "+f"(d[2]), "+f"(d[3]), "+f"(d[4]), "+f"(d[5]), "+f"(d[6]), "+f"(d[7]), "+f"(d[8]), "+f"(d[9]), "+f"(d[10]), "+f"(d[11]), "+f"(d[12]), "+f"(d[13]), "+f"(d[14]), "+f"(d[15]), "+f"(d[16]), "+f"(d[17]), "+f"(d[18]), "+f"(d[19]), "+f"(d[20]), "+f"(d[21]), "+f"(d[22]), "+f"(d[23]), "+f"(d[24]), "+f"(d[25]), "+f"(d[26]), "+f"(d[27]), "+f"(d[28]), "+f"(d[29]), "+f"(d[30]), "+f"(d[31]), "+f"(d[32]), "+f"(d[33]), "+f"(d[34]), "+f"(d[35]), "+f"(d[36]), "+f"(d[37]), "+f"(d[38]), "+f"(d[39]), "+f"(d[40]), "+f"(d[41]), "+f"(d[42]), "+f"(d[43]), "+f"(d[44]), "+f"(d[45]), "+f"(d[46]), "+f"(d[47]), "+f"(d[48]), "+f"(d[49]), "+f"(d[50]), "+f"(d[51]), "+f"(d[52]), "+f"(d[53]), "+f"(d[54]), "+f"(d[55])
    : "r"(a[0]), "r"(a[1]), "r"(a[2]), "r"(a[3]), "r"(bl), "r"(bh), "r"(sc), "n"(TB));
}

namespace {
constexpr int S_ = 2048, D_ = 448, F_ = 1792;
constexpr int SLOT = 22528, BT = 14336;
constexpr int OFF_KV = 8 * SLOT;
constexpr int OFF_X = OFF_KV - 7 * 8192;
constexpr int KV = 10 * 1792;
constexpr int OFF_PART = OFF_KV + 2 * BT;
constexpr int OFF_U = OFF_KV + 10 * 3584;
constexpr int OFF_BAR = OFF_U + BT;
constexpr uint32_t base = 1024, bars = base + OFF_BAR;
constexpr int OFF_OBS = OFF_BAR + 256;
constexpr int SMEM_BYTES = OFF_OBS + 768;
#ifdef TUNE
#define TV(i) p.tune[i]
const char* tune_names[] = {"DLY_B", "DLY_X", "DLY_W", "TPW", "DLY_R", "PF0", "PACE1", "PACE2", "SY_H", "SY_U", "SY_B", "PS_H", "NP_H", "PH_H", "NP_U", "PH_U", "PFN", "PF1", "PACE0", "PFR", "PACER", "DLY_Q", "DLY_D", "DLY_E", "PFD", "PQ"};
int tune_vals[] = {1000, 1000, 3600, 210, 0, 1900, 420, 400, 800, 1400, 1200, 150, 3, 230, 0, 300, 0, 0, 350, 99, 350, 1800, 0, 1500, 0, 200};
constexpr int NTUNE = 26;
#define DLY_B TV(0)
#define DLY_X TV(1)
#define DLY_W TV(2)
#define TPW TV(3)
#define DLY_R TV(4)
#define PF0 TV(5)
#define PACE1 TV(6)
#define PACE2 TV(7)
#define SY_H TV(8)
#define SY_U TV(9)
#define SY_B TV(10)
#define PS_H TV(11)
#define NP_H TV(12)
#define PH_H TV(13)
#define NP_U TV(14)
#define PH_U TV(15)
#define PFN TV(16)
#define PF1 TV(17)
#define PACE0 TV(18)
#define PFR TV(19)
#define PACER TV(20)
#define DLY_Q TV(21)
#define DLY_D TV(22)
#define DLY_E TV(23)
#define PFD TV(24)
#define PQ TV(25)
#else
#ifndef DLY_B
#define DLY_B 1000
#endif
#ifndef DLY_X
#define DLY_X 1000
#endif
#ifndef DLY_W
#define DLY_W 3300
#endif
#ifndef TPW
#define TPW 210
#endif
#ifndef DLY_R
#define DLY_R 0
#endif
#ifndef PF0
#define PF0 1600
#endif
#ifndef PACE1
#define PACE1 420
#endif
#ifndef PACE2
#define PACE2 400
#endif
#ifndef SY_H
#define SY_H 800
#endif
#ifndef SY_U
#define SY_U 1400
#endif
#ifndef SY_B
#define SY_B 1000
#endif
#ifndef PS_H
#define PS_H 150
#endif
#ifndef NP_H
#define NP_H 3
#endif
#ifndef PH_H
#define PH_H 230
#endif
#ifndef NP_U
#define NP_U 0
#endif
#ifndef PH_U
#define PH_U 300
#endif
#ifndef PFN
#define PFN 0
#endif
#ifndef PF1
#define PF1 0
#endif
#ifndef PACE0
#define PACE0 350
#endif
#ifndef PFR
#define PFR 99
#endif
#ifndef PACER
#define PACER 350
#endif
#ifndef DLY_Q
#define DLY_Q 1500
#endif
#ifndef DLY_D
#define DLY_D 0
#endif
#ifndef DLY_E
#define DLY_E 900
#endif
#ifndef PFD
#define PFD 0
#endif
#ifndef PQ
#define PQ 170
#endif
#endif
#ifndef SA
#define SA 0
#endif
#ifndef SB
#define SB 6
#endif
#ifndef PVS
#define PVS 0
#endif
#ifndef UH
#define UH 1
#endif
#ifndef EARLY
#define EARLY 1
#endif
#ifndef PU0
#define PU0 1200
#endif
#ifndef WU
#define WU 1
#endif
#ifndef ANA
#define ANA 1
#endif
#ifndef PS_O
#define PS_O 130
#endif
#ifndef HK
#define HK 1
#endif
#ifndef HE
#define HE 1
#endif
#ifdef DBG_OBS
__device__ int g_obs[128 * 128];
#ifdef OBS_NS
#define OBS_CLK "%%globaltimer_lo"
#else
#define OBS_CLK "%%clock"
#endif
#define OBS(c, i) asm volatile("{\n.reg .pred p;\n.reg .u32 k;\nsetp.ne.u32 p, %1, 0;\nmov.u32 k, " OBS_CLK ";\nsub.u32 k, k, %2;\n@p st.shared.u32 [%0], k;\n}" :: "r"(base + OFF_OBS + (i) * 4), "r"((uint32_t)(c)), "r"(tz) : "memory")
#else
#define OBS(c, i) do {} while (0)
#endif
constexpr int NTHREADS = 384;
constexpr float LOG2E = 1.4426950408889634f;

constexpr int GRP = 7168;
constexpr int G_H = 0, G_W = 256, G_U = G_W + 168, G_WO = G_U + 224, G_O = G_WO + 56, G_HALO = G_O + 256, G_END = G_HALO + 128;
constexpr int SCR_BYTES = G_END * GRP;
__device__ __align__(1024) unsigned char g_scr[SCR_BYTES];
constexpr int C_TICKET = 0, C_W = 1, C_H = 2, C_U = 4, C_W2 = 5, C_O = 8, C_HALO = 40, C_END = 168;
__device__ __align__(128) unsigned g_cnt[C_END * 32];

__device__ __forceinline__ uint32_t smem_u32(const void* p) { return (uint32_t)__cvta_generic_to_shared(p); }
__device__ __forceinline__ void mbar_init(uint32_t bar, uint32_t cnt) { asm volatile("mbarrier.init.shared::cta.b64 [%0], %1;" :: "r"(bar), "r"(cnt)); }
__device__ __forceinline__ void mbar_expect_tx(uint32_t bar, uint32_t bytes) { asm volatile("mbarrier.arrive.expect_tx.shared::cta.b64 _, [%0], %1;" :: "r"(bar), "r"(bytes) : "memory"); }
__device__ __forceinline__ void mbar_arrive(uint32_t bar) { asm volatile("mbarrier.arrive.shared::cta.b64 _, [%0];" :: "r"(bar) : "memory"); }
__device__ __forceinline__ void mbar_wait(uint32_t bar, uint32_t parity) {
  asm volatile("{\n.reg .pred p;\n.reg .u32 n;\nmov.u32 n, 0;\nLAB_WAIT:\n"
               "mbarrier.try_wait.parity.shared::cta.b64 p, [%0], %1;\n@p bra DONE;\n"
               "add.u32 n, n, 1;\nsetp.lt.u32 p, n, 4000000;\n@p bra LAB_WAIT;\ntrap;\nDONE:\n}" :: "r"(bar), "r"(parity) : "memory");
}
__device__ __forceinline__ void mbar_wait_u(uint32_t bar, uint32_t parity) {
  asm volatile("{\n.reg .pred p;\nLAB_WAIT:\nmbarrier.try_wait.parity.shared::cta.b64 p, [%0], %1;\n@!p bra LAB_WAIT;\n}" :: "r"(bar), "r"(parity) : "memory");
}
__device__ __forceinline__ uint32_t mbar_try(uint32_t bar, uint32_t parity) {
  uint32_t ok;
  asm volatile("{\n.reg .pred p;\nmbarrier.test_wait.parity.shared::cta.b64 p, [%1], %2;\nselp.u32 %0, 1, 0, p;\n}" : "=r"(ok) : "r"(bar), "r"(parity) : "memory");
  return ok;
}
__device__ __forceinline__ void tma4d(uint32_t dst, const CUtensorMap* m, int c0, int c1, int c3, uint32_t bar) {
  asm volatile("cp.async.bulk.tensor.4d.shared::cluster.global.mbarrier::complete_tx::bytes [%0], [%1, {%3, %4, %6, %5}], [%2];"
               :: "r"(dst), "l"(m), "r"(bar), "r"(c0), "r"(c1), "r"(c3), "r"(0) : "memory");
}
__device__ __forceinline__ void tma_store(const CUtensorMap* m, int c1, int c3, uint32_t src) {
  asm volatile("cp.async.bulk.tensor.4d.global.shared::cta.bulk_group [%0, {%4, %2, %4, %3}], [%1];" :: "l"(m), "r"(src), "r"(c1), "r"(c3), "r"(0) : "memory");
}
__device__ __forceinline__ void bulk_g2s(uint32_t dst, const void* src, uint32_t bytes, uint32_t bar) {
  asm volatile("cp.async.bulk.shared::cluster.global.mbarrier::complete_tx::bytes [%0], [%1], %2, [%3];" :: "r"(dst), "l"(src), "r"(bytes), "r"(bar) : "memory");
}
__device__ __forceinline__ void bulk_s2g(void* dst, uint32_t src, uint32_t bytes) {
  asm volatile("cp.async.bulk.global.shared::cta.bulk_group [%0], [%1], %2;" :: "l"(dst), "r"(src), "r"(bytes) : "memory");
}
__device__ __forceinline__ void wg_fence() { asm volatile("wgmma.fence.sync.aligned;" ::: "memory"); }
__device__ __forceinline__ void wg_commit() { asm volatile("wgmma.commit_group.sync.aligned;" ::: "memory"); }
template <int N> __device__ __forceinline__ void wg_wait() { asm volatile("wgmma.wait_group.sync.aligned %0;" :: "n"(N) : "memory"); }
__device__ __forceinline__ void proxy_fence() { asm volatile("fence.proxy.async.global;" ::: "memory"); }
#ifndef LIGHT
#define LIGHT 1
#endif
__device__ __forceinline__ void smem_fence() {
  if (LIGHT == 2) return;
  if (LIGHT) asm volatile("mbarrier.init.shared::cta.b64 [%0], 1;" :: "r"(base + OFF_BAR + 248) : "memory");
  else asm volatile("fence.proxy.async.shared::cta;" ::: "memory");
}
__device__ __forceinline__ uint32_t gtime() { uint32_t v; asm volatile("mov.u32 %0, %%globaltimer_lo;" : "=r"(v)); return v; }
__device__ __forceinline__ void publish(int i, bool timed = false) {
  asm volatile("cp.async.bulk.commit_group;" ::: "memory");
  if (timed) asm volatile("red.relaxed.gpu.global.max.u32 [%0], %1;" :: "l"(&g_cnt[i * 32 + 1]), "r"(gtime()) : "memory");
  asm volatile("cp.async.bulk.wait_group 0;" ::: "memory");
  asm volatile("red.relaxed.gpu.global.inc.u32 [%0], 0xffffffff;" :: "l"(&g_cnt[i * 32]) : "memory");
}
__device__ __forceinline__ void spin_ge(int i, unsigned target) {
  asm volatile("{\n.reg .pred p;\n.reg .u32 n, v;\nmov.u32 n, 0;\nLAB_SPIN:\n"
               "ld.relaxed.gpu.global.u32 v, [%0];\nsetp.ge.u32 p, v, %1;\n@p bra DONE;\n"
               "add.u32 n, n, 1;\nsetp.lt.u32 p, n, 4000000;\n@p bra LAB_SPIN;\ntrap;\nDONE:\n}" :: "l"(&g_cnt[i * 32]), "r"(target) : "memory");
}
__device__ __forceinline__ unsigned ld_relaxed(int i) { unsigned v; asm volatile("ld.relaxed.gpu.global.u32 %0, [%1];" : "=r"(v) : "l"(&g_cnt[i * 32]) : "memory"); return v; }
__device__ __forceinline__ bool elect() {
  uint32_t r; asm volatile("{\n.reg .pred p;\nelect.sync _|p, 0xffffffff;\nselp.u32 %0, 1, 0, p;\n}" : "=r"(r)); return r != 0;
}
__device__ __forceinline__ void wait_until(uint32_t tn) { while ((int)(clock() - tn) < 0) __nanosleep(20); }
__device__ __forceinline__ void store_paced(unsigned char* dst, int dstep, uint32_t src, int sstep, int n, int gap, int bytes = 1792) {
  uint32_t tn = clock();
#pragma unroll 1
  for (int i = 0; i < n; i++) { wait_until(tn); bulk_s2g(dst, src, bytes); dst += dstep; src += sstep; tn += gap; }
}
__device__ __forceinline__ uint4 lds128(uint32_t a) { uint4 v; asm volatile("ld.shared.v4.u32 {%0,%1,%2,%3}, [%4];" : "=r"(v.x), "=r"(v.y), "=r"(v.z), "=r"(v.w) : "r"(a) : "memory"); return v; }
__device__ __forceinline__ uint32_t lds32(uint32_t a) { uint32_t v; asm volatile("ld.shared.u32 %0, [%1];" : "=r"(v) : "r"(a) : "memory"); return v; }
__device__ __forceinline__ void sts128(uint32_t p, uint32_t a, uint32_t b, uint32_t c, uint32_t d) { asm volatile("st.shared.v4.u32 [%0], {%1,%2,%3,%4};" :: "r"(p), "r"(a), "r"(b), "r"(c), "r"(d) : "memory"); }
__device__ __forceinline__ void sts64(uint32_t p, float a, float b) { asm volatile("st.shared.v2.f32 [%0], {%1,%2};" :: "r"(p), "f"(a), "f"(b) : "memory"); }
__device__ __forceinline__ void named_sync(int id, int n) { asm volatile("bar.sync %0, %1;" :: "r"(id), "r"(n) : "memory"); }
__device__ __forceinline__ void named_arrive(int id, int n) { asm volatile("bar.arrive %0, %1;" :: "r"(id), "r"(n) : "memory"); }
__device__ __forceinline__ constexpr uint32_t dlo(uint32_t off, uint32_t lbo) { return ((base + off) >> 4) | (lbo >> 4 << 16); }
__device__ __forceinline__ uint32_t pack2(float lo, float hi) { uint32_t r; asm("cvt.rn.bf16x2.f32 %0, %1, %2;" : "=r"(r) : "f"(hi), "f"(lo)); return r; }
__device__ __forceinline__ float bf_lo(uint32_t v) { return __uint_as_float(v << 16); }
__device__ __forceinline__ float bf_hi(uint32_t v) { return __uint_as_float(v & 0xffff0000u); }
__device__ __forceinline__ float rbf(float x) { return bf_lo(pack2(x, 0.f)); }
__device__ __forceinline__ uint32_t hsub2(uint32_t a, uint32_t b) { uint32_t r; asm("sub.rn.bf16x2 %0, %1, %2;" : "=r"(r) : "r"(a), "r"(b)); return r; }
__device__ __forceinline__ uint32_t hadd2(uint32_t a, uint32_t b) { uint32_t r; asm("add.rn.bf16x2 %0, %1, %2;" : "=r"(r) : "r"(a), "r"(b)); return r; }
__device__ __forceinline__ uint32_t hmax2(uint32_t a, uint32_t b) { uint32_t r; asm("max.bf16x2 %0, %1, %2;" : "=r"(r) : "r"(a), "r"(b)); return r; }
__device__ __forceinline__ uint32_t hmul2(uint32_t a, uint32_t b) { uint32_t r; asm("mul.rn.bf16x2 %0, %1, %2;" : "=r"(r) : "r"(a), "r"(b)); return r; }
__device__ __forceinline__ uint32_t hfma2(uint32_t a, uint32_t b, uint32_t c) { uint32_t r; asm("fma.rn.bf16x2 %0, %1, %2, %3;" : "=r"(r) : "r"(a), "r"(b), "r"(c)); return r; }
__device__ __forceinline__ float tanh_fast(float x) { float r; asm("tanh.approx.f32 %0, %1;" : "=f"(r) : "f"(x)); return r; }
__device__ __forceinline__ float rcp_fast(float x) { float r; asm("rcp.approx.ftz.f32 %0, %1;" : "=f"(r) : "f"(x)); return r; }
__device__ __forceinline__ float ex2_fast(float x) { float r; asm("ex2.approx.ftz.f32 %0, %1;" : "=f"(r) : "f"(x)); return r; }
__device__ __forceinline__ void mma16816(float (&c)[4], uint32_t a0, uint32_t a1, uint32_t a2, uint32_t a3, uint32_t b0, uint32_t b1) {
  asm volatile("mma.sync.aligned.m16n8k16.row.col.f32.bf16.bf16.f32 {%0,%1,%2,%3}, {%4,%5,%6,%7}, {%8,%9}, {%0,%1,%2,%3};"
               : "+f"(c[0]), "+f"(c[1]), "+f"(c[2]), "+f"(c[3]) : "r"(a0), "r"(a1), "r"(a2), "r"(a3), "r"(b0), "r"(b1));
}
__device__ __forceinline__ void ldsm4(uint32_t (&r)[4], uint32_t addr) {
  asm volatile("ldmatrix.sync.aligned.m8n8.x4.shared.b16 {%0,%1,%2,%3}, [%4];" : "=r"(r[0]), "=r"(r[1]), "=r"(r[2]), "=r"(r[3]) : "r"(addr) : "memory");
}
__device__ __forceinline__ void stsm4(uint32_t addr, uint32_t a, uint32_t b, uint32_t c, uint32_t d) {
  asm volatile("stmatrix.sync.aligned.m8n8.x4.shared.b16 [%0], {%1,%2,%3,%4};" :: "r"(addr), "r"(a), "r"(b), "r"(c), "r"(d) : "memory");
}
__device__ __forceinline__ void stsm2(uint32_t addr, uint32_t a, uint32_t b) {
  asm volatile("stmatrix.sync.aligned.m8n8.x2.shared.b16 [%0], {%1,%2};" :: "r"(addr), "r"(a), "r"(b) : "memory");
}
__device__ __forceinline__ void load_row(uint32_t (&r)[14], const unsigned char* p, int t) {
#pragma unroll
  for (int i = 0; i < 3; i++)
    asm volatile("ld.global.nc.L1::no_allocate.v4.u32 {%0,%1,%2,%3}, [%4];" : "=r"(r[4 * i]), "=r"(r[4 * i + 1]), "=r"(r[4 * i + 2]), "=r"(r[4 * i + 3]) : "l"(p + i * 64 + t * 16));
  asm volatile("ld.global.nc.L1::no_allocate.v2.u32 {%0,%1}, [%2];" : "=r"(r[12]), "=r"(r[13]) : "l"(p + 192 + t * 8));
}
__device__ __forceinline__ void lds_row(uint32_t* r, uint32_t a, int t) {
#pragma unroll
  for (int i = 0; i < 3; i++) { const uint4 v = lds128(a + i * 64 + t * 16); r[4 * i] = v.x; r[4 * i + 1] = v.y; r[4 * i + 2] = v.z; r[4 * i + 3] = v.w; }
  asm volatile("ld.shared.v2.u32 {%0,%1}, [%2];" : "=r"(r[12]), "=r"(r[13]) : "r"(a + 192 + t * 8) : "memory");
}

struct LnC { uint32_t m, rh, rl; float r; };
__device__ __forceinline__ LnC ln_consts(float mean, float var) {
  float sd;
  asm("sqrt.approx.ftz.f32 %0, %1;" : "=f"(sd) : "f"(rbf(rbf(var) + 1e-5f)));
  const float r = rcp_fast(rbf(sd)), rh = rbf(r);
  return {pack2(mean, mean), pack2(rh, rh), pack2(r - rh, r - rh), r};
}
__device__ __forceinline__ float variance(float mean, float sq) { return fmaxf(fmaf(-mean, mean, sq * (1.0f / D_)), 0.f); }
__device__ __forceinline__ uint32_t ln_apply(uint32_t x, const LnC& c) { const uint32_t d = hsub2(x, c.m); return hfma2(d, c.rh, hmul2(d, c.rl)); }

template <int N> __device__ __forceinline__ void fresh(float (&a)[N]) {
#pragma unroll
  for (int i = 0; i < N; i++) asm volatile("" : "=f"(a[i]));
}
__device__ __forceinline__ void pin(uint32_t (&a)[4]) { asm volatile("" : "+r"(a[0]), "+r"(a[1]), "+r"(a[2]), "+r"(a[3])); }
constexpr int B_EMPTY = 64, B_F0 = 128, B_F1 = 136, B_F2 = 144, B_F3 = 152, B_HALO = 160, B_RT = 176, B_RES = 184, B_TS = 192, B_F1B = 200, B_XF = 208, B_X = 216, S_FLAG = 224;
constexpr int N_GO = 6, N_DONE = 7;
__device__ __forceinline__ void watch_flag(int slot, int i, unsigned target) {
  asm volatile("{\n.reg .pred p;\n.reg .u32 n, v, t;\nmov.u32 n, 0;\nLAB_SPIN:\n"
               "ld.relaxed.gpu.global.v2.u32 {v, t}, [%1];\nsetp.ge.u32 p, v, %2;\n@p st.volatile.shared.v2.u32 [%0], {v, t};\n"
               "ld.volatile.shared.u32 v, [%0];\nsetp.ne.u32 p, v, 0;\n@p bra DONE;\n"
               "add.u32 n, n, 1;\nsetp.lt.u32 p, n, 4000000;\n@p bra LAB_SPIN;\ntrap;\nDONE:\n}" :: "r"(bars + S_FLAG + slot * 8), "l"(&g_cnt[i * 32]), "r"(target) : "memory");
}
__device__ __forceinline__ void wait_flag(int slot, int delay) {
  uint32_t v, last;
  do asm volatile("ld.volatile.shared.v2.u32 {%0, %1}, [%2];" : "=r"(v), "=r"(last) : "r"(bars + S_FLAG + slot * 8) : "memory"); while (!v);
  while (gtime() - last < (uint32_t)delay);
}
__device__ __forceinline__ void arrive_if(int id, bool on) {
  asm volatile("{\n.reg .pred p;\nsetp.ne.u32 p, %1, 0;\n@p bar.arrive %0, 256;\n}" :: "r"(id), "r"((uint32_t)on) : "memory");
}
template <int TA, class Hook>
__device__ __forceinline__ void stage(float (&acc)[56], uint32_t ah, uint32_t bh, int sb, uint32_t par, uint32_t& ok, int& g_tr, bool first, bool rel, Hook hook, const uint32_t (*X)[4] = nullptr) {
  if (!ok) { if (WU) mbar_wait_u(bars + sb * 8, par); else mbar_wait(bars + sb * 8, par); }
  wg_fence();
#pragma unroll
  for (int k = 0; k < 4; k++) {
    if constexpr (TA == 2) wgmma_rs_n112<1>(acc, X[k], dlo(sb * SLOT + 8192 + k * 3584, 1792), bh, k || !first);
    else wgmma_n112<TA, 1>(acc, dlo(sb * SLOT + k * (TA ? 2048 : 256), TA ? 8192 : 128), ah, dlo(sb * SLOT + 8192 + k * 3584, 1792), bh, k || !first);
    if (k == 1) ok = mbar_try(bars + ((sb + 1) & 7) * 8, sb == 7 ? par ^ 1 : par);
    hook(k);
  }
  wg_commit();
  wg_wait<1>();
#if DBG_TRACE == 2
  { const uint32_t tz = 0; OBS((threadIdx.x & 127) == 0, g_tr); g_tr++; }
#endif
  if (rel) mbar_arrive(bars + B_EMPTY + ((sb + 7) & 7) * 8);
}

struct Params {
  const unsigned char *x, *wqkv, *wo, *w1, *w2;
  const unsigned short *b1, *b2;
  unsigned char* out;
  uint32_t dw, dx, db, dk;
#ifdef TUNE
  int tune[NTUNE];
#endif
};

__global__ void __launch_bounds__(NTHREADS, 1)
fused_kernel(const Params p, const __grid_constant__ CUtensorMap m_w1, const __grid_constant__ CUtensorMap m_w2, const __grid_constant__ CUtensorMap m_b14,
             const __grid_constant__ CUtensorMap m_a8, const __grid_constant__ CUtensorMap m_b7, const __grid_constant__ CUtensorMap m_xt) {
  extern __shared__ __align__(1024) unsigned char smem_raw[];
  const uint32_t t0 = clock();
#ifdef DBG_OBS
  uint32_t tz; asm volatile("mov.u32 %0, " OBS_CLK ";" : "=r"(tz));
#endif
  const int tid = threadIdx.x, lane = tid & 31, b = blockIdx.x;
  const int g = lane >> 2, t = lane & 3, r8 = lane & 7, mi = lane >> 3;
  uint32_t H[14];
  if (tid < 128) load_row(H, p.x + (b * 16 + g) * (D_ * 2) + (tid >> 5) * 224, t);
  const int warp = __shfl_sync(0xffffffffu, tid >> 5, 0);
  const int dt = b & 3, mt = b >> 2;
  const bool g1 = b < 112;
  const int ft = mt, d1 = dt;
  if (warp >= 8) {
    if (warp == 8) {
      if (elect()) {
        if (smem_u32(smem_raw) != base) asm volatile("trap;");
#pragma unroll
        for (int i = 0; i < 28; i++) mbar_init(bars + i * 8, i * 8 == B_XF ? 8 : (i * 8 == B_F1 && !g1 ? 2 : 1));
        sts128(bars + S_FLAG, 0, 0, 0, 0);
        asm volatile("fence.mbarrier_init.release.cluster;" ::: "memory");
      }
      __syncwarp();
      named_arrive(12, 160); named_arrive(13, 160);
    }
    named_sync(15, 128);
    asm volatile("setmaxnreg.dec.sync.aligned.u32 80;");
    if (warp == 8) {
      unsigned tk = 0;
      if (elect()) {
        wait_until(t0 + DLY_B);
        mbar_expect_tx(bars + B_F2, GRP);
        bulk_g2s(base + OFF_U, p.x + (b * 2 + 1) * GRP, GRP, bars + B_F2);
        asm volatile("prefetch.tensormap [%0];" :: "l"(&m_xt) : "memory");
        wait_until(t0 + DLY_X);
        mbar_expect_tx(bars + B_X, 7 * 8192);
        asm volatile("cp.async.bulk.tensor.5d.shared::cluster.global.mbarrier::complete_tx::bytes [%0], [%1, {%4, %4, %4, %3, %4}], [%2];"
                     :: "r"(base + OFF_X), "l"(&m_xt), "r"(bars + B_X), "r"(mt * 4), "r"(0) : "memory");
        wait_until(t0 + DLY_D);
        asm volatile("prefetch.tensormap [%0];" :: "l"(&m_w1) : "memory");
        asm volatile("prefetch.tensormap [%0];" :: "l"(&m_b14) : "memory");
        if (g1) {
#pragma unroll 1
          for (int c = 0; c < 8; c++) {
            wait_until(t0 + DLY_W + c * TPW);
            if (c == 6) mbar_wait(bars + B_XF, 0);
            tma4d(base + c * SLOT, &m_w1, ft * 64, 0, c * 8, bars + c * 8);
          }
        } else {
          const int n = dt < 3 ? 16 : 8;
          mbar_expect_tx(bars + B_RT, n * 5376);
#pragma unroll 1
          for (int i = 0; i < n; i++) { wait_until(t0 + DLY_Q + i * PQ); bulk_g2s(base + i * 5376, p.wqkv + ((mt & 3) * 56 + dt * 16 + i) * 5376, 5376, bars + B_RT); }
        }
#pragma unroll 1
        for (int r = g1 ? 1 : 4; r < 4; r++) {
#pragma unroll
          for (int s = 0; s < 8; s++) {
            mbar_wait_u(bars + B_EMPTY + s * 8, (r & 1) ^ 1);
            tma4d(base + s * SLOT, &m_w1, mt * 64, (r & 2) * 4, (r & 1) * 64 + s * 8, bars + s * 8);
          }
        }
        mbar_wait(bars + B_EMPTY + 5 * 8, 1);
        mbar_wait(bars + B_EMPTY + 5 * 8, 0);
#pragma unroll 1
        for (int r = 0; ; r++) {
#pragma unroll
          for (int j = 0; j < 8; j++) {
            const int s = (j + 5) & 7;
            mbar_wait_u(bars + B_EMPTY + s * 8, (r + (j < 3)) & 1);
            tma4d(base + s * SLOT, &m_w2, mt * 64, 0, r * 512 + j * 64, bars + s * 8);
            if (j == 3 && r == 3) goto w2_done;
          }
        }
        w2_done:
        mbar_wait(bars + B_F3, 0);
        OBS(1, 22);
#pragma unroll
        for (int s = 1; s < 8; s++) {
          mbar_wait_u(bars + B_EMPTY + s * 8, 1);
          tma4d(base + s * SLOT, &m_a8, 0, s * 8 - 8, G_O + mt * 8, bars + s * 8);
        }
        tk = atomicInc(&g_cnt[C_TICKET * 32], 0xffffffffu);
      }
      if (__any_sync(0xffffffffu, tk == 127)) {
#pragma unroll 1
        for (int i = lane; i < C_END; i += 32) *(uint2*)&g_cnt[i * 32] = make_uint2(0, 0);
      }
    } else if (warp == 9) {
      if (elect()) {
        if (ld_relaxed(C_H) + ld_relaxed(C_H + 1) > 256) asm volatile("trap;");
        {
          wait_until(t0 + DLY_E);
          asm volatile("prefetch.tensormap [%0];" :: "l"(&m_b7) : "memory");
          asm volatile("prefetch.tensormap [%0];" :: "l"(&m_w2) : "memory");
          asm volatile("prefetch.tensormap [%0];" :: "l"(&m_a8) : "memory");
        }
        uint32_t bytes = SLOT;
#pragma unroll 1
        for (int r = g1 ? 0 : 4; r < 11; r++) {
#pragma unroll
          for (int s = 0; s < 8; s++) {
            if (s == 0 && r == 0) { if (NP_H == 0) watch_flag(0, C_H, 128); wait_flag(0, SY_H); OBS(1, 16); }
            if (s == 0 && (r == 2 || r == 4)) { mbar_wait(bars + B_F0 + (r >> 2) * 8, 0); OBS(1, 16 + (r >> 1)); if (r == 4) bytes = BT; }
            if (s == 5 && r == 0) mbar_wait(bars + B_XF, 0);
            if (s == 7 && r == 4) mbar_wait(bars + B_F1B, 0);
            if (s == 5 && r == 6) { wait_flag(1, SY_U); OBS(1, 20); bytes = SLOT; }
            if (s) mbar_wait_u(bars + B_EMPTY + s * 8, (r & 1) ^ 1); else mbar_wait(bars + B_EMPTY, (r & 1) ^ 1);
#if DBG_TRACE == 1
            { const uint32_t tz = 0; OBS(1, 32 + r * 8 + s); }
#endif
            mbar_expect_tx(bars + s * 8, bytes);
            tma4d(base + s * SLOT + 8192, &m_b14, 0, dt * 14, r * 64 + s * 8, bars + s * 8);
          }
        }
      }
    } else if (warp == 10) {
      uint32_t tn = t0 + PF0;
      const unsigned char* src = p.w1 + (b + (b & ~7)) * 3584 + lane * 128;
#pragma unroll 1
      for (int i = 0; i < 32; i++) {
        if (i == PFR) {
#pragma unroll 1
          for (int j = 0; j < 3; j++) {
            wait_until(t0 + DLY_R + j * PACER);
            if (j * 32 + lane < 74) asm volatile("prefetch.global.L2 [%0];" :: "l"(p.wqkv + min(b * 74 + j * 32 + lane, 9407) * 128) : "memory");
          }
        }
        wait_until(tn);
        if (i == 8) src -= 16 * 458752 - 8 * 3584;
        if (i == 16) src = p.w2 + b * 3584 + lane * 128;
        if (lane < 28) asm volatile("prefetch.global.L2 [%0];" :: "l"(src) : "memory");
        __syncwarp();
        src += i < 16 ? 2 * 458752 : 458752;
        tn += i < PFN ? PACE0 : (i < 16 ? PACE1 : PACE2);
        if (i + 1 == PFN) tn = t0 + PF1;
      }
      watch_flag(1, C_U, 128);
      spin_ge(C_O + mt, 16);
      if (lane == 0) mbar_arrive(bars + B_F3);
    } else {
      unsigned char* dst = g_scr + (G_H + b) * GRP;
      asm volatile("" : "+l"(dst));
      named_sync(10, 160);
      smem_fence();
      if (elect()) { bulk_s2g(dst, base + OFF_KV, GRP); publish(C_H, true); OBS(1, 3); }
      named_sync(9, 160);
      smem_fence();
      if (elect()) {
        if (g1 && SY_B) { wait_flag(0, SY_B); store_paced(dst + 128 * GRP, 1792, base + OFF_KV + GRP, 1792, 4, PS_H); }
        else bulk_s2g(dst + 128 * GRP, base + OFF_KV + GRP, GRP);
        publish(C_H + 1);
        OBS(1, 4);
      }
      __syncwarp();
      if (g1) { spin_ge(C_H + 1, 128); if (lane == 0) mbar_arrive(bars + B_F0); }
      else {
        const int kg0 = (mt & 3) * 14 + dt * 4, nk = dt < 3 ? 4 : 2;
#pragma unroll 1
        for (int m = 0; m < 3; m++) {
          named_sync(m == 0 ? 14 : (m == 1 ? 10 : 9), 160);
          smem_fence();
          if (elect()) {
            if (m == 2) { mbar_expect_tx(bars + B_RT, nk * GRP); bulk_g2s(base, p.wo + kg0 * GRP, nk * GRP, bars + B_RT); }
            bulk_s2g(g_scr + (G_W + m * 56 + kg0) * GRP, base + (12 + m * 4) * GRP, nk * GRP);
            if (m != 1) publish(m ? C_W2 : C_W);
            OBS(m != 1, 5 + (m >> 1));
          }
          __syncwarp();
        }
      }
      spin_ge(C_W, 16);
      if (lane == 0) mbar_arrive(bars + B_F1);
      spin_ge(C_W2, 16);
      if (lane == 0) mbar_arrive(bars + B_F1B);
      if (mt == 0) {
#pragma unroll
        for (int i = 0; i < 14; i++) sts128(base + OFF_KV + (i / 7) * KV + (i % 7) * 512 + lane * 16, 0, 0, 0, 0);
        smem_fence();
        __syncwarp();
        if (lane < 2) mbar_arrive(bars + B_HALO + lane * 8);
      }
      const unsigned have = EARLY && mt > 0 ? ld_relaxed(C_HALO + b - 4) : 0;
      if (g1) {
        named_sync(14, 160);
        smem_fence();
        if (elect()) tma_store(&m_b7, d1 * 14, G_U + ft * 8, base + OFF_U);
        named_sync(10, 160);
        smem_fence();
        if (elect()) { tma_store(&m_b7, d1 * 14 + 7, G_U + ft * 8, base + OFF_U + GRP); publish(C_U, true); OBS(1, 7); }
        __syncwarp();
      }
#pragma unroll 1
      for (int i = 0; i < 2; i++) {
        unsigned char* hg = g_scr + (G_HALO + b) * GRP + i * 3584;
        named_sync(i ? 0 : 11, 64);
        smem_fence();
        if (mt < 31 && elect()) { bulk_s2g(hg, base + OFF_KV + i * KV + 8 * 1792, 3584); publish(C_HALO + b); }
        OBS(lane == 0, i ? 15 : 23);
        if (mt > 0) {
          if (have <= i) spin_ge(C_HALO + b - 4, i + 1);
          if (elect()) { mbar_expect_tx(bars + B_HALO + i * 8, 3584); bulk_g2s(base + OFF_KV + i * KV, hg - 4 * GRP, 3584, bars + B_HALO + i * 8); }
        }
        __syncwarp();
      }
    }
  } else {
    const int wg = warp >> 2, w4 = warp & 3;
    const bool rel = (tid & 127) == 0;
    named_sync(12 + wg, 160);
    if (wg) { mbar_wait(bars + B_F2, 0); lds_row(H, base + OFF_U + g * 896 + w4 * 224, t); }
    {
      const uint32_t part = base + OFF_PART + wg * 512 + g * 32, st = base + OFF_KV + wg * GRP + (w4 * 14 + mi) * 128 + r8 * 16;
#pragma unroll
      for (int ln = 0; ln < (ANA ? 1 : 2); ln++) {
        float s0 = 0.f, s1 = 0.f, q0 = 0.f, q1 = 0.f;
#pragma unroll
        for (int j = 0; j < 14; j++) { const float a = bf_lo(H[j]), c = bf_hi(H[j]); s0 += a; s1 += c; q0 = fmaf(a, a, q0); q1 = fmaf(c, c, q1); }
        s0 += s1; q0 += q1;
#pragma unroll
        for (int o = 1; o < 4; o <<= 1) { s0 += __shfl_xor_sync(0xffffffffu, s0, o); q0 += __shfl_xor_sync(0xffffffffu, q0, o); }
        if (t == 0) sts64(part + ln * 256 + w4 * 8, s0, q0);
        OBS(tid == 0 && ln == 0, 0);
        named_sync(1 + wg, 128);
        const uint4 u = lds128(part + ln * 256), v = lds128(part + ln * 256 + 16);
        const float mean = ((__uint_as_float(u.x) + __uint_as_float(u.z)) + (__uint_as_float(v.x) + __uint_as_float(v.z))) * (1.0f / D_);
        const float var = variance(mean, (__uint_as_float(u.y) + __uint_as_float(u.w)) + (__uint_as_float(v.y) + __uint_as_float(v.w)));
        const LnC l = ln_consts(mean, var);
#pragma unroll
        for (int j = 0; j < 14; j++) H[j] = ln_apply(H[j], l);
        if (ANA) {
          const LnC l2 = ln_consts((mean - bf_lo(l.m)) * l.r, var * l.r * l.r);
#pragma unroll
          for (int j = 0; j < 14; j++) H[j] = ln_apply(H[j], l2);
        }
      }
#pragma unroll
      for (int i = 0; i < 3; i++) stsm4(st + i * 512, H[4 * i], H[4 * i + 1], H[4 * i + 2], H[4 * i + 3]);
      stsm2(st + 1536, H[12], H[13]);
      named_arrive(10 - wg, 160);
      OBS(rel, 1 + wg);
    }
    uint32_t ok = 0;
    int trc = 0;
    auto nohook = [](int) {};
#ifdef DBG_OBS
#define OBS0(c, i) do { mbar_wait(bars + ((c) & 7) * 8, ((c) >> 3) & 1); ok = 1; OBS(rel, i); trc = (i) == 5 ? 32 : 64 + (c); } while (0)
#else
#define OBS0(c, i) ok = 0
#endif
    const uint32_t sx = base + OFF_KV + (tid & 127) * 16;
    if (wg == 0) {
      uint32_t hb[4], R[28];
#pragma unroll
      for (int i = 0; i < 4; i++)
        asm volatile("ld.relaxed.cta.global.u16 %0, [%1];" : "=r"(hb[i]) : "l"((i < 2 ? p.b1 + (g1 ? mt * 64 : 0) : p.b2 + mt * 64) + w4 * 16 + g + (i & 1) * 8) : "memory");
      mbar_wait(bars + B_X, 0);
#pragma unroll
      for (int i = 0; i < 8; i++) {
        const int h = i >> 2, j = i & 3, xi = h * 4 + (g >> 1), c = dt * 14 + (j < 3 ? 4 * j + t : 12 + (t >> 1));
        const uint4 v = lds128(base + OFF_X + (c >> 3) * 8192 + (w4 * 16 + (g & 1) * 8 + xi) * 128 + (((c ^ xi) & 7) << 4));
        if (j < 3) { R[h * 14 + 4 * j] = v.x; R[h * 14 + 4 * j + 1] = v.y; R[h * 14 + 4 * j + 2] = v.z; R[h * 14 + 4 * j + 3] = v.w; }
        else { R[h * 14 + 12] = t & 1 ? v.z : v.x; R[h * 14 + 13] = t & 1 ? v.w : v.y; }
      }
#pragma unroll
      for (int i = 0; i < 28; i++) asm volatile("" : "+r"(R[i]));
      if (lane == 0) mbar_arrive(bars + B_XF + R[27] * threadIdx.y);
      float acc[56];
      if (g1) {
#pragma unroll
        for (int i = 0; i < 56; i++) { acc[i] = bf_lo(hb[(i >> 1) & 1]); asm volatile("" : "+f"(acc[i])); }
        if (w4 < NP_H) { wait_until(clock() + w4 * PH_H); watch_flag(0, C_H, 128); }
        OBS0(0, 5);
#pragma unroll 1
        for (int r = 0; r < 4; r++)
#pragma unroll
          for (int c = 0; c < 8; c++) stage<1>(acc, p.dw, p.db, c, r & 1, ok, trc, false, rel && (c || r), [&](int k) { if (c == 7 && k == 3 - HK) arrive_if(3, r == 3); });
        wg_wait<0>();
        if (rel) mbar_arrive(bars + B_EMPTY + 7 * 8);
        OBS(rel, 6);
        const uint32_t us = base + OFF_U + (w4 * 2 + (mi & 1)) * 896 + (mi >> 1) * 128 + r8 * 16;
#pragma unroll
        for (int hf = 0; hf < 2; hf++) {
          uint32_t U[14];
#pragma unroll
          for (int j = 0; j < 14; j++) {
            const float a = acc[hf * 28 + 2 * j], c = acc[hf * 28 + 2 * j + 1];
            U[j] = pack2(fmaf(a, tanh_fast(a * fmaf(a * a, 0.0356774081f, 0.7978845608f)), a), fmaf(c, tanh_fast(c * fmaf(c * c, 0.0356774081f, 0.7978845608f)), c));
          }
#pragma unroll
          for (int j = 0; j < 3; j++) stsm4(us + hf * GRP + j * 256, U[4 * j], U[4 * j + 1], U[4 * j + 2], U[4 * j + 3]);
          stsm2(us + hf * GRP + 768, U[12], U[13]);
          named_arrive(hf ? 10 : 14, 160);
          if (!hf) mbar_wait(bars + B_X, 0);
        }
        OBS(rel, 30);
      } else {
        named_arrive(3, 256);
        const int kg0 = (mt & 3) * 14 + dt * 4, nk = dt < 3 ? 4 : 2;
        mbar_wait(bars + B_XF, 0);
        mbar_wait(bars + B_RT, 0);
        OBS(tid == 0, 7);
#pragma unroll 1
        for (int m = 1; m < 4; m++) {
          if (w4 < nk) {
            uint4 v[14];
#pragma unroll
            for (int l = 0; l < 14; l++) v[l] = lds128(base + (w4 * 8 + r8) * 2688 + (m % 3) * 896 + (l >> 1) * 128 + ((r8 + mi + (l & 1) * 4) & 7) * 16);
#pragma unroll
            for (int l = 0; l < 14; l++) sts128(base + (8 + m * 4 + w4) * GRP + (l >> 1) * 1024 + ((r8 + mi + (l & 1) * 4) & 7) * 128 + r8 * 16, v[l].x, v[l].y, v[l].z, v[l].w);
          }
          named_arrive(m == 1 ? 14 : (m == 2 ? 10 : 9), 160);
        }
        mbar_wait(bars + B_RT, 1);
#pragma unroll 1
        for (int i = 0; i < nk; i++) {
          uint32_t W[14];
          lds_row(W, base + i * GRP + g * 896 + w4 * 224, t);
          const uint32_t st = base + (4 + i) * GRP + (w4 * 14 + mi) * 128 + r8 * 16;
#pragma unroll
          for (int j = 0; j < 3; j++) stsm4(st + j * 512, W[4 * j], W[4 * j + 1], W[4 * j + 2], W[4 * j + 3]);
          stsm2(st + 1536, W[12], W[13]);
        }
        smem_fence();
        named_sync(1, 128);
        if (w4 == 0 && elect()) {
          bulk_s2g(g_scr + (G_WO + kg0) * GRP, base + 4 * GRP, nk * GRP);
          publish(C_U);
          mbar_arrive(bars + B_F1);
          OBS(1, 16);
        }
        __syncwarp();
      }
#pragma unroll
      for (int i = 0; i < 56; i++) { acc[i] = 0.f; asm volatile("" : "+f"(acc[i])); }
#pragma unroll
      for (int i = 2; i < 4; i++) { hb[i] = hmul2(hb[i] * 0x10001u, 0x3f003f00u); asm volatile("" : "+r"(hb[i])); }
      const int ro = (mt * 64 + w4 * 16 + g) * (D_ * 2) + dt * 224;
      unsigned char *outp = p.out + ro + t * 16, *outq = p.out + ro + 192 + t * 8;
      asm volatile("" : "+l"(outp), "+l"(outq));
      if (w4 < NP_U) { wait_until(clock() + PU0 + w4 * PH_U); watch_flag(1, C_U, 128); }
      named_sync(5, 256);
      OBS0(21, 10);
#pragma unroll 1
      for (int r = 0; ; r++) {
#pragma unroll
        for (int j = 0; j < 8; j++) {
          const bool site = j == SA % 8 || j == SB % 8, yield = (j == SA % 8 && r == SA / 8) || (j == SB % 8 && r == SB / 8);
          stage<1>(acc, p.dw, p.db, (j + 5) & 7, (r + (j > 2)) & 1, ok, trc, false, rel && (j || r), [&](int k) {
            if (k == 3 - HK) { if (site) arrive_if(N_GO, yield); if (j == 3) arrive_if(8, r == 3); } });
          if (site && yield) named_sync(N_DONE, 256);
          if (j == 3 && r == 3) goto gemm2_done;
        }
      }
      gemm2_done:
      wg_wait<0>();
      OBS(rel, 24);
      uint32_t G[28], dep = 0;
#pragma unroll
      for (int j = 0; j < 28; j++) {
        const uint32_t hh = hfma2(pack2(acc[2 * j], acc[2 * j + 1]), 0x3e803e80u, hb[2 + (j & 1)]);
        const float a = bf_lo(hh), c = bf_hi(hh);
        G[j] = pack2(fmaf(a, tanh_fast(a), a), fmaf(c, tanh_fast(c), c));
        dep |= G[j];
      }
      OBS(rel, 26);
      named_sync(12 + w4 + dep * threadIdx.y, 64);
      uint4 S4[8];
#pragma unroll
      for (int i = 0; i < 8; i++) S4[i] = lds128(sx + i * 2048);
      OBS(rel, 123);
#pragma unroll
      for (int i = 0; i < 4; i++) {
#pragma unroll
        for (int h = 0; h < 2; h++) {
          const uint32_t Sv[4] = {S4[2 * i + h].x, S4[2 * i + h].y, S4[2 * i + h].z, S4[2 * i + h].w};
          uint32_t Y[4];
#pragma unroll
          for (int j = 0; j < (i < 3 ? 4 : 2); j++) Y[j] = hadd2(R[h * 14 + 4 * i + j], hmul2(Sv[j], G[8 * i + 2 * j + h]));
          if (i < 3) asm volatile("st.global.v4.u32 [%0], {%1,%2,%3,%4};" :: "l"(outp + h * 8 * D_ * 2 + i * 64), "r"(Y[0]), "r"(Y[1]), "r"(Y[2]), "r"(Y[3]) : "memory");
          else asm volatile("st.global.v2.u32 [%0], {%1,%2};" :: "l"(outq + h * 8 * D_ * 2), "r"(Y[0]), "r"(Y[1]) : "memory");
        }
      }
      OBS(rel, 28);
#ifdef DBG_OBS
      named_sync(1, 128);
      { uint32_t v = lds32(base + OFF_OBS + tid * 4); if (tid == 126) v = tz; if (tid == 127) asm volatile("mov.u32 %0, %%smid;" : "=r"(v)); g_obs[b * 128 + tid] = v; }
#endif
    } else {
      asm volatile("setmaxnreg.inc.sync.aligned.u32 256;");
      float ka[56];
      const uint32_t nat = w4 * 3584 + (mi >> 1) * 128 + (r8 >> 2) * 1792 + (((2 * r8) & 7) + ((mi & 1) ^ (r8 >> 2))) * 16;
      {
        uint32_t X[28][4];
      mbar_wait(bars + B_X, 0);
      OBS(rel, 29);
#pragma unroll
      for (int k = 0; k < 28; k++)
        ldsm4(X[k], base + OFF_X + (k >> 2) * 8192 + (w4 * 16 + (mi >> 1) * 8 + r8) * 128 + (((2 * (k & 3) + (mi & 1)) ^ r8) << 4));
      if (lane == 0) mbar_arrive(bars + B_XF + X[27][3] * threadIdx.y);
      float c0[2][4] = {}, c1[2][4] = {};
      uint32_t one[8];
#pragma unroll
      for (int j = 0; j < 8; j++) asm volatile("{\n.reg .u32 y;\nmov.u32 y, %%tid.y;\nmad.lo.u32 %0, y, %1, 0x3f803f80;\n}" : "=r"(one[j]) : "r"(lane + j));
#pragma unroll
      for (int k = 0; k < 28; k++) {
        mma16816(c0[k & 1], X[k][0], one[(k & 1) * 4], X[k][1], one[(k & 1) * 4 + 1], X[k][0], X[k][1]);
        mma16816(c1[k & 1], X[k][2], one[(k & 1) * 4 + 2], X[k][3], one[(k & 1) * 4 + 3], X[k][2], X[k][3]);
      }
      float st[4];
#pragma unroll
      for (int j = 0; j < 2; j++) {
        st[j] = __shfl_sync(0xffffffffu, (g & 1) ? c0[0][2 * j + 1] + c0[1][2 * j + 1] : c0[0][2 * j] + c0[1][2 * j], (lane & 28) | (g >> 1));
        st[2 + j] = __shfl_sync(0xffffffffu, (g & 1) ? c1[0][2 * j + 1] + c1[1][2 * j + 1] : c1[0][2 * j] + c1[1][2 * j], (lane & 28) | (g >> 1));
      }
      const float m0 = st[1] * (1.0f / D_), m1 = st[3] * (1.0f / D_);
      const LnC l0 = ln_consts(m0, variance(m0, st[0])), l1 = ln_consts(m1, variance(m1, st[2]));
#pragma unroll
      for (int k = 0; k < 28; k++) {
        const uint32_t y = ln_apply(X[k][1], l0);
        X[k][0] = ln_apply(X[k][0], l0); X[k][1] = ln_apply(X[k][2], l1); X[k][2] = y; X[k][3] = ln_apply(X[k][3], l1);
        pin(X[k]);
      }
      OBS(rel, 122);
        float va[56];
        const uint32_t kst = base + OFF_KV + (2 + 2 * w4 + (mi & 1)) * 1792 + (mi >> 1) * 128 + r8 * 16;
        const uint32_t vst = base + OFF_KV + KV + 3584 + nat;
        auto put = [&](const float (&a)[56], uint32_t dst, int n) {
          stsm4(dst + n * 128, pack2(a[4 * n], a[4 * n + 1]), pack2(a[4 * n + 2], a[4 * n + 3]), pack2(a[4 * n + 4], a[4 * n + 5]), pack2(a[4 * n + 6], a[4 * n + 7])); };
        named_sync(3, 256);
        fresh(ka);
        OBS0(0, 8);
#pragma unroll
        for (int c = 0; c < 7; c++) stage<2>(ka, 0, p.db, c, 0, ok, trc, c == 0, rel && c, nohook, &X[c * 4]);
        fresh(va);
#pragma unroll
        for (int c = 7; c < 14; c++)
          stage<2>(va, 0, p.db, c & 7, c >> 3, ok, trc, c == 7, rel, [&](int k) {
            if (c > 7 && (c - 8) * 4 + k < 7) put(ka, kst, (c - 8) * 8 + k * 2);
            if (c == 9 && k == 3 && w4 == 3) named_arrive(11, 64); }, &X[(c - 7) * 4]);
        fresh(ka);
        OBS(rel, 9);
#pragma unroll
        for (int c = 14; c < 21; c++)
          stage<2>(ka, 0, p.db, c & 7, (c >> 3) & 1, ok, trc, c == 14, rel, [&](int k) {
            if (c > 14 && (c - 15) * 4 + k < 7) put(va, vst, (c - 15) * 8 + k * 2);
            if (c == 16 && k == 3 && w4 == 3) named_arrive(0, 64);
            if (c == 20 && k == 3 - HK) named_arrive(5, 256); }, &X[(c - 14) * 4]);
        smem_fence();
        wg_wait<0>();
        if (rel) mbar_arrive(bars + B_EMPTY + 4 * 8);
      }
      {
        uint32_t Q[8][4];
#pragma unroll
        for (int i = 0; i < 16; i++) {
          const int n = i - (i + 4) / 8;
#pragma unroll
          for (int h = 0; h < 2; h++) {
            const uint32_t v = pack2(ka[4 * n + 2 * h], ka[4 * n + 2 * h + 1]);
            Q[i >> 1][(i & 1) * 2 + h] = (i & 7) == 3 ? (t < 2 ? v : 0u) : ((i & 7) == 4 ? (t < 2 ? 0u : v) : v);
          }
        }
#pragma unroll
        for (int i = 0; i < 8; i++) pin(Q[i]);
        float Sc[4][40], O[4][16];
        mbar_wait(bars + B_HALO, 0);
        OBS(rel, 11);
#pragma unroll
        for (int hh = 0; hh < 4; hh++) fresh(Sc[hh]);
        wg_fence();
        named_sync(N_GO, 256);
#pragma unroll
        for (int k = 0; k < 2; k++)
#pragma unroll
          for (int hh = 0; hh < 4; hh++) {
            if (k == 1 && hh == 3) named_arrive(N_DONE, 256);
            wgmma_rs_n80<0>(Sc[hh], Q[hh * 2 + k], dlo(OFF_KV + (hh * 7 / 2 + 2 * k) * 128, 128), p.dk, k);
          }
        wg_commit();
        const bool e0 = 2 * t > g, e1 = 2 * t + 1 > g;
        const uint32_t em = (e0 ? 0xffffu : 0u) | (e1 ? 0xffff0000u : 0u);
        uint32_t L[4][2], M[6];
#pragma unroll
        for (int j = 0; j < 5; j++) { M[j] = j == w4 ? em : (j == w4 + 1 ? ~em : 0u); asm volatile("" : "+r"(M[j])); }
        M[5] = threadIdx.y;
        const uint32_t meta = 0x88dddd88u + M[5];
        wg_wait<0>();
        OBS(rel, 12);
        const uint32_t edge = mt == 0 ? em : 0u;
        auto pick = [&](int w) {
#pragma unroll
          for (int hh = 0; hh < 4; hh++)
#pragma unroll
            for (int h = 0; h < 2; h++) {
              const int i = (2 * w + h) * 4 + 2 * h;
              const uint32_t v = pack2(e0 ? Sc[hh][i] : Sc[hh][i + 8], e1 ? Sc[hh][i + 1] : Sc[hh][i + 9]);
              L[hh][h] = hfma2(v, 0x3e423e42u, hmul2(v, 0xb9f7b9f7u));
              if (w == 0) L[hh][h] = (L[hh][h] & ~edge) | (0xce6ece6eu & edge);
              asm volatile("" : "+r"(L[hh][h]));
            }
        };
        if (w4 == 0) pick(0); else if (w4 == 1) pick(1); else if (w4 == 2) pick(2); else pick(3);
        uint32_t A[4][3][4], mx[4];
        float P[8][2], sm[8];
#pragma unroll
        for (int hh = 0; hh < 4; hh++) mx[hh] = hmax2(__byte_perm(L[hh][0], L[hh][1], 0x5410), __byte_perm(L[hh][0], L[hh][1], 0x7632));
        const uint32_t x1 = 1 + ((mx[0] | mx[1] | mx[2] | mx[3]) & M[5]);
#pragma unroll
        for (int hh = 0; hh < 4; hh++) mx[hh] = hmax2(mx[hh], __shfl_xor_sync(0xffffffffu, mx[hh], x1));
#pragma unroll
        for (int hh = 0; hh < 4; hh++) mx[hh] = hmax2(mx[hh], __shfl_xor_sync(0xffffffffu, mx[hh], 2));
        uint32_t x2 = 0;
#pragma unroll
        for (int i = 0; i < 8; i++) {
          const float m = (i & 1 ? bf_hi(mx[i >> 1]) : bf_lo(mx[i >> 1])) * -LOG2E;
          P[i][0] = ex2_fast(fmaf(bf_lo(L[i >> 1][i & 1]), LOG2E, m)); P[i][1] = ex2_fast(fmaf(bf_hi(L[i >> 1][i & 1]), LOG2E, m));
          sm[i] = P[i][0] + P[i][1];
          x2 |= __float_as_uint(sm[i]);
        }
        x2 = 1 + (x2 & M[5]);
#pragma unroll
        for (int i = 0; i < 8; i++) sm[i] += __shfl_xor_sync(0xffffffffu, sm[i], x2);
#pragma unroll
        for (int i = 0; i < 8; i++) sm[i] += __shfl_xor_sync(0xffffffffu, sm[i], 2);
#pragma unroll
        for (int i = 0; i < 8; i++) {
          const float inv = rcp_fast(sm[i]);
          const uint32_t pp = pack2(P[i][0] * inv, P[i][1] * inv);
#pragma unroll
          for (int j = 0; j < 6; j++) A[i >> 1][j >> 1][(j & 1) * 2 + (i & 1)] = pp & M[j < 4 ? j : 9 - j];
        }
#pragma unroll
        for (int hh = 0; hh < 4; hh++) fresh(O[hh]);
#pragma unroll
        for (int i = 0; i < 12; i++) pin(A[i / 3][i % 3]);
        OBS(rel, 13);
        mbar_wait(bars + B_HALO + 8, 0);
        OBS(rel, 31);
        named_sync(N_GO, 256);
        wg_fence();
        const uint32_t ost = base + OFF_U + nat;
        auto opair = [&](int m, int h2) {
          const int hb2 = m / 7 * 2, r = m % 7;
          if (r < 3) return pack2(O[hb2][4 * r + h2], O[hb2][4 * r + h2 + 1]);
          if (r == 3) return pack2(t < 2 ? O[hb2][12 + h2] : O[hb2 + 1][h2], t < 2 ? O[hb2][13 + h2] : O[hb2 + 1][h2 + 1]);
          return pack2(O[hb2 + 1][4 * (r - 3) + h2], O[hb2 + 1][4 * (r - 3) + h2 + 1]);
        };
        auto oput = [&](int n) { stsm4(ost + n * 128, opair(n, 0), opair(n, 2), opair(n + 1, 0), opair(n + 1, 2)); };
        auto pv = [&](int hh, int j) { wgmma_sp_n32(O[hh], A[hh][j], dlo(OFF_KV + KV + hh * 7 / 2 * 128 + (j ? j + 1 : 0) * 3584, 1792), p.db, meta, j); };
#pragma unroll
        for (int i = 0; i < 12; i++) { if (i == 10) named_arrive(N_DONE, 256); pv(i & 3, i >> 2); }
        wg_commit();
        OBS(rel, 19);
        wg_wait<0>();
        OBS(rel, 21);
#pragma unroll
        for (int n = 0; n < 14; n += 2) oput(n);
        smem_fence();
        __syncwarp();
        OBS(rel, 14);
        if (elect()) {
          wait_until(clock() + w4 * PS_O);
          store_paced(g_scr + (G_O + mt * 8 + w4 * 2) * GRP + dt * 1792, GRP, base + OFF_U + w4 * 3584, 1792, 2, 4 * PS_O);
          publish(C_O + mt);
        }
        OBS(rel, 120);
        __syncwarp();
      }
      named_sync(8, 256);
      fresh(ka);
      OBS0(49, 25);
#pragma unroll
      for (int c = 49; c < 56; c++) stage<0>(ka, p.dx, p.db, c & 7, 0, ok, trc, c == 49, false, nohook);
      wg_wait<0>();
      OBS(rel, 27);
#pragma unroll
      for (int i = 0; i < 8; i++) {
        const float* a = ka + (i >> 1) * 16 + (i & 1) * 2;
        const uint32_t dst = (sx ^ ((i & 1) * 64)) + i * 2048, v0 = pack2(a[0], a[1]), v1 = pack2(a[4], a[5]);
        if (i < 6) sts128(dst, v0, v1, pack2(a[8], a[9]), pack2(a[12], a[13])); else sts64(dst, __uint_as_float(v0), __uint_as_float(v1));
      }
      named_arrive(12 + w4, 64);
      OBS(rel, 121);
    }
  }
}

typedef CUresult (*EncFn)(CUtensorMap*, CUtensorMapDataType, cuuint32_t, void*, const cuuint64_t*, const cuuint64_t*, const cuuint32_t*,
                          const cuuint32_t*, CUtensorMapInterleave, CUtensorMapSwizzle, CUtensorMapL2promotion, CUtensorMapFloatOOBfill);
void enc(EncFn f, CUtensorMap* m, const void* ptr, const cuuint64_t (&gd)[4], const cuuint64_t (&gs)[3], const cuuint32_t (&bx)[4], CUtensorMapSwizzle sw) {
  cuuint32_t es[4] = {1, 1, 1, 1};
  f(m, CU_TENSOR_MAP_DATA_TYPE_BFLOAT16, 4, (void*)ptr, gd, gs, bx, es, CU_TENSOR_MAP_INTERLEAVE_NONE, sw,
    CU_TENSOR_MAP_L2_PROMOTION_L2_128B, CU_TENSOR_MAP_FLOAT_OOB_FILL_NONE);
}
}

extern "C" void kernel_launch(void* const* d_in, const int* in_sizes, int n_in, void* d_out, int out_size) {
  (void)in_sizes; (void)n_in; (void)out_size;
  void* fp = nullptr;
  cudaDriverEntryPointQueryResult qr;
  cudaGetDriverEntryPoint("cuTensorMapEncodeTiled", &fp, cudaEnableDefault, &qr);
  EncFn f = (EncFn)fp;
  CUtensorMap m_w1, m_w2, m_b14, m_a8, m_b7, m_xt;
  void* scr = nullptr;
  cudaGetSymbolAddress(&scr, g_scr);
  enc(f, &m_w1, d_in[4], {F_, 16, 1, S_ / 16}, {F_ * 2, F_ * 2, F_ * 32}, {64, 8, 1, 8}, CU_TENSOR_MAP_SWIZZLE_128B);
  {
    cuuint64_t gd[5] = {64, 8, 2, S_ / 16, 7}, gs[4] = {D_ * 4, D_ * 2, D_ * 32, 128};
    cuuint32_t bx[5] = {64, 8, 2, 4, 7}, es[5] = {1, 1, 1, 1, 1};
    f(&m_xt, CU_TENSOR_MAP_DATA_TYPE_BFLOAT16, 5, d_in[0], gd, gs, bx, es, CU_TENSOR_MAP_INTERLEAVE_NONE, CU_TENSOR_MAP_SWIZZLE_128B,
      CU_TENSOR_MAP_L2_PROMOTION_L2_128B, CU_TENSOR_MAP_FLOAT_OOB_FILL_NONE);
  }
  enc(f, &m_w2, d_in[6], {S_, 1, 1, F_}, {S_ * 2, S_ * 2, S_ * 2}, {64, 1, 1, 64}, CU_TENSOR_MAP_SWIZZLE_128B);
  enc(f, &m_b14, scr, {64, 56, 1, G_END}, {128, GRP, GRP}, {64, 14, 1, 8}, CU_TENSOR_MAP_SWIZZLE_NONE);
  enc(f, &m_b7, scr, {64, 56, 1, G_END}, {128, GRP, GRP}, {64, 7, 1, 8}, CU_TENSOR_MAP_SWIZZLE_NONE);
  enc(f, &m_a8, scr, {64, 56, 1, G_END}, {128, GRP, GRP}, {64, 8, 1, 8}, CU_TENSOR_MAP_SWIZZLE_NONE);
  Params p;
  p.x = (const unsigned char*)d_in[0]; p.wqkv = (const unsigned char*)d_in[1]; p.wo = (const unsigned char*)d_in[2];
  p.w1 = (const unsigned char*)d_in[4]; p.b1 = (const unsigned short*)d_in[5];
  p.w2 = (const unsigned char*)d_in[6]; p.b2 = (const unsigned short*)d_in[7];
  p.out = (unsigned char*)d_out;
  p.dw = 0x40000040u; p.dx = 64; p.db = 8; p.dk = 112;
#ifdef TUNE
  for (int i = 0; i < NTUNE; i++) p.tune[i] = tune_vals[i];
#endif
  cudaFuncSetAttribute(fused_kernel, cudaFuncAttributeMaxDynamicSharedMemorySize, SMEM_BYTES);
  fused_kernel<<<128, NTHREADS, SMEM_BYTES, cudaStreamPerThread>>>(p, m_w1, m_w2, m_b14, m_a8, m_b7, m_xt);
}
```

```cpp
#include <cuda_runtime.h>
#include <cuda.h>
#include <cuda_bf16.h>
#include <stdint.h>

template<int TA, int TB> __device__ __forceinline__ void wgmma_n112(float (&d)[56], uint32_t al, uint32_t ah, uint32_t bl, uint32_t bh, int sc) {
  asm volatile("{\n.reg .pred p;\n.reg .b64 a, b;\nsetp.ne.b32 p, %60, 0;\nmov.b64 a, {%56, %57};\nmov.b64 b, {%58, %59};\n"
    "wgmma.mma_async.sync.aligned.m64n112k16.f32.bf16.bf16 {%0, %1, %2, %3, %4, %5, %6, %7, %8, %9, %10, %11, %12, %13, %14, %15, %16, %17, %18, %19, %20, %21, %22, %23, %24, %25, %26, %27, %28, %29, %30, %31, %32, %33, %34, %35, %36, %37, %38, %39, %40, %41, %42, %43, %44, %45, %46, %47, %48, %49, %50, %51, %52, %53, %54, %55}, a, b, p, 1, 1, %61, %62;\n}\n"
    : "+f"(d[0]), "+f"(d[1]), "+f"(d[2]), "+f"(d[3]), "+f"(d[4]), "+f"(d[5]), "+f"(d[6]), "+f"(d[7]), "+f"(d[8]), "+f"(d[9]), "+f"(d[10]), "+f"(d[11]), "+f"(d[12]), "+f"(d[13]), "+f"(d[14]), "+f"(d[15]), "+f"(d[16]), "+f"(d[17]), "+f"(d[18]), "+f"(d[19]), "+f"(d[20]), "+f"(d[21]), "+f"(d[22]), "+f"(d[23]), "+f"(d[24]), "+f"(d[25]), "+f"(d[26]), "+f"(d[27]), "+f"(d[28]), "+f"(d[29]), "+f"(d[30]), "+f"(d[31]), "+f"(d[32]), "+f"(d[33]), "+f"(d[34]), "+f"(d[35]), "+f"(d[36]), "+f"(d[37]), "+f"(d[38]), "+f"(d[39]), "+f"(d[40]), "+f"(d[41]), "+f"(d[42]), "+f"(d[43]), "+f"(d[44]), "+f"(d[45]), "+f"(d[46]), "+f"(d[47]), "+f"(d[48]), "+f"(d[49]), "+f"(d[50]), "+f"(d[51]), "+f"(d[52]), "+f"(d[53]), "+f"(d[54]), "+f"(d[55])
    : "r"(al), "r"(ah), "r"(bl), "r"(bh), "r"(sc), "n"(TA), "n"(TB));
}

template<int TB> __device__ __forceinline__ void wgmma_rs_n80(float (&d)[40], const uint32_t (&a)[4], uint32_t bl, uint32_t bh, int sc) {
  asm volatile("{\n.reg .pred p;\n.reg .b64 b;\nsetp.ne.b32 p, %46, 0;\nmov.b64 b, {%44, %45};\n"
    "wgmma.mma_async.sync.aligned.m64n80k16.f32.bf16.bf16 {%0, %1, %2, %3, %4, %5, %6, %7, %8, %9, %10, %11, %12, %13, %14, %15, %16, %17, %18, %19, %20, %21, %22, %23, %24, %25, %26, %27, %28, %29, %30, %31, %32, %33, %34, %35, %36, %37, %38, %39}, {%40, %41, %42, %43}, b, p, 1, 1, %47;\n}\n"
    : "+f"(d[0]), "+f"(d[1]), "+f"(d[2]), "+f"(d[3]), "+f"(d[4]), "+f"(d[5]), "+f"(d[6]), "+f"(d[7]), "+f"(d[8]), "+f"(d[9]), "+f"(d[10]), "+f"(d[11]), "+f"(d[12]), "+f"(d[13]), "+f"(d[14]), "+f"(d[15]), "+f"(d[16]), "+f"(d[17]), "+f"(d[18]), "+f"(d[19]), "+f"(d[20]), "+f"(d[21]), "+f"(d[22]), "+f"(d[23]), "+f"(d[24]), "+f"(d[25]), "+f"(d[26]), "+f"(d[27]), "+f"(d[28]), "+f"(d[29]), "+f"(d[30]), "+f"(d[31]), "+f"(d[32]), "+f"(d[33]), "+f"(d[34]), "+f"(d[35]), "+f"(d[36]), "+f"(d[37]), "+f"(d[38]), "+f"(d[39])
    : "r"(a[0]), "r"(a[1]), "r"(a[2]), "r"(a[3]), "r"(bl), "r"(bh), "r"(sc), "n"(TB));
}

__device__ __forceinline__ void wgmma_sp_n32(float (&d)[16], const uint32_t (&a)[4], uint32_t bl, uint32_t bh, uint32_t meta, int sc) {
  asm volatile("{\n.reg .pred p;\n.reg .b64 b;\nsetp.ne.b32 p, %23, 0;\nmov.b64 b, {%20, %21};\n"
    "wgmma.mma_async.sp.sync.aligned.m64n32k32.f32.bf16.bf16 {%0, %1, %2, %3, %4, %5, %6, %7, %8, %9, %10, %11, %12, %13, %14, %15}, {%16, %17, %18, %19}, b, %22, 0, p, 1, 1, 1;\n}\n"
    : "+f"(d[0]), "+f"(d[1]), "+f"(d[2]), "+f"(d[3]), "+f"(d[4]), "+f"(d[5]), "+f"(d[6]), "+f"(d[7]), "+f"(d[8]), "+f"(d[9]), "+f"(d[10]), "+f"(d[11]), "+f"(d[12]), "+f"(d[13]), "+f"(d[14]), "+f"(d[15])
    : "r"(a[0]), "r"(a[1]), "r"(a[2]), "r"(a[3]), "r"(bl), "r"(bh), "r"(meta), "r"(sc));
}

template<int TB> __device__ __forceinline__ void wgmma_rs_n112(float (&d)[56], const uint32_t (&a)[4], uint32_t bl, uint32_t bh, int sc) {
  asm volatile("{\n.reg .pred p;\n.reg .b64 b;\nsetp.ne.b32 p, %62, 0;\nmov.b64 b, {%60, %61};\n"
    "wgmma.mma_async.sync.aligned.m64n112k16.f32.bf16.bf16 {%0, %1, %2, %3, %4, %5, %6, %7, %8, %9, %10, %11, %12, %13, %14, %15, %16, %17, %18, %19, %20, %21, %22, %23, %24, %25, %26, %27, %28, %29, %30, %31, %32, %33, %34, %35, %36, %37, %38, %39, %40, %41, %42, %43, %44, %45, %46, %47, %48, %49, %50, %51, %52, %53, %54, %55}, {%56, %57, %58, %59}, b, p, 1, 1, %63;\n}\n"
    : "+f"(d[0]), "+f"(d[1]), "+f"(d[2]), "+f"(d[3]), "+f"(d[4]), "+f"(d[5]), "+f"(d[6]), "+f"(d[7]), "+f"(d[8]), "+f"(d[9]), "+f"(d[10]), "+f"(d[11]), "+f"(d[12]), "+f"(d[13]), "+f"(d[14]), "+f"(d[15]), "+f"(d[16]), "+f"(d[17]), "+f"(d[18]), "+f"(d[19]), "+f"(d[20]), "+f"(d[21]), "+f"(d[22]), "+f"(d[23]), "+f"(d[24]), "+f"(d[25]), "+f"(d[26]), "+f"(d[27]), "+f"(d[28]), "+f"(d[29]), "+f"(d[30]), "+f"(d[31]), "+f"(d[32]), "+f"(d[33]), "+f"(d[34]), "+f"(d[35]), "+f"(d[36]), "+f"(d[37]), "+f"(d[38]), "+f"(d[39]), "+f"(d[40]), "+f"(d[41]), "+f"(d[42]), "+f"(d[43]), "+f"(d[44]), "+f"(d[45]), "+f"(d[46]), "+f"(d[47]), "+f"(d[48]), "+f"(d[49]), "+f"(d[50]), "+f"(d[51]), "+f"(d[52]), "+f"(d[53]), "+f"(d[54]), "+f"(d[55])
    : "r"(a[0]), "r"(a[1]), "r"(a[2]), "r"(a[3]), "r"(bl), "r"(bh), "r"(sc), "n"(TB));
}

namespace {
constexpr int S_ = 2048, D_ = 448, F_ = 1792;
constexpr int SLOT = 22528, BT = 14336;
constexpr int OFF_KV = 8 * SLOT;
constexpr int OFF_X = OFF_KV - 7 * 8192;
constexpr int KV = 10 * 1792;
constexpr int OFF_PART = OFF_KV + 2 * BT;
constexpr int OFF_U = OFF_KV + 10 * 3584;
constexpr int OFF_BAR = OFF_U + BT;
constexpr uint32_t base = 1024, bars = base + OFF_BAR;
constexpr int OFF_OBS = OFF_BAR + 256;
constexpr int SMEM_BYTES = OFF_OBS + 768;
#ifdef TUNE
#define TV(i) p.tune[i]
const char* tune_names[] = {"DLY_B", "DLY_X", "DLY_W", "TPW", "DLY_R", "PF0", "PACE1", "PACE2", "SY_H", "SY_U", "SY_B", "PS_H", "NP_H", "PH_H", "NP_U", "PH_U", "PFN", "PF1", "PACE0", "PFR", "PACER", "DLY_Q", "DLY_D", "DLY_E", "PQ", "PS_O", "PU0"};
int tune_vals[] = {1000, 1000, 3300, 210, 0, 1600, 420, 400, 800, 1400, 1000, 150, 3, 230, 0, 300, 0, 0, 350, 99, 350, 1500, 0, 900, 170, 90, 1200};
constexpr int NTUNE = 27;
#define DLY_B TV(0)
#define DLY_X TV(1)
#define DLY_W TV(2)
#define TPW TV(3)
#define DLY_R TV(4)
#define PF0 TV(5)
#define PACE1 TV(6)
#define PACE2 TV(7)
#define SY_H TV(8)
#define SY_U TV(9)
#define SY_B TV(10)
#define PS_H TV(11)
#define NP_H TV(12)
#define PH_H TV(13)
#define NP_U TV(14)
#define PH_U TV(15)
#define PFN TV(16)
#define PF1 TV(17)
#define PACE0 TV(18)
#define PFR TV(19)
#define PACER TV(20)
#define DLY_Q TV(21)
#define DLY_D TV(22)
#define DLY_E TV(23)
#define PQ TV(24)
#define PS_O TV(25)
#define PU0 TV(26)
#else
#ifndef DLY_B
#define DLY_B 1000
#endif
#ifndef DLY_X
#define DLY_X 1000
#endif
#ifndef DLY_W
#define DLY_W 3300
#endif
#ifndef TPW
#define TPW 210
#endif
#ifndef DLY_R
#define DLY_R 0
#endif
#ifndef PF0
#define PF0 1600
#endif
#ifndef PACE1
#define PACE1 420
#endif
#ifndef PACE2
#define PACE2 400
#endif
#ifndef SY_H
#define SY_H 800
#endif
#ifndef SY_U
#define SY_U 1400
#endif
#ifndef SY_B
#define SY_B 1000
#endif
#ifndef PS_H
#define PS_H 150
#endif
#ifndef NP_H
#define NP_H 3
#endif
#ifndef PH_H
#define PH_H 230
#endif
#ifndef NP_U
#define NP_U 0
#endif
#ifndef PH_U
#define PH_U 300
#endif
#ifndef PFN
#define PFN 0
#endif
#ifndef PF1
#define PF1 0
#endif
#ifndef PACE0
#define PACE0 350
#endif
#ifndef PFR
#define PFR 99
#endif
#ifndef PACER
#define PACER 350
#endif
#ifndef DLY_Q
#define DLY_Q 1500
#endif
#ifndef DLY_D
#define DLY_D 0
#endif
#ifndef DLY_E
#define DLY_E 900
#endif
#ifndef PQ
#define PQ 170
#endif
#ifndef PS_O
#define PS_O 90
#endif
#ifndef PU0
#define PU0 1200
#endif
#endif
#ifndef SA
#define SA 0
#endif
#ifndef SB
#define SB 6
#endif
#ifndef PVS
#define PVS 0
#endif
#ifndef UH
#define UH 1
#endif
#ifndef EARLY
#define EARLY 1
#endif
#ifndef WU
#define WU 0
#endif
#ifndef ANA
#define ANA 1
#endif
#ifndef HK
#define HK 1
#endif
#ifndef HE
#define HE 1
#endif
#ifdef DBG_OBS
__device__ int g_obs[128 * 128];
#ifdef OBS_NS
#define OBS_CLK "%%globaltimer_lo"
#else
#define OBS_CLK "%%clock"
#endif
#define OBS(c, i) asm volatile("{\n.reg .pred p;\n.reg .u32 k;\nsetp.ne.u32 p, %1, 0;\nmov.u32 k, " OBS_CLK ";\nsub.u32 k, k, %2;\n@p st.shared.u32 [%0], k;\n}" :: "r"(base + OFF_OBS + (i) * 4), "r"((uint32_t)(c)), "r"(tz) : "memory")
#else
#define OBS(c, i) do {} while (0)
#endif
constexpr int NTHREADS = 384;
constexpr float LOG2E = 1.4426950408889634f;

constexpr int GRP = 7168;
constexpr int G_H = 0, G_W = 256, G_U = G_W + 168, G_WO = G_U + 224, G_O = G_WO + 56, G_HALO = G_O + 256, G_END = G_HALO + 128;
constexpr int SCR_BYTES = G_END * GRP;
__device__ __align__(1024) unsigned char g_scr[SCR_BYTES];
constexpr int C_TICKET = 0, C_W = 1, C_H = 2, C_U = 4, C_W2 = 5, C_O = 8, C_HALO = 40, C_END = 168;
__device__ __align__(128) unsigned g_cnt[C_END * 32];

__device__ __forceinline__ uint32_t smem_u32(const void* p) { return (uint32_t)__cvta_generic_to_shared(p); }
__device__ __forceinline__ void mbar_init(uint32_t bar, uint32_t cnt) { asm volatile("mbarrier.init.shared::cta.b64 [%0], %1;" :: "r"(bar), "r"(cnt)); }
__device__ __forceinline__ void mbar_expect_tx(uint32_t bar, uint32_t bytes) { asm volatile("mbarrier.arrive.expect_tx.shared::cta.b64 _, [%0], %1;" :: "r"(bar), "r"(bytes) : "memory"); }
__device__ __forceinline__ void mbar_arrive(uint32_t bar) { asm volatile("mbarrier.arrive.shared::cta.b64 _, [%0];" :: "r"(bar) : "memory"); }
__device__ __forceinline__ void mbar_wait(uint32_t bar, uint32_t parity) {
  asm volatile("{\n.reg .pred p;\n.reg .u32 n;\nmov.u32 n, 0;\nLAB_WAIT:\n"
               "mbarrier.try_wait.parity.shared::cta.b64 p, [%0], %1;\n@p bra DONE;\n"
               "add.u32 n, n, 1;\nsetp.lt.u32 p, n, 4000000;\n@p bra LAB_WAIT;\ntrap;\nDONE:\n}" :: "r"(bar), "r"(parity) : "memory");
}
__device__ __forceinline__ void mbar_wait_u(uint32_t bar, uint32_t parity) {
  asm volatile("{\n.reg .pred p;\nLAB_WAIT:\nmbarrier.try_wait.parity.shared::cta.b64 p, [%0], %1;\n@!p bra LAB_WAIT;\n}" :: "r"(bar), "r"(parity) : "memory");
}
__device__ __forceinline__ uint32_t mbar_try(uint32_t bar, uint32_t parity) {
  uint32_t ok;
  asm volatile("{\n.reg .pred p;\nmbarrier.test_wait.parity.shared::cta.b64 p, [%1], %2;\nselp.u32 %0, 1, 0, p;\n}" : "=r"(ok) : "r"(bar), "r"(parity) : "memory");
  return ok;
}
__device__ __forceinline__ void tma4d(uint32_t dst, const CUtensorMap* m, int c0, int c1, int c3, uint32_t bar) {
  asm volatile("cp.async.bulk.tensor.4d.shared::cluster.global.mbarrier::complete_tx::bytes [%0], [%1, {%3, %4, %6, %5}], [%2];"
               :: "r"(dst), "l"(m), "r"(bar), "r"(c0), "r"(c1), "r"(c3), "r"(0) : "memory");
}
__device__ __forceinline__ void tma_store(const CUtensorMap* m, int c1, int c3, uint32_t src) {
  asm volatile("cp.async.bulk.tensor.4d.global.shared::cta.bulk_group [%0, {%4, %2, %4, %3}], [%1];" :: "l"(m), "r"(src), "r"(c1), "r"(c3), "r"(0) : "memory");
}
__device__ __forceinline__ void bulk_g2s(uint32_t dst, const void* src, uint32_t bytes, uint32_t bar) {
  asm volatile("cp.async.bulk.shared::cluster.global.mbarrier::complete_tx::bytes [%0], [%1], %2, [%3];" :: "r"(dst), "l"(src), "r"(bytes), "r"(bar) : "memory");
}
__device__ __forceinline__ void bulk_s2g(void* dst, uint32_t src, uint32_t bytes) {
  asm volatile("cp.async.bulk.global.shared::cta.bulk_group [%0], [%1], %2;" :: "l"(dst), "r"(src), "r"(bytes) : "memory");
}
__device__ __forceinline__ void wg_fence() { asm volatile("wgmma.fence.sync.aligned;" ::: "memory"); }
__device__ __forceinline__ void wg_commit() { asm volatile("wgmma.commit_group.sync.aligned;" ::: "memory"); }
template <int N> __device__ __forceinline__ void wg_wait() { asm volatile("wgmma.wait_group.sync.aligned %0;" :: "n"(N) : "memory"); }
__device__ __forceinline__ void proxy_fence() { asm volatile("fence.proxy.async.global;" ::: "memory"); }
#ifndef LIGHT
#define LIGHT 1
#endif
__device__ __forceinline__ void smem_fence() {
  if (LIGHT == 2) return;
  if (LIGHT) asm volatile("mbarrier.init.shared::cta.b64 [%0], 1;" :: "r"(base + OFF_BAR + 248) : "memory");
  else asm volatile("fence.proxy.async.shared::cta;" ::: "memory");
}
__device__ __forceinline__ uint32_t gtime() { uint32_t v; asm volatile("mov.u32 %0, %%globaltimer_lo;" : "=r"(v)); return v; }
__device__ __forceinline__ void publish(int i, bool timed = false) {
  asm volatile("cp.async.bulk.commit_group;" ::: "memory");
  if (timed) asm volatile("red.relaxed.gpu.global.max.u32 [%0], %1;" :: "l"(&g_cnt[i * 32 + 1]), "r"(gtime()) : "memory");
  asm volatile("cp.async.bulk.wait_group 0;" ::: "memory");
  asm volatile("red.relaxed.gpu.global.inc.u32 [%0], 0xffffffff;" :: "l"(&g_cnt[i * 32]) : "memory");
}
__device__ __forceinline__ void spin_ge(int i, unsigned target) {
  asm volatile("{\n.reg .pred p;\n.reg .u32 n, v;\nmov.u32 n, 0;\nLAB_SPIN:\n"
               "ld.relaxed.gpu.global.u32 v, [%0];\nsetp.ge.u32 p, v, %1;\n@p bra DONE;\n"
               "add.u32 n, n, 1;\nsetp.lt.u32 p, n, 4000000;\n@p bra LAB_SPIN;\ntrap;\nDONE:\n}" :: "l"(&g_cnt[i * 32]), "r"(target) : "memory");
}
__device__ __forceinline__ unsigned ld_relaxed(int i) { unsigned v; asm volatile("ld.relaxed.gpu.global.u32 %0, [%1];" : "=r"(v) : "l"(&g_cnt[i * 32]) : "memory"); return v; }
__device__ __forceinline__ bool elect() {
  uint32_t r; asm volatile("{\n.reg .pred p;\nelect.sync _|p, 0xffffffff;\nselp.u32 %0, 1, 0, p;\n}" : "=r"(r)); return r != 0;
}
__device__ __forceinline__ void wait_until(uint32_t tn) { while ((int)(clock() - tn) < 0) __nanosleep(20); }
__device__ __forceinline__ void store_paced(unsigned char* dst, int dstep, uint32_t src, int sstep, int n, int gap, int bytes = 1792) {
  uint32_t tn = clock();
#pragma unroll 1
  for (int i = 0; i < n; i++) { wait_until(tn); bulk_s2g(dst, src, bytes); dst += dstep; src += sstep; tn += gap; }
}
__device__ __forceinline__ uint4 lds128(uint32_t a) { uint4 v; asm volatile("ld.shared.v4.u32 {%0,%1,%2,%3}, [%4];" : "=r"(v.x), "=r"(v.y), "=r"(v.z), "=r"(v.w) : "r"(a) : "memory"); return v; }
__device__ __forceinline__ uint32_t lds32(uint32_t a) { uint32_t v; asm volatile("ld.shared.u32 %0, [%1];" : "=r"(v) : "r"(a) : "memory"); return v; }
__device__ __forceinline__ void sts128(uint32_t p, uint32_t a, uint32_t b, uint32_t c, uint32_t d) { asm volatile("st.shared.v4.u32 [%0], {%1,%2,%3,%4};" :: "r"(p), "r"(a), "r"(b), "r"(c), "r"(d) : "memory"); }
__device__ __forceinline__ void sts64(uint32_t p, float a, float b) { asm volatile("st.shared.v2.f32 [%0], {%1,%2};" :: "r"(p), "f"(a), "f"(b) : "memory"); }
__device__ __forceinline__ void named_sync(int id, int n) { asm volatile("bar.sync %0, %1;" :: "r"(id), "r"(n) : "memory"); }
__device__ __forceinline__ void named_arrive(int id, int n) { asm volatile("bar.arrive %0, %1;" :: "r"(id), "r"(n) : "memory"); }
__device__ __forceinline__ constexpr uint32_t dlo(uint32_t off, uint32_t lbo) { return ((base + off) >> 4) | (lbo >> 4 << 16); }
__device__ __forceinline__ uint32_t pack2(float lo, float hi) { uint32_t r; asm("cvt.rn.bf16x2.f32 %0, %1, %2;" : "=r"(r) : "f"(hi), "f"(lo)); return r; }
__device__ __forceinline__ float bf_lo(uint32_t v) { return __uint_as_float(v << 16); }
__device__ __forceinline__ float bf_hi(uint32_t v) { return __uint_as_float(v & 0xffff0000u); }
__device__ __forceinline__ float rbf(float x) { return bf_lo(pack2(x, 0.f)); }
__device__ __forceinline__ uint32_t hsub2(uint32_t a, uint32_t b) { uint32_t r; asm("sub.rn.bf16x2 %0, %1, %2;" : "=r"(r) : "r"(a), "r"(b)); return r; }
__device__ __forceinline__ uint32_t hadd2(uint32_t a, uint32_t b) { uint32_t r; asm("add.rn.bf16x2 %0, %1, %2;" : "=r"(r) : "r"(a), "r"(b)); return r; }
__device__ __forceinline__ uint32_t hmax2(uint32_t a, uint32_t b) { uint32_t r; asm("max.bf16x2 %0, %1, %2;" : "=r"(r) : "r"(a), "r"(b)); return r; }
__device__ __forceinline__ uint32_t hmul2(uint32_t a, uint32_t b) { uint32_t r; asm("mul.rn.bf16x2 %0, %1, %2;" : "=r"(r) : "r"(a), "r"(b)); return r; }
__device__ __forceinline__ uint32_t hfma2(uint32_t a, uint32_t b, uint32_t c) { uint32_t r; asm("fma.rn.bf16x2 %0, %1, %2, %3;" : "=r"(r) : "r"(a), "r"(b), "r"(c)); return r; }
__device__ __forceinline__ float tanh_fast(float x) { float r; asm("tanh.approx.f32 %0, %1;" : "=f"(r) : "f"(x)); return r; }
__device__ __forceinline__ float rcp_fast(float x) { float r; asm("rcp.approx.ftz.f32 %0, %1;" : "=f"(r) : "f"(x)); return r; }
__device__ __forceinline__ float ex2_fast(float x) { float r; asm("ex2.approx.ftz.f32 %0, %1;" : "=f"(r) : "f"(x)); return r; }
__device__ __forceinline__ void mma16816(float (&c)[4], uint32_t a0, uint32_t a1, uint32_t a2, uint32_t a3, uint32_t b0, uint32_t b1) {
  asm volatile("mma.sync.aligned.m16n8k16.row.col.f32.bf16.bf16.f32 {%0,%1,%2,%3}, {%4,%5,%6,%7}, {%8,%9}, {%0,%1,%2,%3};"
               : "+f"(c[0]), "+f"(c[1]), "+f"(c[2]), "+f"(c[3]) : "r"(a0), "r"(a1), "r"(a2), "r"(a3), "r"(b0), "r"(b1));
}
__device__ __forceinline__ void ldsm4(uint32_t (&r)[4], uint32_t addr) {
  asm volatile("ldmatrix.sync.aligned.m8n8.x4.shared.b16 {%0,%1,%2,%3}, [%4];" : "=r"(r[0]), "=r"(r[1]), "=r"(r[2]), "=r"(r[3]) : "r"(addr) : "memory");
}
__device__ __forceinline__ void stsm4(uint32_t addr, uint32_t a, uint32_t b, uint32_t c, uint32_t d) {
  asm volatile("stmatrix.sync.aligned.m8n8.x4.shared.b16 [%0], {%1,%2,%3,%4};" :: "r"(addr), "r"(a), "r"(b), "r"(c), "r"(d) : "memory");
}
__device__ __forceinline__ void stsm2(uint32_t addr, uint32_t a, uint32_t b) {
  asm volatile("stmatrix.sync.aligned.m8n8.x2.shared.b16 [%0], {%1,%2};" :: "r"(addr), "r"(a), "r"(b) : "memory");
}
__device__ __forceinline__ void load_row(uint32_t (&r)[14], const unsigned char* p, int t) {
#pragma unroll
  for (int i = 0; i < 3; i++)
    asm volatile("ld.global.nc.L1::no_allocate.v4.u32 {%0,%1,%2,%3}, [%4];" : "=r"(r[4 * i]), "=r"(r[4 * i + 1]), "=r"(r[4 * i + 2]), "=r"(r[4 * i + 3]) : "l"(p + i * 64 + t * 16));
  asm volatile("ld.global.nc.L1::no_allocate.v2.u32 {%0,%1}, [%2];" : "=r"(r[12]), "=r"(r[13]) : "l"(p + 192 + t * 8));
}
__device__ __forceinline__ void lds_row(uint32_t* r, uint32_t a, int t) {
#pragma unroll
  for (int i = 0; i < 3; i++) { const uint4 v = lds128(a + i * 64 + t * 16); r[4 * i] = v.x; r[4 * i + 1] = v.y; r[4 * i + 2] = v.z; r[4 * i + 3] = v.w; }
  asm volatile("ld.shared.v2.u32 {%0,%1}, [%2];" : "=r"(r[12]), "=r"(r[13]) : "r"(a + 192 + t * 8) : "memory");
}

struct LnC { uint32_t m, rh, rl; float r; };
__device__ __forceinline__ LnC ln_consts(float mean, float var) {
  float sd;
  asm("sqrt.approx.ftz.f32 %0, %1;" : "=f"(sd) : "f"(rbf(rbf(var) + 1e-5f)));
  const float r = rcp_fast(rbf(sd)), rh = rbf(r);
  return {pack2(mean, mean), pack2(rh, rh), pack2(r - rh, r - rh), r};
}
__device__ __forceinline__ float variance(float mean, float sq) { return fmaxf(fmaf(-mean, mean, sq * (1.0f / D_)), 0.f); }
__device__ __forceinline__ uint32_t ln_apply(uint32_t x, const LnC& c) { const uint32_t d = hsub2(x, c.m); return hfma2(d, c.rh, hmul2(d, c.rl)); }

template <int N> __device__ __forceinline__ void fresh(float (&a)[N]) {
#pragma unroll
  for (int i = 0; i < N; i++) asm volatile("" : "=f"(a[i]));
}
__device__ __forceinline__ void pin(uint32_t (&a)[4]) { asm volatile("" : "+r"(a[0]), "+r"(a[1]), "+r"(a[2]), "+r"(a[3])); }
constexpr int B_EMPTY = 64, B_F0 = 128, B_F1 = 136, B_F2 = 144, B_F3 = 152, B_HALO = 160, B_RT = 176, B_RES = 184, B_TS = 192, B_F1B = 200, B_XF = 208, B_X = 216, S_FLAG = 224;
constexpr int N_GO = 6, N_DONE = 7;
__device__ __forceinline__ void watch_flag(int slot, int i, unsigned target) {
  asm volatile("{\n.reg .pred p;\n.reg .u32 n, v, t;\nmov.u32 n, 0;\nLAB_SPIN:\n"
               "ld.relaxed.gpu.global.v2.u32 {v, t}, [%1];\nsetp.ge.u32 p, v, %2;\n@p st.volatile.shared.v2.u32 [%0], {v, t};\n"
               "ld.volatile.shared.u32 v, [%0];\nsetp.ne.u32 p, v, 0;\n@p bra DONE;\n"
               "add.u32 n, n, 1;\nsetp.lt.u32 p, n, 4000000;\n@p bra LAB_SPIN;\ntrap;\nDONE:\n}" :: "r"(bars + S_FLAG + slot * 8), "l"(&g_cnt[i * 32]), "r"(target) : "memory");
}
__device__ __forceinline__ void wait_flag(int slot, int delay) {
  uint32_t v, last;
  do asm volatile("ld.volatile.shared.v2.u32 {%0, %1}, [%2];" : "=r"(v), "=r"(last) : "r"(bars + S_FLAG + slot * 8) : "memory"); while (!v);
  while (gtime() - last < (uint32_t)delay);
}
__device__ __forceinline__ void arrive_if(int id, bool on) {
  asm volatile("{\n.reg .pred p;\nsetp.ne.u32 p, %1, 0;\n@p bar.arrive %0, 256;\n}" :: "r"(id), "r"((uint32_t)on) : "memory");
}
template <int TA, class Hook>
__device__ __forceinline__ void stage(float (&acc)[56], uint32_t ah, uint32_t bh, int sb, uint32_t par, uint32_t& ok, int& g_tr, bool first, bool rel, Hook hook, const uint32_t (*X)[4] = nullptr) {
  if (!ok) { if (WU) mbar_wait_u(bars + sb * 8, par); else mbar_wait(bars + sb * 8, par); }
  wg_fence();
#pragma unroll
  for (int k = 0; k < 4; k++) {
    if constexpr (TA == 2) wgmma_rs_n112<1>(acc, X[k], dlo(sb * SLOT + 8192 + k * 3584, 1792), bh, k || !first);
    else wgmma_n112<TA, 1>(acc, dlo(sb * SLOT + k * (TA ? 2048 : 256), TA ? 8192 : 128), ah, dlo(sb * SLOT + 8192 + k * 3584, 1792), bh, k || !first);
    if (k == 1) ok = mbar_try(bars + ((sb + 1) & 7) * 8, sb == 7 ? par ^ 1 : par);
    hook(k);
  }
  wg_commit();
  wg_wait<1>();
#if DBG_TRACE == 2
  { const uint32_t tz = 0; OBS((threadIdx.x & 127) == 0, g_tr); g_tr++; }
#endif
  if (rel) mbar_arrive(bars + B_EMPTY + ((sb + 7) & 7) * 8);
}

struct Params {
  const unsigned char *x, *wqkv, *wo, *w1, *w2;
  const unsigned short *b1, *b2;
  unsigned char* out;
  uint32_t dw, dx, db, dk;
#ifdef TUNE
  int tune[NTUNE];
#endif
};

__global__ void __launch_bounds__(NTHREADS, 1)
fused_kernel(const Params p, const __grid_constant__ CUtensorMap m_w1, const __grid_constant__ CUtensorMap m_w2, const __grid_constant__ CUtensorMap m_b14,
             const __grid_constant__ CUtensorMap m_a8, const __grid_constant__ CUtensorMap m_b7, const __grid_constant__ CUtensorMap m_xt) {
  extern __shared__ __align__(1024) unsigned char smem_raw[];
  const uint32_t t0 = clock();
#ifdef DBG_OBS
  uint32_t tz; asm volatile("mov.u32 %0, " OBS_CLK ";" : "=r"(tz));
#endif
  const int tid = threadIdx.x, lane = tid & 31, b = blockIdx.x;
  const int g = lane >> 2, t = lane & 3, r8 = lane & 7, mi = lane >> 3;
  uint32_t H[14];
  if (tid < 128) load_row(H, p.x + (b * 16 + g) * (D_ * 2) + (tid >> 5) * 224, t);
  const int warp = __shfl_sync(0xffffffffu, tid >> 5, 0);
  const int dt = b & 3, mt = b >> 2;
  const bool g1 = b < 112;
  const int ft = mt, d1 = dt;
  if (warp >= 8) {
    if (warp == 8) {
      if (elect()) {
        if (smem_u32(smem_raw) != base) asm volatile("trap;");
#pragma unroll
        for (int i = 0; i < 28; i++) mbar_init(bars + i * 8, i * 8 == B_XF ? 8 : 1);
        sts128(bars + S_FLAG, 0, 0, 0, 0);
        asm volatile("fence.mbarrier_init.release.cluster;" ::: "memory");
      }
      __syncwarp();
      named_arrive(12, 160); named_arrive(13, 160);
    }
    named_sync(15, 128);
    asm volatile("setmaxnreg.dec.sync.aligned.u32 80;");
    if (warp == 8) {
      unsigned tk = 0;
      if (elect()) {
        wait_until(t0 + DLY_B);
        mbar_expect_tx(bars + B_F2, GRP);
        bulk_g2s(base + OFF_U, p.x + (b * 2 + 1) * GRP, GRP, bars + B_F2);
        asm volatile("prefetch.tensormap [%0];" :: "l"(&m_xt) : "memory");
        wait_until(t0 + DLY_X);
        mbar_expect_tx(bars + B_X, 7 * 8192);
        asm volatile("cp.async.bulk.tensor.5d.shared::cluster.global.mbarrier::complete_tx::bytes [%0], [%1, {%4, %4, %4, %3, %4}], [%2];"
                     :: "r"(base + OFF_X), "l"(&m_xt), "r"(bars + B_X), "r"(mt * 4), "r"(0) : "memory");
        wait_until(t0 + DLY_D);
        asm volatile("prefetch.tensormap [%0];" :: "l"(&m_w1) : "memory");
        asm volatile("prefetch.tensormap [%0];" :: "l"(&m_b14) : "memory");
        if (g1) {
#pragma unroll 1
          for (int c = 0; c < 8; c++) {
            wait_until(t0 + DLY_W + c * TPW);
            if (c == 6) mbar_wait(bars + B_XF, 0);
            tma4d(base + c * SLOT, &m_w1, ft * 64, 0, c * 8, bars + c * 8);
          }
        } else {
          const int n = dt < 3 ? 16 : 8;
          mbar_expect_tx(bars + B_RT, n * 5376);
#pragma unroll 1
          for (int i = 0; i < n; i++) { wait_until(t0 + DLY_Q + i * PQ); bulk_g2s(base + i * 5376, p.wqkv + ((mt & 3) * 56 + dt * 16 + i) * 5376, 5376, bars + B_RT); }
        }
#pragma unroll 1
        for (int r = g1 ? 1 : 4; r < 4; r++) {
#pragma unroll
          for (int s = 0; s < 8; s++) {
            mbar_wait_u(bars + B_EMPTY + s * 8, (r & 1) ^ 1);
            tma4d(base + s * SLOT, &m_w1, mt * 64, (r & 2) * 4, (r & 1) * 64 + s * 8, bars + s * 8);
          }
        }
        mbar_wait(bars + B_EMPTY + 5 * 8, 1);
        mbar_wait(bars + B_EMPTY + 5 * 8, 0);
        if (!g1) mbar_wait(bars + B_TS, 0);
#pragma unroll 1
        for (int r = 0; ; r++) {
#pragma unroll
          for (int j = 0; j < 8; j++) {
            const int s = (j + 5) & 7;
            mbar_wait_u(bars + B_EMPTY + s * 8, (r + (j < 3)) & 1);
            tma4d(base + s * SLOT, &m_w2, mt * 64, 0, r * 512 + j * 64, bars + s * 8);
            if (j == 3 && r == 3) goto w2_done;
          }
        }
        w2_done:
        mbar_wait(bars + B_F3, 0);
        OBS(1, 22);
#pragma unroll
        for (int s = 1; s < 8; s++) {
          mbar_wait_u(bars + B_EMPTY + s * 8, 1);
          tma4d(base + s * SLOT, &m_a8, 0, s * 8 - 8, G_O + mt * 8, bars + s * 8);
        }
        tk = atomicInc(&g_cnt[C_TICKET * 32], 0xffffffffu);
      }
      if (__any_sync(0xffffffffu, tk == 127)) {
#pragma unroll 1
        for (int i = lane; i < C_END; i += 32) *(uint2*)&g_cnt[i * 32] = make_uint2(0, 0);
      }
    } else if (warp == 9) {
      if (elect()) {
        if (ld_relaxed(C_H) + ld_relaxed(C_H + 1) > 256) asm volatile("trap;");
        {
          wait_until(t0 + DLY_E);
          asm volatile("prefetch.tensormap [%0];" :: "l"(&m_b7) : "memory");
          asm volatile("prefetch.tensormap [%0];" :: "l"(&m_w2) : "memory");
          asm volatile("prefetch.tensormap [%0];" :: "l"(&m_a8) : "memory");
        }
        uint32_t bytes = SLOT;
#pragma unroll 1
        for (int r = g1 ? 0 : 4; r < 11; r++) {
#pragma unroll
          for (int s = 0; s < 8; s++) {
            if (s == 0 && r == 0) { if (NP_H == 0) watch_flag(0, C_H, 128); wait_flag(0, SY_H); OBS(1, 16); }
            if (s == 0 && (r == 2 || r == 4)) { mbar_wait(bars + B_F0 + (r >> 2) * 8, 0); OBS(1, 16 + (r >> 1)); if (r == 4) bytes = BT; }
            if (s == 5 && r == 0) mbar_wait(bars + B_XF, 0);
            if (s == 7 && r == 4) mbar_wait(bars + B_F1B, 0);
            if (s == 5 && r == 6) { wait_flag(1, SY_U); OBS(1, 20); bytes = SLOT; }
            if (s) mbar_wait_u(bars + B_EMPTY + s * 8, (r & 1) ^ 1); else mbar_wait(bars + B_EMPTY, (r & 1) ^ 1);
#if DBG_TRACE == 1
            { const uint32_t tz = 0; OBS(1, 32 + r * 8 + s); }
#endif
            mbar_expect_tx(bars + s * 8, bytes);
            tma4d(base + s * SLOT + 8192, &m_b14, 0, dt * 14, r * 64 + s * 8, bars + s * 8);
          }
        }
      }
    } else if (warp == 10) {
      uint32_t tn = t0 + PF0;
      const unsigned char* src = p.w1 + (b + (b & ~7)) * 3584 + lane * 128;
#pragma unroll 1
      for (int i = 0; i < 32; i++) {
        if (i == PFR) {
#pragma unroll 1
          for (int j = 0; j < 3; j++) {
            wait_until(t0 + DLY_R + j * PACER);
            if (j * 32 + lane < 74) asm volatile("prefetch.global.L2 [%0];" :: "l"(p.wqkv + min(b * 74 + j * 32 + lane, 9407) * 128) : "memory");
          }
        }
        wait_until(tn);
        if (i == 8) src -= 16 * 458752 - 8 * 3584;
        if (i == 16) src = p.w2 + b * 3584 + lane * 128;
        if (lane < 28) asm volatile("prefetch.global.L2 [%0];" :: "l"(src) : "memory");
        __syncwarp();
        src += i < 16 ? 2 * 458752 : 458752;
        tn += i < PFN ? PACE0 : (i < 16 ? PACE1 : PACE2);
        if (i + 1 == PFN) tn = t0 + PF1;
      }
      watch_flag(1, C_U, 128);
      spin_ge(C_O + mt, 16);
      if (lane == 0) mbar_arrive(bars + B_F3);
    } else {
      unsigned char* dst = g_scr + (G_H + b) * GRP;
      asm volatile("" : "+l"(dst));
      named_sync(10, 160);
      smem_fence();
      if (elect()) { bulk_s2g(dst, base + OFF_KV, GRP); publish(C_H, true); OBS(1, 3); }
      named_sync(9, 160);
      smem_fence();
      if (elect()) {
        if (g1 && SY_B) { wait_flag(0, SY_B); store_paced(dst + 128 * GRP, 1792, base + OFF_KV + GRP, 1792, 4, PS_H); }
        else bulk_s2g(dst + 128 * GRP, base + OFF_KV + GRP, GRP);
        publish(C_H + 1);
        OBS(1, 4);
      }
      __syncwarp();
      if (g1) { spin_ge(C_H + 1, 128); if (lane == 0) mbar_arrive(bars + B_F0); }
      else {
        const int kg0 = (mt & 3) * 14 + dt * 4, nk = dt < 3 ? 4 : 2;
#pragma unroll 1
        for (int m = 0; m < 3; m++) {
          named_sync(m == 0 ? 14 : (m == 1 ? 10 : 9), 160);
          smem_fence();
          if (elect()) {
            if (m == 2) {
              mbar_expect_tx(bars + B_RT, nk * GRP);
#pragma unroll 1
              for (int i = 0; i < nk; i++) bulk_g2s(base + i * SLOT, p.wo + (kg0 + i) * GRP, GRP, bars + B_RT);
            }
            bulk_s2g(g_scr + (G_W + m * 56 + kg0) * GRP, base + (12 + m * 4) * GRP, nk * GRP);
            if (m != 1) publish(m ? C_W2 : C_W);
            OBS(m != 1, 5 + (m >> 1));
          }
          __syncwarp();
        }
      }
      spin_ge(C_W, 16);
      if (lane == 0) mbar_arrive(bars + B_F1);
      spin_ge(C_W2, 16);
      if (lane == 0) mbar_arrive(bars + B_F1B);
      if (mt == 0) {
#pragma unroll
        for (int i = 0; i < 14; i++) sts128(base + OFF_KV + (i / 7) * KV + (i % 7) * 512 + lane * 16, 0, 0, 0, 0);
        smem_fence();
        __syncwarp();
        if (lane < 2) mbar_arrive(bars + B_HALO + lane * 8);
      }
      const unsigned have = EARLY && mt > 0 ? ld_relaxed(C_HALO + b - 4) : 0;
      if (g1) {
        named_sync(14, 160);
        smem_fence();
        if (elect()) tma_store(&m_b7, d1 * 14, G_U + ft * 8, base + OFF_U);
        named_sync(10, 160);
        smem_fence();
        if (elect()) { tma_store(&m_b7, d1 * 14 + 7, G_U + ft * 8, base + OFF_U + GRP); publish(C_U, true); OBS(1, 7); }
        __syncwarp();
      }
#pragma unroll 1
      for (int i = 0; i < 2; i++) {
        unsigned char* hg = g_scr + (G_HALO + b) * GRP + i * 3584;
        named_sync(i ? 0 : 11, 64);
        smem_fence();
        if (mt < 31 && elect()) { bulk_s2g(hg, base + OFF_KV + i * KV + 8 * 1792, 3584); publish(C_HALO + b); }
        OBS(lane == 0, i ? 15 : 23);
        if (mt > 0) {
          if (have <= i) spin_ge(C_HALO + b - 4, i + 1);
          if (elect()) { mbar_expect_tx(bars + B_HALO + i * 8, 3584); bulk_g2s(base + OFF_KV + i * KV, hg - 4 * GRP, 3584, bars + B_HALO + i * 8); }
        }
        __syncwarp();
      }
    }
  } else {
    const int wg = warp >> 2, w4 = warp & 3;
    const bool rel = (tid & 127) == 0;
    named_sync(12 + wg, 160);
    if (wg) { mbar_wait(bars + B_F2, 0); lds_row(H, base + OFF_U + g * 896 + w4 * 224, t); }
    {
      const uint32_t part = base + OFF_PART + wg * 512 + g * 32, st = base + OFF_KV + wg * GRP + (w4 * 14 + mi) * 128 + r8 * 16;
#pragma unroll
      for (int ln = 0; ln < (ANA ? 1 : 2); ln++) {
        float s0 = 0.f, s1 = 0.f, q0 = 0.f, q1 = 0.f;
#pragma unroll
        for (int j = 0; j < 14; j++) { const float a = bf_lo(H[j]), c = bf_hi(H[j]); s0 += a; s1 += c; q0 = fmaf(a, a, q0); q1 = fmaf(c, c, q1); }
        s0 += s1; q0 += q1;
#pragma unroll
        for (int o = 1; o < 4; o <<= 1) { s0 += __shfl_xor_sync(0xffffffffu, s0, o); q0 += __shfl_xor_sync(0xffffffffu, q0, o); }
        if (t == 0) sts64(part + ln * 256 + w4 * 8, s0, q0);
        OBS(tid == 0 && ln == 0, 0);
        named_sync(1 + wg, 128);
        const uint4 u = lds128(part + ln * 256), v = lds128(part + ln * 256 + 16);
        const float mean = ((__uint_as_float(u.x) + __uint_as_float(u.z)) + (__uint_as_float(v.x) + __uint_as_float(v.z))) * (1.0f / D_);
        const float var = variance(mean, (__uint_as_float(u.y) + __uint_as_float(u.w)) + (__uint_as_float(v.y) + __uint_as_float(v.w)));
        const LnC l = ln_consts(mean, var);
#pragma unroll
        for (int j = 0; j < 14; j++) H[j] = ln_apply(H[j], l);
        if (ANA) {
          const LnC l2 = ln_consts((mean - bf_lo(l.m)) * l.r, var * l.r * l.r);
#pragma unroll
          for (int j = 0; j < 14; j++) H[j] = ln_apply(H[j], l2);
        }
      }
#pragma unroll
      for (int i = 0; i < 3; i++) stsm4(st + i * 512, H[4 * i], H[4 * i + 1], H[4 * i + 2], H[4 * i + 3]);
      stsm2(st + 1536, H[12], H[13]);
      named_arrive(10 - wg, 160);
      OBS(rel, 1 + wg);
    }
    uint32_t ok = 0;
    int trc = 0;
    auto nohook = [](int) {};
#ifdef DBG_OBS
#define OBS0(c, i) do { mbar_wait(bars + ((c) & 7) * 8, ((c) >> 3) & 1); ok = 1; OBS(rel, i); trc = (i) == 5 ? 32 : 64 + (c); } while (0)
#else
#define OBS0(c, i) ok = 0
#endif
    const uint32_t sx = base + OFF_KV + (tid & 127) * 16;
    if (wg == 0) {
      uint32_t hb[4], R[28];
#pragma unroll
      for (int i = 0; i < 4; i++)
        asm volatile("ld.relaxed.cta.global.u16 %0, [%1];" : "=r"(hb[i]) : "l"((i < 2 ? p.b1 + (g1 ? mt * 64 : 0) : p.b2 + mt * 64) + w4 * 16 + g + (i & 1) * 8) : "memory");
      mbar_wait(bars + B_X, 0);
#pragma unroll
      for (int i = 0; i < 8; i++) {
        const int h = i >> 2, j = i & 3, xi = h * 4 + (g >> 1), c = dt * 14 + (j < 3 ? 4 * j + t : 12 + (t >> 1));
        const uint4 v = lds128(base + OFF_X + (c >> 3) * 8192 + (w4 * 16 + (g & 1) * 8 + xi) * 128 + (((c ^ xi) & 7) << 4));
        if (j < 3) { R[h * 14 + 4 * j] = v.x; R[h * 14 + 4 * j + 1] = v.y; R[h * 14 + 4 * j + 2] = v.z; R[h * 14 + 4 * j + 3] = v.w; }
        else { R[h * 14 + 12] = t & 1 ? v.z : v.x; R[h * 14 + 13] = t & 1 ? v.w : v.y; }
      }
#pragma unroll
      for (int i = 0; i < 28; i++) asm volatile("" : "+r"(R[i]));
      if (lane == 0) mbar_arrive(bars + B_XF + R[27] * threadIdx.y);
      float acc[56];
      if (g1) {
#pragma unroll
        for (int i = 0; i < 56; i++) { acc[i] = bf_lo(hb[(i >> 1) & 1]); asm volatile("" : "+f"(acc[i])); }
        if (w4 < NP_H) { wait_until(clock() + w4 * PH_H); watch_flag(0, C_H, 128); }
        OBS0(0, 5);
#pragma unroll 1
        for (int r = 0; r < 4; r++)
#pragma unroll
          for (int c = 0; c < 8; c++) stage<1>(acc, p.dw, p.db, c, r & 1, ok, trc, false, rel && (c || r), [&](int k) { if (c == 7 && k == 3 - HK) arrive_if(3, r == 3); });
        wg_wait<0>();
        if (rel) mbar_arrive(bars + B_EMPTY + 7 * 8);
        OBS(rel, 6);
        const uint32_t us = base + OFF_U + (w4 * 2 + (mi & 1)) * 896 + (mi >> 1) * 128 + r8 * 16;
#pragma unroll
        for (int hf = 0; hf < 2; hf++) {
          uint32_t U[14];
#pragma unroll
          for (int j = 0; j < 14; j++) {
            const float a = acc[hf * 28 + 2 * j], c = acc[hf * 28 + 2 * j + 1];
            U[j] = pack2(fmaf(a, tanh_fast(a * fmaf(a * a, 0.0356774081f, 0.7978845608f)), a), fmaf(c, tanh_fast(c * fmaf(c * c, 0.0356774081f, 0.7978845608f)), c));
          }
#pragma unroll
          for (int j = 0; j < 3; j++) stsm4(us + hf * GRP + j * 256, U[4 * j], U[4 * j + 1], U[4 * j + 2], U[4 * j + 3]);
          stsm2(us + hf * GRP + 768, U[12], U[13]);
          named_arrive(hf ? 10 : 14, 160);
          if (!hf) mbar_wait(bars + B_X, 0);
        }
        OBS(rel, 30);
      } else {
        named_arrive(3, 256);
        const int kg0 = (mt & 3) * 14 + dt * 4, nk = dt < 3 ? 4 : 2;
        mbar_wait(bars + B_XF, 0);
        mbar_wait(bars + B_RT, 0);
        OBS(tid == 0, 7);
#pragma unroll 1
        for (int m = 1; m < 4; m++) {
          if (w4 < nk) {
            uint4 v[14];
#pragma unroll
            for (int l = 0; l < 14; l++) v[l] = lds128(base + (w4 * 8 + r8) * 2688 + (m % 3) * 896 + (l >> 1) * 128 + ((r8 + mi + (l & 1) * 4) & 7) * 16);
#pragma unroll
            for (int l = 0; l < 14; l++) sts128(base + (8 + m * 4 + w4) * GRP + (l >> 1) * 1024 + ((r8 + mi + (l & 1) * 4) & 7) * 128 + r8 * 16, v[l].x, v[l].y, v[l].z, v[l].w);
          }
          named_arrive(m == 1 ? 14 : (m == 2 ? 10 : 9), 160);
        }
        mbar_wait(bars + B_RT, 1);
        uint32_t W[4][14];
#pragma unroll
        for (int i = 0; i < 4; i++) lds_row(W[i], base + i * SLOT + g * 896 + w4 * 224, t);
        named_sync(1, 128);
#pragma unroll
        for (int i = 0; i < 4; i++) {
          const uint32_t st = base + i * SLOT + (w4 * 14 + mi) * 128 + r8 * 16;
#pragma unroll
          for (int j = 0; j < 3; j++) stsm4(st + j * 512, W[i][4 * j], W[i][4 * j + 1], W[i][4 * j + 2], W[i][4 * j + 3]);
          stsm2(st + 1536, W[i][12], W[i][13]);
        }
        smem_fence();
        named_sync(1, 128);
        if (w4 == 0 && elect()) {
#pragma unroll 1
          for (int i = 0; i < nk; i++) bulk_s2g(g_scr + (G_WO + kg0 + i) * GRP, base + i * SLOT, GRP);
          publish(C_U);
          mbar_arrive(bars + B_TS);
          OBS(1, 16);
        }
        __syncwarp();
      }
#pragma unroll
      for (int i = 0; i < 56; i++) { acc[i] = 0.f; asm volatile("" : "+f"(acc[i])); }
#pragma unroll
      for (int i = 2; i < 4; i++) { hb[i] = hmul2(hb[i] * 0x10001u, 0x3f003f00u); asm volatile("" : "+r"(hb[i])); }
      const int ro = (mt * 64 + w4 * 16 + g) * (D_ * 2) + dt * 224;
      unsigned char *outp = p.out + ro + t * 16, *outq = p.out + ro + 192 + t * 8;
      asm volatile("" : "+l"(outp), "+l"(outq));
      if (w4 < NP_U) { wait_until(clock() + PU0 + w4 * PH_U); watch_flag(1, C_U, 128); }
      named_sync(5, 256);
      OBS0(21, 10);
#pragma unroll 1
      for (int r = 0; ; r++) {
#pragma unroll
        for (int j = 0; j < 8; j++) {
          const bool site = j == SA % 8 || j == SB % 8, yield = (j == SA % 8 && r == SA / 8) || (j == SB % 8 && r == SB / 8);
          stage<1>(acc, p.dw, p.db, (j + 5) & 7, (r + (j > 2)) & 1, ok, trc, false, rel && (j || r), [&](int k) {
            if (k == 3 - HK) { if (site) arrive_if(N_GO, yield); if (j == 3) arrive_if(8, r == 3); } });
          if (site && yield) named_sync(N_DONE, 256);
          if (j == 3 && r == 3) goto gemm2_done;
        }
      }
      gemm2_done:
      wg_wait<0>();
      OBS(rel, 24);
      uint32_t G[28], dep = 0;
#pragma unroll
      for (int j = 0; j < 28; j++) {
        const uint32_t hh = hfma2(pack2(acc[2 * j], acc[2 * j + 1]), 0x3e803e80u, hb[2 + (j & 1)]);
        const float a = bf_lo(hh), c = bf_hi(hh);
        G[j] = pack2(fmaf(a, tanh_fast(a), a), fmaf(c, tanh_fast(c), c));
        dep |= G[j];
      }
      OBS(rel, 26);
      named_sync(12 + w4 + dep * threadIdx.y, 64);
      uint4 S4[8];
#pragma unroll
      for (int i = 0; i < 8; i++) S4[i] = lds128(sx + i * 2048);
      OBS(rel, 123);
#pragma unroll
      for (int i = 0; i < 4; i++) {
#pragma unroll
        for (int h = 0; h < 2; h++) {
          const uint32_t Sv[4] = {S4[2 * i + h].x, S4[2 * i + h].y, S4[2 * i + h].z, S4[2 * i + h].w};
          uint32_t Y[4];
#pragma unroll
          for (int j = 0; j < (i < 3 ? 4 : 2); j++) Y[j] = hadd2(R[h * 14 + 4 * i + j], hmul2(Sv[j], G[8 * i + 2 * j + h]));
          if (i < 3) asm volatile("st.global.v4.u32 [%0], {%1,%2,%3,%4};" :: "l"(outp + h * 8 * D_ * 2 + i * 64), "r"(Y[0]), "r"(Y[1]), "r"(Y[2]), "r"(Y[3]) : "memory");
          else asm volatile("st.global.v2.u32 [%0], {%1,%2};" :: "l"(outq + h * 8 * D_ * 2), "r"(Y[0]), "r"(Y[1]) : "memory");
        }
      }
      OBS(rel, 28);
#ifdef DBG_OBS
      named_sync(1, 128);
      { uint32_t v = lds32(base + OFF_OBS + tid * 4); if (tid == 126) v = tz; if (tid == 127) asm volatile("mov.u32 %0, %%smid;" : "=r"(v)); g_obs[b * 128 + tid] = v; }
#endif
    } else {
      asm volatile("setmaxnreg.inc.sync.aligned.u32 256;");
      float ka[56];
      const uint32_t nat = w4 * 3584 + (mi >> 1) * 128 + (r8 >> 2) * 1792 + (((2 * r8) & 7) + ((mi & 1) ^ (r8 >> 2))) * 16;
      {
        uint32_t X[28][4];
      mbar_wait(bars + B_X, 0);
      OBS(rel, 29);
#pragma unroll
      for (int k = 0; k < 28; k++)
        ldsm4(X[k], base + OFF_X + (k >> 2) * 8192 + (w4 * 16 + (mi >> 1) * 8 + r8) * 128 + (((2 * (k & 3) + (mi & 1)) ^ r8) << 4));
      if (lane == 0) mbar_arrive(bars + B_XF + X[27][3] * threadIdx.y);
      float c0[2][4] = {}, c1[2][4] = {};
      uint32_t one[8];
#pragma unroll
      for (int j = 0; j < 8; j++) asm volatile("{\n.reg .u32 y;\nmov.u32 y, %%tid.y;\nmad.lo.u32 %0, y, %1, 0x3f803f80;\n}" : "=r"(one[j]) : "r"(lane + j));
#pragma unroll
      for (int k = 0; k < 28; k++) {
        mma16816(c0[k & 1], X[k][0], one[(k & 1) * 4], X[k][1], one[(k & 1) * 4 + 1], X[k][0], X[k][1]);
        mma16816(c1[k & 1], X[k][2], one[(k & 1) * 4 + 2], X[k][3], one[(k & 1) * 4 + 3], X[k][2], X[k][3]);
      }
      float st[4];
#pragma unroll
      for (int j = 0; j < 2; j++) {
        st[j] = __shfl_sync(0xffffffffu, (g & 1) ? c0[0][2 * j + 1] + c0[1][2 * j + 1] : c0[0][2 * j] + c0[1][2 * j], (lane & 28) | (g >> 1));
        st[2 + j] = __shfl_sync(0xffffffffu, (g & 1) ? c1[0][2 * j + 1] + c1[1][2 * j + 1] : c1[0][2 * j] + c1[1][2 * j], (lane & 28) | (g >> 1));
      }
      const float m0 = st[1] * (1.0f / D_), m1 = st[3] * (1.0f / D_);
      const LnC l0 = ln_consts(m0, variance(m0, st[0])), l1 = ln_consts(m1, variance(m1, st[2]));
#pragma unroll
      for (int k = 0; k < 28; k++) {
        const uint32_t y = ln_apply(X[k][1], l0);
        X[k][0] = ln_apply(X[k][0], l0); X[k][1] = ln_apply(X[k][2], l1); X[k][2] = y; X[k][3] = ln_apply(X[k][3], l1);
        pin(X[k]);
      }
      OBS(rel, 122);
        float va[56];
        const uint32_t kst = base + OFF_KV + (2 + 2 * w4 + (mi & 1)) * 1792 + (mi >> 1) * 128 + r8 * 16;
        const uint32_t vst = base + OFF_KV + KV + 3584 + nat;
        auto put = [&](const float (&a)[56], uint32_t dst, int n) {
          stsm4(dst + n * 128, pack2(a[4 * n], a[4 * n + 1]), pack2(a[4 * n + 2], a[4 * n + 3]), pack2(a[4 * n + 4], a[4 * n + 5]), pack2(a[4 * n + 6], a[4 * n + 7])); };
        named_sync(3, 256);
        fresh(ka);
        OBS0(0, 8);
#pragma unroll
        for (int c = 0; c < 7; c++) stage<2>(ka, 0, p.db, c, 0, ok, trc, c == 0, rel && c, nohook, &X[c * 4]);
        fresh(va);
#pragma unroll
        for (int c = 7; c < 14; c++)
          stage<2>(va, 0, p.db, c & 7, c >> 3, ok, trc, c == 7, rel, [&](int k) {
            if (c > 7 && (c - 8) * 4 + k < 7) put(ka, kst, (c - 8) * 8 + k * 2);
            if (c == 9 && k == 3 && w4 == 3) named_arrive(11, 64); }, &X[(c - 7) * 4]);
        fresh(ka);
        OBS(rel, 9);
#pragma unroll
        for (int c = 14; c < 21; c++)
          stage<2>(ka, 0, p.db, c & 7, (c >> 3) & 1, ok, trc, c == 14, rel, [&](int k) {
            if (c > 14 && (c - 15) * 4 + k < 7) put(va, vst, (c - 15) * 8 + k * 2);
            if (c == 16 && k == 3 && w4 == 3) named_arrive(0, 64);
            if (SA >= 0 && c == 20 && k == 3 - HK) named_arrive(5, 256); }, &X[(c - 14) * 4]);
        smem_fence();
        wg_wait<0>();
        if (rel) mbar_arrive(bars + B_EMPTY + 4 * 8);
      }
      {
        uint32_t Q[8][4];
#pragma unroll
        for (int i = 0; i < 16; i++) {
          const int n = i - (i + 4) / 8;
#pragma unroll
          for (int h = 0; h < 2; h++) {
            const uint32_t v = pack2(ka[4 * n + 2 * h], ka[4 * n + 2 * h + 1]);
            Q[i >> 1][(i & 1) * 2 + h] = (i & 7) == 3 ? (t < 2 ? v : 0u) : ((i & 7) == 4 ? (t < 2 ? 0u : v) : v);
          }
        }
#pragma unroll
        for (int i = 0; i < 8; i++) pin(Q[i]);
        float Sc[4][40], O[4][16];
        mbar_wait(bars + B_HALO, 0);
        OBS(rel, 11);
#pragma unroll
        for (int hh = 0; hh < 4; hh++) fresh(Sc[hh]);
        wg_fence();
        if (SA >= 0) named_sync(N_GO, 256); else named_sync(2, 128);
#pragma unroll
        for (int k = 0; k < 2; k++)
#pragma unroll
          for (int hh = 0; hh < 4; hh++) {
            if (k == 1 && hh == (SA < 0 ? 2 : 3)) named_arrive(SA < 0 ? 5 : N_DONE, 256);
            wgmma_rs_n80<0>(Sc[hh], Q[hh * 2 + k], dlo(OFF_KV + (hh * 7 / 2 + 2 * k) * 128, 128), p.dk, k);
          }
        wg_commit();
        const bool e0 = 2 * t > g, e1 = 2 * t + 1 > g;
        const uint32_t em = (e0 ? 0xffffu : 0u) | (e1 ? 0xffff0000u : 0u);
        uint32_t L[4][2], M[6];
#pragma unroll
        for (int j = 0; j < 5; j++) { M[j] = j == w4 ? em : (j == w4 + 1 ? ~em : 0u); asm volatile("" : "+r"(M[j])); }
        M[5] = threadIdx.y;
        const uint32_t meta = 0x88dddd88u + M[5];
        wg_wait<0>();
        OBS(rel, 12);
        const uint32_t edge = mt == 0 ? em : 0u;
        auto pick = [&](int w) {
#pragma unroll
          for (int hh = 0; hh < 4; hh++)
#pragma unroll
            for (int h = 0; h < 2; h++) {
              const int i = (2 * w + h) * 4 + 2 * h;
              const uint32_t v = pack2(e0 ? Sc[hh][i] : Sc[hh][i + 8], e1 ? Sc[hh][i + 1] : Sc[hh][i + 9]);
              L[hh][h] = hfma2(v, 0x3e423e42u, hmul2(v, 0xb9f7b9f7u));
              if (w == 0) L[hh][h] = (L[hh][h] & ~edge) | (0xce6ece6eu & edge);
              asm volatile("" : "+r"(L[hh][h]));
            }
        };
        if (w4 == 0) pick(0); else if (w4 == 1) pick(1); else if (w4 == 2) pick(2); else pick(3);
        uint32_t A[4][3][4], mx[4];
        float P[8][2], sm[8];
#pragma unroll
        for (int hh = 0; hh < 4; hh++) mx[hh] = hmax2(__byte_perm(L[hh][0], L[hh][1], 0x5410), __byte_perm(L[hh][0], L[hh][1], 0x7632));
        const uint32_t x1 = 1 + ((mx[0] | mx[1] | mx[2] | mx[3]) & M[5]);
#pragma unroll
        for (int hh = 0; hh < 4; hh++) mx[hh] = hmax2(mx[hh], __shfl_xor_sync(0xffffffffu, mx[hh], x1));
#pragma unroll
        for (int hh = 0; hh < 4; hh++) mx[hh] = hmax2(mx[hh], __shfl_xor_sync(0xffffffffu, mx[hh], 2));
        uint32_t x2 = 0;
#pragma unroll
        for (int i = 0; i < 8; i++) {
          const float m = (i & 1 ? bf_hi(mx[i >> 1]) : bf_lo(mx[i >> 1])) * -LOG2E;
          P[i][0] = ex2_fast(fmaf(bf_lo(L[i >> 1][i & 1]), LOG2E, m)); P[i][1] = ex2_fast(fmaf(bf_hi(L[i >> 1][i & 1]), LOG2E, m));
          sm[i] = P[i][0] + P[i][1];
          x2 |= __float_as_uint(sm[i]);
        }
        x2 = 1 + (x2 & M[5]);
#pragma unroll
        for (int i = 0; i < 8; i++) sm[i] += __shfl_xor_sync(0xffffffffu, sm[i], x2);
#pragma unroll
        for (int i = 0; i < 8; i++) sm[i] += __shfl_xor_sync(0xffffffffu, sm[i], 2);
#pragma unroll
        for (int i = 0; i < 8; i++) {
          const float inv = rcp_fast(sm[i]);
          const uint32_t pp = pack2(P[i][0] * inv, P[i][1] * inv);
#pragma unroll
          for (int j = 0; j < 6; j++) A[i >> 1][j >> 1][(j & 1) * 2 + (i & 1)] = pp & M[j < 4 ? j : 9 - j];
        }
#pragma unroll
        for (int hh = 0; hh < 4; hh++) fresh(O[hh]);
#pragma unroll
        for (int i = 0; i < 12; i++) pin(A[i / 3][i % 3]);
        OBS(rel, 13);
        mbar_wait(bars + B_HALO + 8, 0);
        OBS(rel, 31);
        named_sync(N_GO, 256);
        wg_fence();
        const uint32_t ost = base + OFF_U + nat;
        auto opair = [&](int m, int h2) {
          const int hb2 = m / 7 * 2, r = m % 7;
          if (r < 3) return pack2(O[hb2][4 * r + h2], O[hb2][4 * r + h2 + 1]);
          if (r == 3) return pack2(t < 2 ? O[hb2][12 + h2] : O[hb2 + 1][h2], t < 2 ? O[hb2][13 + h2] : O[hb2 + 1][h2 + 1]);
          return pack2(O[hb2 + 1][4 * (r - 3) + h2], O[hb2 + 1][4 * (r - 3) + h2 + 1]);
        };
        auto oput = [&](int n) { stsm4(ost + n * 128, opair(n, 0), opair(n, 2), opair(n + 1, 0), opair(n + 1, 2)); };
        auto pv = [&](int hh, int j) { wgmma_sp_n32(O[hh], A[hh][j], dlo(OFF_KV + KV + hh * 7 / 2 * 128 + (j ? j + 1 : 0) * 3584, 1792), p.db, meta, j); };
#pragma unroll
        for (int i = 0; i < 12; i++) { if (i == 10) named_arrive(N_DONE, 256); pv(i & 3, i >> 2); }
        wg_commit();
        OBS(rel, 19);
        wg_wait<0>();
        OBS(rel, 21);
#pragma unroll
        for (int n = 0; n < 14; n += 2) oput(n);
        smem_fence();
        __syncwarp();
        OBS(rel, 14);
        if (elect()) {
          wait_until(clock() + w4 * PS_O);
          store_paced(g_scr + (G_O + mt * 8 + w4 * 2) * GRP + dt * 1792, GRP, base + OFF_U + w4 * 3584, 1792, 2, 4 * PS_O);
          publish(C_O + mt);
        }
        OBS(rel, 120);
        __syncwarp();
      }
      named_sync(8, 256);
      fresh(ka);
      OBS0(49, 25);
#pragma unroll
      for (int c = 49; c < 56; c++) stage<0>(ka, p.dx, p.db, c & 7, 0, ok, trc, c == 49, false, nohook);
      wg_wait<0>();
      OBS(rel, 27);
#pragma unroll
      for (int i = 0; i < 8; i++) {
        const float* a = ka + (i >> 1) * 16 + (i & 1) * 2;
        const uint32_t dst = (sx ^ ((i & 1) * 64)) + i * 2048, v0 = pack2(a[0], a[1]), v1 = pack2(a[4], a[5]);
        if (i < 6) sts128(dst, v0, v1, pack2(a[8], a[9]), pack2(a[12], a[13])); else sts64(dst, __uint_as_float(v0), __uint_as_float(v1));
      }
      named_arrive(12 + w4, 64);
      OBS(rel, 121);
    }
  }
}

typedef CUresult (*EncFn)(CUtensorMap*, CUtensorMapDataType, cuuint32_t, void*, const cuuint64_t*, const cuuint64_t*, const cuuint32_t*,
                          const cuuint32_t*, CUtensorMapInterleave, CUtensorMapSwizzle, CUtensorMapL2promotion, CUtensorMapFloatOOBfill);
void enc(EncFn f, CUtensorMap* m, const void* ptr, const cuuint64_t (&gd)[4], const cuuint64_t (&gs)[3], const cuuint32_t (&bx)[4], CUtensorMapSwizzle sw) {
  cuuint32_t es[4] = {1, 1, 1, 1};
  f(m, CU_TENSOR_MAP_DATA_TYPE_BFLOAT16, 4, (void*)ptr, gd, gs, bx, es, CU_TENSOR_MAP_INTERLEAVE_NONE, sw,
    CU_TENSOR_MAP_L2_PROMOTION_L2_128B, CU_TENSOR_MAP_FLOAT_OOB_FILL_NONE);
}
}

extern "C" void kernel_launch(void* const* d_in, const int* in_sizes, int n_in, void* d_out, int out_size) {
  (void)in_sizes; (void)n_in; (void)out_size;
  void* fp = nullptr;
  cudaDriverEntryPointQueryResult qr;
  cudaGetDriverEntryPoint("cuTensorMapEncodeTiled", &fp, cudaEnableDefault, &qr);
  EncFn f = (EncFn)fp;
  CUtensorMap m_w1, m_w2, m_b14, m_a8, m_b7, m_xt;
  void* scr = nullptr;
  cudaGetSymbolAddress(&scr, g_scr);
  enc(f, &m_w1, d_in[4], {F_, 16, 1, S_ / 16}, {F_ * 2, F_ * 2, F_ * 32}, {64, 8, 1, 8}, CU_TENSOR_MAP_SWIZZLE_128B);
  {
    cuuint64_t gd[5] = {64, 8, 2, S_ / 16, 7}, gs[4] = {D_ * 4, D_ * 2, D_ * 32, 128};
    cuuint32_t bx[5] = {64, 8, 2, 4, 7}, es[5] = {1, 1, 1, 1, 1};
    f(&m_xt, CU_TENSOR_MAP_DATA_TYPE_BFLOAT16, 5, d_in[0], gd, gs, bx, es, CU_TENSOR_MAP_INTERLEAVE_NONE, CU_TENSOR_MAP_SWIZZLE_128B,
      CU_TENSOR_MAP_L2_PROMOTION_L2_128B, CU_TENSOR_MAP_FLOAT_OOB_FILL_NONE);
  }
  enc(f, &m_w2, d_in[6], {S_, 1, 1, F_}, {S_ * 2, S_ * 2, S_ * 2}, {64, 1, 1, 64}, CU_TENSOR_MAP_SWIZZLE_128B);
  enc(f, &m_b14, scr, {64, 56, 1, G_END}, {128, GRP, GRP}, {64, 14, 1, 8}, CU_TENSOR_MAP_SWIZZLE_NONE);
  enc(f, &m_b7, scr, {64, 56, 1, G_END}, {128, GRP, GRP}, {64, 7, 1, 8}, CU_TENSOR_MAP_SWIZZLE_NONE);
  enc(f, &m_a8, scr, {64, 56, 1, G_END}, {128, GRP, GRP}, {64, 8, 1, 8}, CU_TENSOR_MAP_SWIZZLE_NONE);
  Params p;
  p.x = (const unsigned char*)d_in[0]; p.wqkv = (const unsigned char*)d_in[1]; p.wo = (const unsigned char*)d_in[2];
  p.w1 = (const unsigned char*)d_in[4]; p.b1 = (const unsigned short*)d_in[5];
  p.w2 = (const unsigned char*)d_in[6]; p.b2 = (const unsigned short*)d_in[7];
  p.out = (unsigned char*)d_out;
  p.dw = 0x40000040u; p.dx = 64; p.db = 8; p.dk = 112;
#ifdef TUNE
  for (int i = 0; i < NTUNE; i++) p.tune[i] = tune_vals[i];
#endif
  cudaFuncSetAttribute(fused_kernel, cudaFuncAttributeMaxDynamicSharedMemorySize, SMEM_BYTES);
  fused_kernel<<<128, NTHREADS, SMEM_BYTES, cudaStreamPerThread>>>(p, m_w1, m_w2, m_b14, m_a8, m_b7, m_xt);
}
```

```cpp
#include <cuda_runtime.h>
#include <cuda.h>
#include <cuda_bf16.h>
#include <stdint.h>

template<int TA, int TB> __device__ __forceinline__ void wgmma_n112(float (&d)[56], uint32_t al, uint32_t ah, uint32_t bl, uint32_t bh, int sc) {
  asm volatile("{\n.reg .pred p;\n.reg .b64 a, b;\nsetp.ne.b32 p, %60, 0;\nmov.b64 a, {%56, %57};\nmov.b64 b, {%58, %59};\n"
    "wgmma.mma_async.sync.aligned.m64n112k16.f32.bf16.bf16 {%0, %1, %2, %3, %4, %5, %6, %7, %8, %9, %10, %11, %12, %13, %14, %15, %16, %17, %18, %19, %20, %21, %22, %23, %24, %25, %26, %27, %28, %29, %30, %31, %32, %33, %34, %35, %36, %37, %38, %39, %40, %41, %42, %43, %44, %45, %46, %47, %48, %49, %50, %51, %52, %53, %54, %55}, a, b, p, 1, 1, %61, %62;\n}\n"
    : "+f"(d[0]), "+f"(d[1]), "+f"(d[2]), "+f"(d[3]), "+f"(d[4]), "+f"(d[5]), "+f"(d[6]), "+f"(d[7]), "+f"(d[8]), "+f"(d[9]), "+f"(d[10]), "+f"(d[11]), "+f"(d[12]), "+f"(d[13]), "+f"(d[14]), "+f"(d[15]), "+f"(d[16]), "+f"(d[17]), "+f"(d[18]), "+f"(d[19]), "+f"(d[20]), "+f"(d[21]), "+f"(d[22]), "+f"(d[23]), "+f"(d[24]), "+f"(d[25]), "+f"(d[26]), "+f"(d[27]), "+f"(d[28]), "+f"(d[29]), "+f"(d[30]), "+f"(d[31]), "+f"(d[32]), "+f"(d[33]), "+f"(d[34]), "+f"(d[35]), "+f"(d[36]), "+f"(d[37]), "+f"(d[38]), "+f"(d[39]), "+f"(d[40]), "+f"(d[41]), "+f"(d[42]), "+f"(d[43]), "+f"(d[44]), "+f"(d[45]), "+f"(d[46]), "+f"(d[47]), "+f"(d[48]), "+f"(d[49]), "+f"(d[50]), "+f"(d[51]), "+f"(d[52]), "+f"(d[53]), "+f"(d[54]), "+f"(d[55])
    : "r"(al), "r"(ah), "r"(bl), "r"(bh), "r"(sc), "n"(TA), "n"(TB));
}

template<int TB> __device__ __forceinline__ void wgmma_rs_n80(float (&d)[40], const uint32_t (&a)[4], uint32_t bl, uint32_t bh, int sc) {
  asm volatile("{\n.reg .pred p;\n.reg .b64 b;\nsetp.ne.b32 p, %46, 0;\nmov.b64 b, {%44, %45};\n"
    "wgmma.mma_async.sync.aligned.m64n80k16.f32.bf16.bf16 {%0, %1, %2, %3, %4, %5, %6, %7, %8, %9, %10, %11, %12, %13, %14, %15, %16, %17, %18, %19, %20, %21, %22, %23, %24, %25, %26, %27, %28, %29, %30, %31, %32, %33, %34, %35, %36, %37, %38, %39}, {%40, %41, %42, %43}, b, p, 1, 1, %47;\n}\n"
    : "+f"(d[0]), "+f"(d[1]), "+f"(d[2]), "+f"(d[3]), "+f"(d[4]), "+f"(d[5]), "+f"(d[6]), "+f"(d[7]), "+f"(d[8]), "+f"(d[9]), "+f"(d[10]), "+f"(d[11]), "+f"(d[12]), "+f"(d[13]), "+f"(d[14]), "+f"(d[15]), "+f"(d[16]), "+f"(d[17]), "+f"(d[18]), "+f"(d[19]), "+f"(d[20]), "+f"(d[21]), "+f"(d[22]), "+f"(d[23]), "+f"(d[24]), "+f"(d[25]), "+f"(d[26]), "+f"(d[27]), "+f"(d[28]), "+f"(d[29]), "+f"(d[30]), "+f"(d[31]), "+f"(d[32]), "+f"(d[33]), "+f"(d[34]), "+f"(d[35]), "+f"(d[36]), "+f"(d[37]), "+f"(d[38]), "+f"(d[39])
    : "r"(a[0]), "r"(a[1]), "r"(a[2]), "r"(a[3]), "r"(bl), "r"(bh), "r"(sc), "n"(TB));
}

__device__ __forceinline__ void wgmma_sp_n32(float (&d)[16], const uint32_t (&a)[4], uint32_t bl, uint32_t bh, uint32_t meta, int sc) {
  asm volatile("{\n.reg .pred p;\n.reg .b64 b;\nsetp.ne.b32 p, %23, 0;\nmov.b64 b, {%20, %21};\n"
    "wgmma.mma_async.sp.sync.aligned.m64n32k32.f32.bf16.bf16 {%0, %1, %2, %3, %4, %5, %6, %7, %8, %9, %10, %11, %12, %13, %14, %15}, {%16, %17, %18, %19}, b, %22, 0, p, 1, 1, 1;\n}\n"
    : "+f"(d[0]), "+f"(d[1]), "+f"(d[2]), "+f"(d[3]), "+f"(d[4]), "+f"(d[5]), "+f"(d[6]), "+f"(d[7]), "+f"(d[8]), "+f"(d[9]), "+f"(d[10]), "+f"(d[11]), "+f"(d[12]), "+f"(d[13]), "+f"(d[14]), "+f"(d[15])
    : "r"(a[0]), "r"(a[1]), "r"(a[2]), "r"(a[3]), "r"(bl), "r"(bh), "r"(meta), "r"(sc));
}

template<int TB> __device__ __forceinline__ void wgmma_rs_n112(float (&d)[56], const uint32_t (&a)[4], uint32_t bl, uint32_t bh, int sc) {
  asm volatile("{\n.reg .pred p;\n.reg .b64 b;\nsetp.ne.b32 p, %62, 0;\nmov.b64 b, {%60, %61};\n"
    "wgmma.mma_async.sync.aligned.m64n112k16.f32.bf16.bf16 {%0, %1, %2, %3, %4, %5, %6, %7, %8, %9, %10, %11, %12, %13, %14, %15, %16, %17, %18, %19, %20, %21, %22, %23, %24, %25, %26, %27, %28, %29, %30, %31, %32, %33, %34, %35, %36, %37, %38, %39, %40, %41, %42, %43, %44, %45, %46, %47, %48, %49, %50, %51, %52, %53, %54, %55}, {%56, %57, %58, %59}, b, p, 1, 1, %63;\n}\n"
    : "+f"(d[0]), "+f"(d[1]), "+f"(d[2]), "+f"(d[3]), "+f"(d[4]), "+f"(d[5]), "+f"(d[6]), "+f"(d[7]), "+f"(d[8]), "+f"(d[9]), "+f"(d[10]), "+f"(d[11]), "+f"(d[12]), "+f"(d[13]), "+f"(d[14]), "+f"(d[15]), "+f"(d[16]), "+f"(d[17]), "+f"(d[18]), "+f"(d[19]), "+f"(d[20]), "+f"(d[21]), "+f"(d[22]), "+f"(d[23]), "+f"(d[24]), "+f"(d[25]), "+f"(d[26]), "+f"(d[27]), "+f"(d[28]), "+f"(d[29]), "+f"(d[30]), "+f"(d[31]), "+f"(d[32]), "+f"(d[33]), "+f"(d[34]), "+f"(d[35]), "+f"(d[36]), "+f"(d[37]), "+f"(d[38]), "+f"(d[39]), "+f"(d[40]), "+f"(d[41]), "+f"(d[42]), "+f"(d[43]), "+f"(d[44]), "+f"(d[45]), "+f"(d[46]), "+f"(d[47]), "+f"(d[48]), "+f"(d[49]), "+f"(d[50]), "+f"(d[51]), "+f"(d[52]), "+f"(d[53]), "+f"(d[54]), "+f"(d[55])
    : "r"(a[0]), "r"(a[1]), "r"(a[2]), "r"(a[3]), "r"(bl), "r"(bh), "r"(sc), "n"(TB));
}

namespace {
constexpr int S_ = 2048, D_ = 448, F_ = 1792;
constexpr int SLOT = 22528, BT = 14336;
constexpr int OFF_KV = 8 * SLOT;
constexpr int OFF_X = OFF_KV - 7 * 8192;
constexpr int KV = 10 * 1792;
constexpr int OFF_PART = OFF_KV + 2 * BT;
constexpr int OFF_U = OFF_KV + 10 * 3584;
constexpr int OFF_BAR = OFF_U + BT;
constexpr uint32_t base = 1024, bars = base + OFF_BAR;
constexpr int OFF_OBS = OFF_BAR + 256;
constexpr int SMEM_BYTES = OFF_OBS + 768;
#define DLY_X 1200
#define DLY_W 3400
#define TPW 170
#define PF0 3000
#define PACE1 460
#define PACE2 400
#define SY_H 750
#define SY_U 1400
#define SY_B 900
#define PS_H 150
#define NP_H 3
#define PH_H 300
#define NP_U 2
#define PH_U 300
#define DLY_Q 1300
#define DLY_D 2000
#define DLY_E 2500
#define PQ 160
#define PS_O 90
#define PU0 1200
#define DLY_P 3200
#define SY_G 0
#define NP_O 1
#define PH_O 300
#define SA 0
#define SB 6
#define PVS 0
#define UH 1
#define EARLY 1
#define WU 0
#define TAILDRY 0
#define LATE 0
#define HOLD 0
#define DRY 0
#define HK 1
#define HE 1
#define OBS(c, i) do {} while (0)
constexpr int NTHREADS = 384;
constexpr float LOG2E = 1.4426950408889634f;

constexpr int GRP = 7168;
constexpr int G_H = 0, G_W = 256, G_U = G_W + 168, G_WO = G_U + 224, G_O = G_WO + 56, G_HALO = G_O + 256, G_END = G_HALO + 128;
constexpr int SCR_BYTES = G_END * GRP + S_ * 16;
__device__ __align__(1024) unsigned char g_scr[SCR_BYTES];
constexpr int C_TICKET = 0, C_W = 1, C_H = 2, C_U = 4, C_W2 = 5, C_O = 8, C_HALO = 40, C_END = 168;
__device__ __align__(128) unsigned g_cnt[C_END * 32];

__device__ __forceinline__ uint32_t smem_u32(const void* p) { return (uint32_t)__cvta_generic_to_shared(p); }
__device__ __forceinline__ void mbar_init(uint32_t bar, uint32_t cnt) { asm volatile("mbarrier.init.shared::cta.b64 [%0], %1;" :: "r"(bar), "r"(cnt)); }
__device__ __forceinline__ void mbar_expect_tx(uint32_t bar, uint32_t bytes) { asm volatile("mbarrier.arrive.expect_tx.shared::cta.b64 _, [%0], %1;" :: "r"(bar), "r"(bytes) : "memory"); }
__device__ __forceinline__ void mbar_arrive(uint32_t bar) { asm volatile("mbarrier.arrive.shared::cta.b64 _, [%0];" :: "r"(bar) : "memory"); }
__device__ __forceinline__ void mbar_wait(uint32_t bar, uint32_t parity) {
  asm volatile("{\n.reg .pred p;\n.reg .u32 n;\nmov.u32 n, 0;\nLAB_WAIT:\n"
               "mbarrier.try_wait.parity.shared::cta.b64 p, [%0], %1;\n@p bra DONE;\n"
               "add.u32 n, n, 1;\nsetp.lt.u32 p, n, 4000000;\n@p bra LAB_WAIT;\ntrap;\nDONE:\n}" :: "r"(bar), "r"(parity) : "memory");
}
__device__ __forceinline__ void mbar_wait_u(uint32_t bar, uint32_t parity) {
  asm volatile("{\n.reg .pred p;\nLAB_WAIT:\nmbarrier.try_wait.parity.shared::cta.b64 p, [%0], %1;\n@!p bra LAB_WAIT;\n}" :: "r"(bar), "r"(parity) : "memory");
}
__device__ __forceinline__ uint32_t mbar_try(uint32_t bar, uint32_t parity) {
  uint32_t ok;
  asm volatile("{\n.reg .pred p;\nmbarrier.test_wait.parity.shared::cta.b64 p, [%1], %2;\nselp.u32 %0, 1, 0, p;\n}" : "=r"(ok) : "r"(bar), "r"(parity) : "memory");
  return ok;
}
__device__ __forceinline__ void tma4d(uint32_t dst, const CUtensorMap* m, int c0, int c1, int c3, uint32_t bar) {
  asm volatile("cp.async.bulk.tensor.4d.shared::cluster.global.mbarrier::complete_tx::bytes [%0], [%1, {%3, %4, %6, %5}], [%2];"
               :: "r"(dst), "l"(m), "r"(bar), "r"(c0), "r"(c1), "r"(c3), "r"(0) : "memory");
}
__device__ __forceinline__ void tma_store(const CUtensorMap* m, int c1, int c3, uint32_t src) {
  asm volatile("cp.async.bulk.tensor.4d.global.shared::cta.bulk_group [%0, {%4, %2, %4, %3}], [%1];" :: "l"(m), "r"(src), "r"(c1), "r"(c3), "r"(0) : "memory");
}
__device__ __forceinline__ void bulk_g2s(uint32_t dst, const void* src, uint32_t bytes, uint32_t bar) {
  asm volatile("cp.async.bulk.shared::cluster.global.mbarrier::complete_tx::bytes [%0], [%1], %2, [%3];" :: "r"(dst), "l"(src), "r"(bytes), "r"(bar) : "memory");
}
__device__ __forceinline__ void bulk_s2g(void* dst, uint32_t src, uint32_t bytes) {
  asm volatile("cp.async.bulk.global.shared::cta.bulk_group [%0], [%1], %2;" :: "l"(dst), "r"(src), "r"(bytes) : "memory");
}
__device__ __forceinline__ void wg_fence() { asm volatile("wgmma.fence.sync.aligned;" ::: "memory"); }
__device__ __forceinline__ void wg_commit() { asm volatile("wgmma.commit_group.sync.aligned;" ::: "memory"); }
template <int N> __device__ __forceinline__ void wg_wait() { asm volatile("wgmma.wait_group.sync.aligned %0;" :: "n"(N) : "memory"); }
__device__ __forceinline__ void proxy_fence() { asm volatile("fence.proxy.async.global;" ::: "memory"); }
#define LIGHT 1
__device__ __forceinline__ void smem_fence() {
  if (LIGHT == 2) return;
  if (LIGHT) asm volatile("mbarrier.init.shared::cta.b64 [%0], 1;" :: "r"(base + OFF_BAR + 248) : "memory");
  else asm volatile("fence.proxy.async.shared::cta;" ::: "memory");
}
__device__ __forceinline__ uint32_t gtime() { uint32_t v; asm volatile("mov.u32 %0, %%globaltimer_lo;" : "=r"(v)); return v; }
__device__ __forceinline__ void publish(int i, bool timed = false) {
  asm volatile("cp.async.bulk.commit_group;" ::: "memory");
  if (timed) asm volatile("red.relaxed.gpu.global.max.u32 [%0], %1;" :: "l"(&g_cnt[i * 32 + 1]), "r"(gtime()) : "memory");
  asm volatile("cp.async.bulk.wait_group 0;" ::: "memory");
  asm volatile("red.relaxed.gpu.global.inc.u32 [%0], 0xffffffff;" :: "l"(&g_cnt[i * 32]) : "memory");
}
__device__ __forceinline__ void spin_ge(int i, unsigned target) {
  asm volatile("{\n.reg .pred p;\n.reg .u32 n, v;\nmov.u32 n, 0;\nLAB_SPIN:\n"
               "ld.relaxed.gpu.global.u32 v, [%0];\nsetp.ge.u32 p, v, %1;\n@p bra DONE;\n"
               "add.u32 n, n, 1;\nsetp.lt.u32 p, n, 4000000;\n@p bra LAB_SPIN;\ntrap;\nDONE:\n}" :: "l"(&g_cnt[i * 32]), "r"(target) : "memory");
}
__device__ __forceinline__ unsigned ld_relaxed(int i) { unsigned v; asm volatile("ld.relaxed.gpu.global.u32 %0, [%1];" : "=r"(v) : "l"(&g_cnt[i * 32]) : "memory"); return v; }
__device__ __forceinline__ bool elect() {
  uint32_t r; asm volatile("{\n.reg .pred p;\nelect.sync _|p, 0xffffffff;\nselp.u32 %0, 1, 0, p;\n}" : "=r"(r)); return r != 0;
}
__device__ __forceinline__ void wait_until(uint32_t tn) { while ((int)(clock() - tn) < 0) __nanosleep(20); }
__device__ __forceinline__ void store_paced(unsigned char* dst, int dstep, uint32_t src, int sstep, int n, int gap, int bytes = 1792) {
  uint32_t tn = clock();
#pragma unroll 1
  for (int i = 0; i < n; i++) { wait_until(tn); bulk_s2g(dst, src, bytes); dst += dstep; src += sstep; tn += gap; }
}
__device__ __forceinline__ uint4 lds128(uint32_t a) { uint4 v; asm volatile("ld.shared.v4.u32 {%0,%1,%2,%3}, [%4];" : "=r"(v.x), "=r"(v.y), "=r"(v.z), "=r"(v.w) : "r"(a) : "memory"); return v; }
__device__ __forceinline__ uint4 lds128_if(uint32_t a, int on) {
  uint4 v;
  asm volatile("{\n.reg .pred p;\nsetp.ne.u32 p, %5, 0;\n@p ld.shared.v4.u32 {%0,%1,%2,%3}, [%4];\n}" : "=r"(v.x), "=r"(v.y), "=r"(v.z), "=r"(v.w) : "r"(a), "r"(on) : "memory");
  return v;
}
__device__ __forceinline__ uint32_t lds32(uint32_t a) { uint32_t v; asm volatile("ld.shared.u32 %0, [%1];" : "=r"(v) : "r"(a) : "memory"); return v; }
__device__ __forceinline__ void sts128(uint32_t p, uint32_t a, uint32_t b, uint32_t c, uint32_t d) { asm volatile("st.shared.v4.u32 [%0], {%1,%2,%3,%4};" :: "r"(p), "r"(a), "r"(b), "r"(c), "r"(d) : "memory"); }
__device__ __forceinline__ void sts64(uint32_t p, float a, float b) { asm volatile("st.shared.v2.f32 [%0], {%1,%2};" :: "r"(p), "f"(a), "f"(b) : "memory"); }
__device__ __forceinline__ void named_sync(int id, int n) { asm volatile("bar.sync %0, %1;" :: "r"(id), "r"(n) : "memory"); }
__device__ __forceinline__ void named_arrive(int id, int n) { asm volatile("bar.arrive %0, %1;" :: "r"(id), "r"(n) : "memory"); }
__device__ __forceinline__ constexpr uint32_t dlo(uint32_t off, uint32_t lbo) { return ((base + off) >> 4) | (lbo >> 4 << 16); }
__device__ __forceinline__ uint32_t pack2(float lo, float hi) { uint32_t r; asm("cvt.rn.bf16x2.f32 %0, %1, %2;" : "=r"(r) : "f"(hi), "f"(lo)); return r; }
__device__ __forceinline__ float bf_lo(uint32_t v) { return __uint_as_float(v << 16); }
__device__ __forceinline__ float bf_hi(uint32_t v) { return __uint_as_float(v & 0xffff0000u); }
__device__ __forceinline__ float rbf(float x) { return bf_lo(pack2(x, 0.f)); }
__device__ __forceinline__ uint32_t hsub2(uint32_t a, uint32_t b) { uint32_t r; asm("sub.rn.bf16x2 %0, %1, %2;" : "=r"(r) : "r"(a), "r"(b)); return r; }
__device__ __forceinline__ uint32_t hadd2(uint32_t a, uint32_t b) { uint32_t r; asm("add.rn.bf16x2 %0, %1, %2;" : "=r"(r) : "r"(a), "r"(b)); return r; }
__device__ __forceinline__ uint32_t hmax2(uint32_t a, uint32_t b) { uint32_t r; asm("max.bf16x2 %0, %1, %2;" : "=r"(r) : "r"(a), "r"(b)); return r; }
__device__ __forceinline__ uint32_t hmul2(uint32_t a, uint32_t b) { uint32_t r; asm("mul.rn.bf16x2 %0, %1, %2;" : "=r"(r) : "r"(a), "r"(b)); return r; }
__device__ __forceinline__ uint32_t hfma2(uint32_t a, uint32_t b, uint32_t c) { uint32_t r; asm("fma.rn.bf16x2 %0, %1, %2, %3;" : "=r"(r) : "r"(a), "r"(b), "r"(c)); return r; }
__device__ __forceinline__ float tanh_fast(float x) { float r; asm("tanh.approx.f32 %0, %1;" : "=f"(r) : "f"(x)); return r; }
__device__ __forceinline__ float rcp_fast(float x) { float r; asm("rcp.approx.ftz.f32 %0, %1;" : "=f"(r) : "f"(x)); return r; }
__device__ __forceinline__ float ex2_fast(float x) { float r; asm("ex2.approx.ftz.f32 %0, %1;" : "=f"(r) : "f"(x)); return r; }
__device__ __forceinline__ void mma16816(float (&c)[4], uint32_t a0, uint32_t a1, uint32_t a2, uint32_t a3, uint32_t b0, uint32_t b1) {
  asm volatile("mma.sync.aligned.m16n8k16.row.col.f32.bf16.bf16.f32 {%0,%1,%2,%3}, {%4,%5,%6,%7}, {%8,%9}, {%0,%1,%2,%3};"
               : "+f"(c[0]), "+f"(c[1]), "+f"(c[2]), "+f"(c[3]) : "r"(a0), "r"(a1), "r"(a2), "r"(a3), "r"(b0), "r"(b1));
}
__device__ __forceinline__ void ldsm4(uint32_t (&r)[4], uint32_t addr) {
  asm volatile("ldmatrix.sync.aligned.m8n8.x4.shared.b16 {%0,%1,%2,%3}, [%4];" : "=r"(r[0]), "=r"(r[1]), "=r"(r[2]), "=r"(r[3]) : "r"(addr) : "memory");
}
__device__ __forceinline__ void stsm4(uint32_t addr, uint32_t a, uint32_t b, uint32_t c, uint32_t d) {
  asm volatile("stmatrix.sync.aligned.m8n8.x4.shared.b16 [%0], {%1,%2,%3,%4};" :: "r"(addr), "r"(a), "r"(b), "r"(c), "r"(d) : "memory");
}
__device__ __forceinline__ void stsm2(uint32_t addr, uint32_t a, uint32_t b) {
  asm volatile("stmatrix.sync.aligned.m8n8.x2.shared.b16 [%0], {%1,%2};" :: "r"(addr), "r"(a), "r"(b) : "memory");
}
__device__ __forceinline__ void load_row(uint32_t (&r)[14], const unsigned char* p, int t) {
#pragma unroll
  for (int i = 0; i < 3; i++)
    asm volatile("ld.global.nc.L1::no_allocate.v4.u32 {%0,%1,%2,%3}, [%4];" : "=r"(r[4 * i]), "=r"(r[4 * i + 1]), "=r"(r[4 * i + 2]), "=r"(r[4 * i + 3]) : "l"(p + i * 64 + t * 16));
  asm volatile("ld.global.nc.L1::no_allocate.v2.u32 {%0,%1}, [%2];" : "=r"(r[12]), "=r"(r[13]) : "l"(p + 192 + t * 8));
}
__device__ __forceinline__ void lds_row(uint32_t* r, uint32_t a, int t) {
#pragma unroll
  for (int i = 0; i < 3; i++) { const uint4 v = lds128(a + i * 64 + t * 16); r[4 * i] = v.x; r[4 * i + 1] = v.y; r[4 * i + 2] = v.z; r[4 * i + 3] = v.w; }
  asm volatile("ld.shared.v2.u32 {%0,%1}, [%2];" : "=r"(r[12]), "=r"(r[13]) : "r"(a + 192 + t * 8) : "memory");
}

__device__ __forceinline__ void tile_row(uint32_t* r, int tok, int d, int t) {
  const int xi = (tok >> 1) & 7;
#pragma unroll
  for (int j = 0; j < 4; j++) {
    const int c = d * 14 + (j < 3 ? 4 * j + t : 12 + (t >> 1));
    const uint4 v = lds128(base + OFF_X + ((tok & 48) + (tok & 1) * 8 + xi) * 896 + (c >> 3) * 128 + (((c ^ ((c >> 3) - xi)) & 7) << 4));
    if (j < 3) { r[4 * j] = v.x; r[4 * j + 1] = v.y; r[4 * j + 2] = v.z; r[4 * j + 3] = v.w; }
    else { r[12] = t & 1 ? v.z : v.x; r[13] = t & 1 ? v.w : v.y; }
  }
}

struct LnC { uint32_t m, rh, rl; float r; };
__device__ __forceinline__ LnC ln_consts(float mean, float var) {
  float sd;
  asm("sqrt.approx.ftz.f32 %0, %1;" : "=f"(sd) : "f"(rbf(rbf(var) + 1e-5f)));
  const float r = rcp_fast(rbf(sd)), rh = rbf(r);
  return {pack2(mean, mean), pack2(rh, rh), pack2(r - rh, r - rh), r};
}
__device__ __forceinline__ float variance(float mean, float sq) { return fmaxf(fmaf(-mean, mean, sq * (1.0f / D_)), 0.f); }
__device__ __forceinline__ uint32_t ln_apply(uint32_t x, const LnC& c) { const uint32_t d = hsub2(x, c.m); return hfma2(d, c.rh, hmul2(d, c.rl)); }

template <int N> __device__ __forceinline__ void fresh(float (&a)[N]) {
#pragma unroll
  for (int i = 0; i < N; i++) asm volatile("" : "=f"(a[i]));
}
__device__ __forceinline__ void pin(uint32_t (&a)[4]) { asm volatile("" : "+r"(a[0]), "+r"(a[1]), "+r"(a[2]), "+r"(a[3])); }
constexpr int B_EMPTY = 64, B_F0 = 128, B_F1 = 136, B_F2 = 144, B_F3 = 152, B_HALO = 160, B_RT = 176, B_RES = 184, B_TS = 192, B_F1B = 200, B_XF = 208, B_X = 216, S_FLAG = 224;
constexpr int N_GO = 6, N_DONE = 7;
__device__ __forceinline__ void watch_flag(int slot, int i, unsigned target) {
  asm volatile("{\n.reg .pred p;\n.reg .u32 n, v, t;\nmov.u32 n, 0;\nLAB_SPIN:\n"
               "ld.relaxed.gpu.global.v2.u32 {v, t}, [%1];\nsetp.ge.u32 p, v, %2;\n@p st.volatile.shared.v2.u32 [%0], {v, t};\n"
               "ld.volatile.shared.u32 v, [%0];\nsetp.ne.u32 p, v, 0;\n@p bra DONE;\n"
               "add.u32 n, n, 1;\nsetp.lt.u32 p, n, 4000000;\n@p bra LAB_SPIN;\ntrap;\nDONE:\n}" :: "r"(bars + S_FLAG + slot * 8), "l"(&g_cnt[i * 32]), "r"(target) : "memory");
}
__device__ __forceinline__ void wait_flag(int slot, int delay) {
  uint32_t v, last;
  do asm volatile("ld.volatile.shared.v2.u32 {%0, %1}, [%2];" : "=r"(v), "=r"(last) : "r"(bars + S_FLAG + slot * 8) : "memory"); while (!v);
  while (gtime() - last < (uint32_t)delay);
}
__device__ __forceinline__ void arrive_if(int id, bool on) {
  asm volatile("{\n.reg .pred p;\nsetp.ne.u32 p, %1, 0;\n@p bar.arrive %0, 256;\n}" :: "r"(id), "r"((uint32_t)on) : "memory");
}
template <int TA, class Hook>
__device__ __forceinline__ void stage(float (&acc)[56], uint32_t ah, uint32_t bh, int sb, uint32_t par, uint32_t& ok, int& g_tr, bool first, bool rel, Hook hook, const uint32_t (*X)[4] = nullptr) {
  if (!ok) { if (WU) mbar_wait_u(bars + sb * 8, par); else mbar_wait(bars + sb * 8, par); }
  wg_fence();
#pragma unroll
  for (int k = 0; k < 4; k++) {
    if constexpr (TA == 2) wgmma_rs_n112<1>(acc, X[k], dlo(sb * SLOT + 8192 + k * 3584, 1792), bh, k || !first);
    else wgmma_n112<TA, 1>(acc, dlo(sb * SLOT + k * (TA ? 2048 : 256), TA ? 8192 : 128), ah, dlo(sb * SLOT + 8192 + k * 3584, 1792), bh, k || !first);
    if (k == 1) ok = mbar_try(bars + ((sb + 1) & 7) * 8, sb == 7 ? par ^ 1 : par);
    hook(k);
  }
  wg_commit();
  wg_wait<1>();
  if (rel) mbar_arrive(bars + B_EMPTY + ((sb + 7) & 7) * 8);
}

struct Params {
  const unsigned char *x, *wqkv, *wo, *w1, *w2;
  const unsigned short *b1, *b2;
  unsigned char* out;
  uint32_t dw, dx, db, dk;
};

__global__ void __launch_bounds__(NTHREADS, 1)
fused_kernel(const Params p, const __grid_constant__ CUtensorMap m_w1, const __grid_constant__ CUtensorMap m_w2, const __grid_constant__ CUtensorMap m_b14,
             const __grid_constant__ CUtensorMap m_a8, const __grid_constant__ CUtensorMap m_b7, const __grid_constant__ CUtensorMap m_xt) {
  extern __shared__ __align__(1024) unsigned char smem_raw[];
  const uint32_t t0 = clock();
  const int tid = threadIdx.x, lane = tid & 31, b = blockIdx.x;
  const int g = lane >> 2, t = lane & 3, r8 = lane & 7, mi = lane >> 3;
  uint32_t H[14];
  if (tid < 128) load_row(H, p.x + (b * 16 + g) * (D_ * 2) + (tid >> 5) * 224, t);
  const int warp = __shfl_sync(0xffffffffu, tid >> 5, 0);
  const int dt = b & 3, mt = b >> 2;
  const bool g1 = b < 112;
  const int ft = mt, d1 = dt;
  if (warp >= 8) {
    if (warp == 8) {
      if (elect()) {
        asm volatile("prefetch.tensormap [%0];" :: "l"(&m_xt) : "memory");
        if (smem_u32(smem_raw) != base) asm volatile("trap;");
#pragma unroll
        for (int i = 0; i < 28; i++) mbar_init(bars + i * 8, i * 8 == B_XF ? 8 : 1);
        sts128(bars + S_FLAG, 0, 0, 0, 0); sts64(bars + S_FLAG + 16, 0.f, 0.f);
        asm volatile("fence.mbarrier_init.release.cluster;" ::: "memory");
      }
      __syncwarp();
      named_arrive(12, 160); named_arrive(13, 160);
    }
    named_sync(15, 128);
    asm volatile("setmaxnreg.dec.sync.aligned.u32 80;");
    if (warp == 8) {
      unsigned tk = 0;
      if (elect()) {
        wait_until(t0 + DLY_X);
        mbar_expect_tx(bars + B_X, 7 * 8192);
        asm volatile("cp.async.bulk.tensor.5d.shared::cluster.global.mbarrier::complete_tx::bytes [%0], [%1, {%4, %4, %4, %4, %3}], [%2];"
                     :: "r"(base + OFF_X), "l"(&m_xt), "r"(bars + B_X), "r"(mt * 4), "r"(0) : "memory");
        wait_until(t0 + DLY_D);
        asm volatile("prefetch.tensormap [%0];" :: "l"(&m_w1) : "memory");
        asm volatile("prefetch.tensormap [%0];" :: "l"(&m_b14) : "memory");
        if (g1) {
#pragma unroll 1
          for (int c = 0; c < 8; c++) {
            wait_until(t0 + DLY_W + c * TPW);
            if (c == 6) mbar_wait(bars + B_XF, 0);
            tma4d(base + c * SLOT, &m_w1, ft * 64, 0, c * 8, bars + c * 8);
          }
        } else {
          const int n = dt < 3 ? 16 : 8;
          mbar_expect_tx(bars + B_RT, n * 5376);
#pragma unroll 1
          for (int i = 0; i < n; i++) { wait_until(t0 + DLY_Q + i * PQ); bulk_g2s(base + i * 5376, p.wqkv + ((mt & 3) * 56 + dt * 16 + i) * 5376, 5376, bars + B_RT); }
        }
#pragma unroll 1
        for (int r = g1 ? 1 : 4; r < 4; r++) {
#pragma unroll
          for (int s = 0; s < 8; s++) {
            mbar_wait_u(bars + B_EMPTY + s * 8, (r & 1) ^ 1);
            tma4d(base + s * SLOT, &m_w1, mt * 64, (r & 2) * 4, (r & 1) * 64 + s * 8, bars + s * 8);
          }
        }
        mbar_wait(bars + B_EMPTY + 5 * 8, 1);
        mbar_wait(bars + B_EMPTY + 5 * 8, 0);
        if (!g1) mbar_wait(bars + B_TS, 0);
#pragma unroll 1
        for (int r = 0; ; r++) {
#pragma unroll
          for (int j = 0; j < 8; j++) {
            const int s = (j + 5) & 7;
            mbar_wait_u(bars + B_EMPTY + s * 8, (r + (j < 3)) & 1);
            tma4d(base + s * SLOT, &m_w2, mt * 64, 0, r * 512 + j * 64, bars + s * 8);
            if (j == 3 && r == 3) goto w2_done;
          }
        }
        w2_done:
        while (!lds32(bars + S_FLAG + 16));
        OBS(1, 22);
#pragma unroll
        for (int s = 1; s < 8; s++) {
          mbar_wait_u(bars + B_EMPTY + s * 8, 1);
          tma4d(base + s * SLOT, &m_a8, 0, s * 8 - 8, G_O + mt * 8, bars + s * 8);
        }
        tk = atomicInc(&g_cnt[C_TICKET * 32], 0xffffffffu);
      }
      if (__any_sync(0xffffffffu, tk == 127)) {
#pragma unroll 1
        for (int i = lane; i < C_END; i += 32) *(uint2*)&g_cnt[i * 32] = make_uint2(0, 0);
      }
    } else if (warp == 9) {
      if (elect()) {
        if (ld_relaxed(C_H) + ld_relaxed(C_H + 1) > 256) asm volatile("trap;");
        {
          wait_until(t0 + DLY_E);
          asm volatile("prefetch.tensormap [%0];" :: "l"(&m_b7) : "memory");
          asm volatile("prefetch.tensormap [%0];" :: "l"(&m_w2) : "memory");
          asm volatile("prefetch.tensormap [%0];" :: "l"(&m_a8) : "memory");
        }
        uint32_t bytes = SLOT;
#pragma unroll 1
        for (int r = g1 ? 0 : 4; r < 11; r++) {
#pragma unroll
          for (int s = 0; s < 8; s++) {
            if (s == 0 && r == 0) { if (NP_H & 1) { wait_until(t0 + DLY_P); watch_flag(0, C_H, 128); } wait_flag(0, SY_H); OBS(1, 16); }
            if (s == 0 && (r == 2 || r == 4)) { mbar_wait(bars + B_F0 + (r >> 2) * 8, 0); OBS(1, 16 + (r >> 1)); if (r == 4) bytes = BT; }
            if (s == 5 && r == 0) mbar_wait(bars + B_XF, 0);
            if (s == 7 && r == 4) mbar_wait(bars + B_F1B, 0);
            if (s == 5 && r == 6) { wait_flag(1, SY_U); OBS(1, 20); bytes = SLOT; }
            if (s) mbar_wait_u(bars + B_EMPTY + s * 8, (r & 1) ^ 1); else mbar_wait(bars + B_EMPTY, (r & 1) ^ 1);
            mbar_expect_tx(bars + s * 8, bytes);
            tma4d(base + s * SLOT + 8192, &m_b14, 0, dt * 14, r * 64 + s * 8, bars + s * 8);
          }
        }
      }
    } else if (warp == 10) {
      uint32_t tn = t0 + PF0;
      const unsigned char* src = p.w1 + (b + (b & ~7)) * 3584 + lane * 128;
#pragma unroll 1
      for (int i = 0; i < 32; i++) {
        wait_until(tn);
        if (i == 8) src -= 16 * 458752 - 8 * 3584;
        if (i == 16) src = p.w2 + b * 3584 + lane * 128;
        if (lane < 28) asm volatile("prefetch.global.L2 [%0];" :: "l"(src) : "memory");
        __syncwarp();
        src += i < 16 ? 2 * 458752 : 458752;
        tn += i < 16 ? PACE1 : PACE2;
      }
      watch_flag(1, C_U, 128);
      watch_flag(2, C_O + mt, 16);
    } else {
      unsigned char* dst = g_scr + (G_H + b) * GRP;
      asm volatile("" : "+l"(dst));
      named_sync(10, 160);
      smem_fence();
      if (elect()) { bulk_s2g(dst, base + OFF_KV, GRP); publish(C_H, true); OBS(1, 3); }
      if (g1 && (NP_H & 2)) { wait_until(t0 + DLY_P + PH_H); watch_flag(0, C_H, 128); }
      named_sync(9, 160);
      smem_fence();
      if (elect()) {
        if (g1 && SY_B) { wait_flag(0, SY_B); store_paced(dst + 128 * GRP, 1792, base + OFF_KV + GRP, 1792, 4, PS_H); }
        else bulk_s2g(dst + 128 * GRP, base + OFF_KV + GRP, GRP);
        bulk_s2g(g_scr + G_END * GRP + b * 256, base + OFF_PART + 1024, 256);
        publish(C_H + 1);
        OBS(1, 4);
      }
      __syncwarp();
      if (!g1) {
        const int kg0 = (mt & 3) * 14 + dt * 4, nk = dt < 3 ? 4 : 2;
#pragma unroll 1
        for (int m = 0; m < 3; m++) {
          named_sync(m == 0 ? 14 : (m == 1 ? 10 : 9), 160);
          smem_fence();
          if (elect()) {
            if (m == 2) {
              mbar_expect_tx(bars + B_RT, nk * GRP);
#pragma unroll 1
              for (int i = 0; i < nk; i++) bulk_g2s(base + i * SLOT, p.wo + (kg0 + i) * GRP, GRP, bars + B_RT);
            }
            bulk_s2g(g_scr + (G_W + m * 56 + kg0) * GRP, base + (12 + m * 4) * GRP, nk * GRP);
            if (m != 1) publish(m ? C_W2 : C_W);
            OBS(m != 1, 5 + (m >> 1));
          }
          __syncwarp();
        }
      }
      spin_ge(C_H + 1, 128);
      if (lane == 0) mbar_arrive(bars + B_F0);
      spin_ge(C_W, 16);
      if (lane == 0) mbar_arrive(bars + B_F1);
      spin_ge(C_W2, 16);
      if (lane == 0) mbar_arrive(bars + B_F1B);
      if (mt == 0) {
#pragma unroll
        for (int i = 0; i < 14; i++) sts128(base + OFF_KV + (i / 7) * KV + (i % 7) * 512 + lane * 16, 0, 0, 0, 0);
        smem_fence();
        __syncwarp();
        if (lane < 2) mbar_arrive(bars + B_HALO + lane * 8);
      }
      const unsigned have = EARLY && mt > 0 ? ld_relaxed(C_HALO + b - 4) : 0;
      if (g1) {
        named_sync(14, 160);
        smem_fence();
        if (elect()) tma_store(&m_b7, d1 * 14, G_U + ft * 8, base + OFF_U);
        named_sync(10, 160);
        smem_fence();
        if (elect()) { tma_store(&m_b7, d1 * 14 + 7, G_U + ft * 8, base + OFF_U + GRP); publish(C_U, true); OBS(1, 7); }
        __syncwarp();
      }
#pragma unroll 1
      for (int i = 0; i < 2; i++) {
        unsigned char* hg = g_scr + (G_HALO + b) * GRP + i * 3584;
        named_sync(i ? 0 : 11, 64);
        smem_fence();
        if (mt < 31 && elect()) { bulk_s2g(hg, base + OFF_KV + i * KV + 8 * 1792, 3584); publish(C_HALO + b); }
        OBS(lane == 0, i ? 15 : 23);
        if (mt > 0) {
          if (have <= i) spin_ge(C_HALO + b - 4, i + 1);
          if (elect()) { mbar_expect_tx(bars + B_HALO + i * 8, 3584); bulk_g2s(base + OFF_KV + i * KV, hg - 4 * GRP, 3584, bars + B_HALO + i * 8); }
        }
        __syncwarp();
      }
    }
  } else {
    const int wg = warp >> 2, w4 = warp & 3;
    const bool rel = (tid & 127) == 0;
#pragma unroll 1
    for (int trip = wg && DRY ? 0 : 1; trip < 2; trip++) {
      if (wg && trip) { named_sync(13, 160); mbar_wait(bars + B_X, 0); OBS(rel, 29); tile_row(H, dt * 16 + 8 + g, w4, t); }
      const uint32_t part = base + OFF_PART + (wg + trip) * 256 + g * 32, st = base + OFF_KV + wg * GRP + (w4 * 14 + mi) * 128 + r8 * 16;
      float s0 = 0.f, s1 = 0.f, q0 = 0.f, q1 = 0.f;
#pragma unroll
      for (int j = 0; j < 14; j++) { const float a = bf_lo(H[j]), c = bf_hi(H[j]); s0 += a; s1 += c; q0 = fmaf(a, a, q0); q1 = fmaf(c, c, q1); }
      s0 += s1; q0 += q1;
#pragma unroll
      for (int o = 1; o < 4; o <<= 1) { s0 += __shfl_xor_sync(0xffffffffu, s0, o); q0 += __shfl_xor_sync(0xffffffffu, q0, o); }
      if (t == 0) sts64(part + wg * 256 + w4 * 8, s0, q0);
      OBS(tid == 0, 0);
      named_sync(1 + wg, 128);
      const uint4 u = lds128(part + wg * 256), v = lds128(part + wg * 256 + 16);
      const float mean = ((__uint_as_float(u.x) + __uint_as_float(u.z)) + (__uint_as_float(v.x) + __uint_as_float(v.z))) * (1.0f / D_);
      const float var = variance(mean, (__uint_as_float(u.y) + __uint_as_float(u.w)) + (__uint_as_float(v.y) + __uint_as_float(v.w)));
      const LnC l = ln_consts(mean, var), l2 = ln_consts((mean - bf_lo(l.m)) * l.r, var * l.r * l.r);
      if (w4 == 0 && t == 0) sts128(base + OFF_PART + 1024 + wg * 128 + g * 16, l.m, l.rh, l.rl, 0);
#pragma unroll
      for (int j = 0; j < 14; j++) H[j] = ln_apply(ln_apply(H[j], l), l2);
#pragma unroll
      for (int i = 0; i < 3; i++) stsm4(st + i * 512, H[4 * i], H[4 * i + 1], H[4 * i + 2], H[4 * i + 3]);
      stsm2(st + 1536, H[12], H[13]);
      if (trip) named_arrive(10 - wg, 160);
      OBS(rel, 1 + wg);
    }
    uint32_t ok = 0;
    int trc = 0;
    auto nohook = [](int) {};
#define OBS0(c, i) ok = 0
    const uint32_t sx = base + OFF_KV + (tid & 127) * 16;
    if (wg == 0) {
      uint32_t hb[4], R[28];
#pragma unroll
      for (int i = 0; i < 4; i++)
        asm volatile("ld.relaxed.cta.global.u16 %0, [%1];" : "=r"(hb[i]) : "l"((i < 2 ? p.b1 + (g1 ? mt * 64 : 0) : p.b2 + mt * 64) + w4 * 16 + g + (i & 1) * 8) : "memory");
      named_sync(12, 160);
      mbar_wait(bars + B_X, 0);
#pragma unroll
      for (int h = 0; h < 2; h++) tile_row(R + h * 14, w4 * 16 + h * 8 + g, dt, t);
#pragma unroll
      for (int i = 0; i < 28; i++) asm volatile("" : "+r"(R[i]));
      if (lane == 0) mbar_arrive(bars + B_XF + R[27] * threadIdx.y);
      float acc[56];
      if (g1) {
#pragma unroll
        for (int i = 0; i < 56; i++) { acc[i] = bf_lo(hb[(i >> 1) & 1]); asm volatile("" : "+f"(acc[i])); }
        if (w4 < (NP_H >> 2)) { wait_until(clock() + w4 * PH_H); watch_flag(0, C_H, 128); }
        OBS0(0, 5);
#pragma unroll 1
        for (int r = 0; r < 4; r++)
#pragma unroll
          for (int c = 0; c < 8; c++) stage<1>(acc, p.dw, p.db, c, r & 1, ok, trc, false, rel && (c || r), [&](int k) { if (c == 7 && k == 3 - HK) arrive_if(3, r == 3); });
        wg_wait<0>();
        if (rel) mbar_arrive(bars + B_EMPTY + 7 * 8);
        OBS(rel, 6);
        const uint32_t us = base + OFF_U + (w4 * 2 + (mi & 1)) * 896 + (mi >> 1) * 128 + r8 * 16;
#pragma unroll
        for (int hf = 0; hf < 2; hf++) {
          uint32_t U[14];
#pragma unroll
          for (int j = 0; j < 14; j++) {
            const float a = acc[hf * 28 + 2 * j], c = acc[hf * 28 + 2 * j + 1];
            U[j] = pack2(fmaf(a, tanh_fast(a * fmaf(a * a, 0.0356774081f, 0.7978845608f)), a), fmaf(c, tanh_fast(c * fmaf(c * c, 0.0356774081f, 0.7978845608f)), c));
          }
#pragma unroll
          for (int j = 0; j < 3; j++) stsm4(us + hf * GRP + j * 256, U[4 * j], U[4 * j + 1], U[4 * j + 2], U[4 * j + 3]);
          stsm2(us + hf * GRP + 768, U[12], U[13]);
          named_arrive(hf ? 10 : 14, 160);
          if (!hf) mbar_wait(bars + B_X, 0);
        }
        OBS(rel, 30);
      } else {
        named_arrive(3, 256);
        const int kg0 = (mt & 3) * 14 + dt * 4, nk = dt < 3 ? 4 : 2;
        mbar_wait(bars + B_XF, 0);
        mbar_wait(bars + B_RT, 0);
        OBS(tid == 0, 7);
#pragma unroll 1
        for (int m = 1; m < 4; m++) {
          if (w4 < nk) {
            uint4 v[14];
#pragma unroll
            for (int l = 0; l < 14; l++) v[l] = lds128(base + (w4 * 8 + r8) * 2688 + (m % 3) * 896 + (l >> 1) * 128 + ((r8 + mi + (l & 1) * 4) & 7) * 16);
#pragma unroll
            for (int l = 0; l < 14; l++) sts128(base + (8 + m * 4 + w4) * GRP + (l >> 1) * 1024 + ((r8 + mi + (l & 1) * 4) & 7) * 128 + r8 * 16, v[l].x, v[l].y, v[l].z, v[l].w);
          }
          named_arrive(m == 1 ? 14 : (m == 2 ? 10 : 9), 160);
        }
        mbar_wait(bars + B_RT, 1);
        uint32_t W[4][14];
#pragma unroll
        for (int i = 0; i < 4; i++) lds_row(W[i], base + i * SLOT + g * 896 + w4 * 224, t);
        named_sync(1, 128);
#pragma unroll
        for (int i = 0; i < 4; i++) {
          const uint32_t st = base + i * SLOT + (w4 * 14 + mi) * 128 + r8 * 16;
#pragma unroll
          for (int j = 0; j < 3; j++) stsm4(st + j * 512, W[i][4 * j], W[i][4 * j + 1], W[i][4 * j + 2], W[i][4 * j + 3]);
          stsm2(st + 1536, W[i][12], W[i][13]);
        }
        smem_fence();
        named_sync(1, 128);
        if (w4 == 0 && elect()) {
#pragma unroll 1
          for (int i = 0; i < nk; i++) bulk_s2g(g_scr + (G_WO + kg0 + i) * GRP, base + i * SLOT, GRP);
          publish(C_U);
          mbar_arrive(bars + B_TS);
          OBS(1, 16);
        }
        __syncwarp();
      }
#pragma unroll
      for (int i = 0; i < 56; i++) { acc[i] = 0.f; asm volatile("" : "+f"(acc[i])); }
#pragma unroll
      for (int i = 2; i < 4; i++) { hb[i] = hmul2(hb[i] * 0x10001u, 0x3f003f00u); asm volatile("" : "+r"(hb[i])); }
      const int ro = (mt * 64 + w4 * 16 + g) * (D_ * 2) + dt * 224;
      unsigned char *outp = p.out + ro + t * 16, *outq = p.out + ro + 192 + t * 8;
      asm volatile("" : "+l"(outp), "+l"(outq));
      if (w4 < NP_U) { wait_until(clock() + PU0 + w4 * PH_U); watch_flag(1, C_U, 128); }
      if (SY_G) wait_flag(1, SY_G);
      named_sync(5, 256);
      OBS0(21, 10);
#pragma unroll 1
      for (int r = 0; ; r++) {
#pragma unroll
        for (int j = 0; j < 8; j++) {
          const bool site = j == SA % 8 || j == SB % 8, yield = (j == SA % 8 && r == SA / 8) || (j == SB % 8 && r == SB / 8);
          stage<1>(acc, p.dw, p.db, (j + 5) & 7, (r + (j > 2)) & 1, ok, trc, false, rel && (j || r), [&](int k) {
            if (k == 3 - HK) { if (site) arrive_if(N_GO, yield); if (j == 3) arrive_if(8, r == 3); } });
          if (site && yield) named_sync(N_DONE, 256);
          if (j == 3 && r == 3) goto gemm2_done;
        }
      }
      gemm2_done:
      wg_wait<0>();
      OBS(rel, 24);
      uint32_t G[28], dep = 0;
#pragma unroll
      for (int j = 0; j < 28; j++) {
        const uint32_t hh = hfma2(pack2(acc[2 * j], acc[2 * j + 1]), 0x3e803e80u, hb[2 + (j & 1)]);
        const float a = bf_lo(hh), c = bf_hi(hh);
        G[j] = pack2(fmaf(a, tanh_fast(a), a), fmaf(c, tanh_fast(c), c));
        dep |= G[j];
      }
      OBS(rel, 26);
#pragma unroll 1
      for (int trip = TAILDRY ? 0 : 1; trip < 2; trip++) {
        if (trip) named_sync(12 + w4 + dep * threadIdx.y, 64);
        uint4 S4[8];
#pragma unroll
        for (int i = 0; i < 8; i++) S4[i] = lds128_if(sx + i * 2048, trip);
        OBS(rel, 123);
#pragma unroll
        for (int i = 0; i < 8; i++) {
          const uint32_t Sv[4] = {S4[i].x, S4[i].y, S4[i].z, S4[i].w};
          const int h = i & 1, n = i >> 1;
          uint32_t Y[4];
#pragma unroll
          for (int j = 0; j < (n < 3 ? 4 : 2); j++) Y[j] = hadd2(R[h * 14 + 4 * n + j], hmul2(Sv[j], G[8 * n + 2 * j + h]));
          if (n < 3) asm volatile("{\n.reg .pred p;\nsetp.ne.u32 p, %5, 0;\n@p st.global.v4.u32 [%0], {%1,%2,%3,%4};\n}" :: "l"(outp + h * 8 * D_ * 2 + n * 64), "r"(Y[0]), "r"(Y[1]), "r"(Y[2]), "r"(Y[3]), "r"(trip) : "memory");
          else asm volatile("{\n.reg .pred p;\nsetp.ne.u32 p, %3, 0;\n@p st.global.v2.u32 [%0], {%1,%2};\n}" :: "l"(outq + h * 8 * D_ * 2), "r"(Y[0]), "r"(Y[1]), "r"(trip) : "memory");
        }
      }
      OBS(rel, 28);
    } else {
      asm volatile("setmaxnreg.inc.sync.aligned.u32 256;");
      float ka[56];
      const uint32_t nat = w4 * 3584 + (mi >> 1) * 128 + (r8 >> 2) * 1792 + (((2 * r8) & 7) + ((mi & 1) ^ (r8 >> 2))) * 16;
      {
        uint32_t X[28][4];
#pragma unroll
        for (int k = 0; k < 28; k++)
          ldsm4(X[k], base + OFF_X + (w4 * 16 + (mi & 1) * 8 + r8) * 896 + (k >> 2) * 128 + ((((2 * (k & 3) + (mi >> 1)) ^ ((k >> 2) - r8)) & 7) << 4));
        if (lane == 0) mbar_arrive(bars + B_XF + X[27][3] * threadIdx.y);
        mbar_wait(bars + B_F0, 0);
        LnC l[2];
#pragma unroll
        for (int h = 0; h < 2; h++)
          asm volatile("ld.relaxed.gpu.global.v4.u32 {%0,%1,%2,%3}, [%4];" : "=r"(l[h].m), "=r"(l[h].rh), "=r"(l[h].rl), "=f"(l[h].r) : "l"(g_scr + G_END * GRP + (mt * 64 + w4 * 16 + 2 * g + h) * 16) : "memory");
        int once = threadIdx.y;
#pragma unroll 1
        do {
#pragma unroll
          for (int k = 0; k < 112; k++) X[k >> 2][k & 3] = ln_apply(X[k >> 2][k & 3], l[k & 1]);
        } while (once--);
        OBS(rel, 122);
        float va[56];
        const uint32_t kst = base + OFF_KV + (2 + 2 * w4 + (mi & 1)) * 1792 + (mi >> 1) * 128 + r8 * 16;
        const uint32_t vst = base + OFF_KV + KV + 3584 + nat;
        auto put = [&](const float (&a)[56], uint32_t dst, int n) {
          stsm4(dst + n * 128, pack2(a[4 * n], a[4 * n + 1]), pack2(a[4 * n + 2], a[4 * n + 3]), pack2(a[4 * n + 4], a[4 * n + 5]), pack2(a[4 * n + 6], a[4 * n + 7])); };
        named_sync(3, 256);
        fresh(ka);
        OBS0(0, 8);
#pragma unroll
        for (int c = 0; c < 7; c++) stage<2>(ka, 0, p.db, c, 0, ok, trc, c == 0, rel && c, nohook, &X[c * 4]);
        fresh(va);
#pragma unroll
        for (int c = 7; c < 14; c++)
          stage<2>(va, 0, p.db, c & 7, c >> 3, ok, trc, c == 7, rel, [&](int k) {
            if (c > 7 && (c - 8) * 4 + k < 7) put(ka, kst, (c - 8) * 8 + k * 2);
            if (c == 9 && k == 3 && w4 == 3) named_arrive(11, 64); }, &X[(c - 7) * 4]);
        fresh(ka);
        OBS(rel, 9);
#pragma unroll
        for (int c = 14; c < 21; c++)
          stage<2>(ka, 0, p.db, c & 7, (c >> 3) & 1, ok, trc, c == 14, rel, [&](int k) {
            if (c > 14 && (c - 15) * 4 + k < 7) put(va, vst, (c - 15) * 8 + k * 2);
            if (c == 16 && k == 3 && w4 == 3) named_arrive(0, 64);
            if (SA >= 0 && c == 20 && k == 3 - HK) named_arrive(5, 256); }, &X[(c - 14) * 4]);
        smem_fence();
        wg_wait<0>();
        if (rel) mbar_arrive(bars + B_EMPTY + 4 * 8);
      }
      {
        uint32_t Q[8][4];
#pragma unroll
        for (int i = 0; i < 16; i++) {
          const int n = i - (i + 4) / 8;
#pragma unroll
          for (int h = 0; h < 2; h++) {
            const uint32_t v = pack2(ka[4 * n + 2 * h], ka[4 * n + 2 * h + 1]);
            Q[i >> 1][(i & 1) * 2 + h] = (i & 7) == 3 ? (t < 2 ? v : 0u) : ((i & 7) == 4 ? (t < 2 ? 0u : v) : v);
          }
        }
#pragma unroll
        for (int i = 0; i < 8; i++) pin(Q[i]);
        float Sc[4][40], O[4][16];
        mbar_wait(bars + B_HALO, 0);
        OBS(rel, 11);
#pragma unroll
        for (int hh = 0; hh < 4; hh++) fresh(Sc[hh]);
        wg_fence();
        if (SA >= 0) named_sync(N_GO, 256); else named_sync(2, 128);
#pragma unroll
        for (int k = 0; k < 2; k++)
#pragma unroll
          for (int hh = 0; hh < 4; hh++) {
            if (k == 1 && hh == (SA < 0 ? 2 : 3)) named_arrive(SA < 0 ? 5 : N_DONE, 256);
            wgmma_rs_n80<0>(Sc[hh], Q[hh * 2 + k], dlo(OFF_KV + (hh * 7 / 2 + 2 * k) * 128, 128), p.dk, k);
          }
        wg_commit();
        const bool e0 = 2 * t > g, e1 = 2 * t + 1 > g;
        const uint32_t em = (e0 ? 0xffffu : 0u) | (e1 ? 0xffff0000u : 0u);
        uint32_t L[4][2], M[6];
#pragma unroll
        for (int j = 0; j < 5; j++) { M[j] = j == w4 ? em : (j == w4 + 1 ? ~em : 0u); asm volatile("" : "+r"(M[j])); }
        M[5] = threadIdx.y;
        const uint32_t meta = 0x88dddd88u + M[5];
        wg_wait<0>();
        OBS(rel, 12);
        const uint32_t edge = mt == 0 ? em : 0u;
        auto pick = [&](int w) {
#pragma unroll
          for (int hh = 0; hh < 4; hh++)
#pragma unroll
            for (int h = 0; h < 2; h++) {
              const int i = (2 * w + h) * 4 + 2 * h;
              const uint32_t v = pack2(e0 ? Sc[hh][i] : Sc[hh][i + 8], e1 ? Sc[hh][i + 1] : Sc[hh][i + 9]);
              L[hh][h] = hfma2(v, 0x3e423e42u, hmul2(v, 0xb9f7b9f7u));
              if (w == 0) L[hh][h] = (L[hh][h] & ~edge) | (0xce6ece6eu & edge);
              asm volatile("" : "+r"(L[hh][h]));
            }
        };
        if (w4 == 0) pick(0); else if (w4 == 1) pick(1); else if (w4 == 2) pick(2); else pick(3);
        uint32_t A[4][3][4], mx[4];
        float P[8][2], sm[8];
#pragma unroll
        for (int hh = 0; hh < 4; hh++) mx[hh] = hmax2(__byte_perm(L[hh][0], L[hh][1], 0x5410), __byte_perm(L[hh][0], L[hh][1], 0x7632));
        const uint32_t x1 = 1 + ((mx[0] | mx[1] | mx[2] | mx[3]) & M[5]);
#pragma unroll
        for (int hh = 0; hh < 4; hh++) mx[hh] = hmax2(mx[hh], __shfl_xor_sync(0xffffffffu, mx[hh], x1));
#pragma unroll
        for (int hh = 0; hh < 4; hh++) mx[hh] = hmax2(mx[hh], __shfl_xor_sync(0xffffffffu, mx[hh], 2));
        uint32_t x2 = 0;
#pragma unroll
        for (int i = 0; i < 8; i++) {
          const float m = (i & 1 ? bf_hi(mx[i >> 1]) : bf_lo(mx[i >> 1])) * -LOG2E;
          P[i][0] = ex2_fast(fmaf(bf_lo(L[i >> 1][i & 1]), LOG2E, m)); P[i][1] = ex2_fast(fmaf(bf_hi(L[i >> 1][i & 1]), LOG2E, m));
          sm[i] = P[i][0] + P[i][1];
          x2 |= __float_as_uint(sm[i]);
        }
        x2 = 1 + (x2 & M[5]);
#pragma unroll
        for (int i = 0; i < 8; i++) sm[i] += __shfl_xor_sync(0xffffffffu, sm[i], x2);
#pragma unroll
        for (int i = 0; i < 8; i++) sm[i] += __shfl_xor_sync(0xffffffffu, sm[i], 2);
#pragma unroll
        for (int i = 0; i < 8; i++) {
          const float inv = rcp_fast(sm[i]);
          const uint32_t pp = pack2(P[i][0] * inv, P[i][1] * inv);
#pragma unroll
          for (int j = 0; j < 6; j++) A[i >> 1][j >> 1][(j & 1) * 2 + (i & 1)] = pp & M[j < 4 ? j : 9 - j];
        }
#pragma unroll
        for (int hh = 0; hh < 4; hh++) fresh(O[hh]);
#pragma unroll
        for (int i = 0; i < 12; i++) pin(A[i / 3][i % 3]);
        OBS(rel, 13);
        mbar_wait(bars + B_HALO + 8, 0);
        OBS(rel, 31);
        named_sync(N_GO, 256);
        wg_fence();
        const uint32_t ost = base + OFF_U + nat;
        auto opair = [&](int m, int h2) {
          const int hb2 = m / 7 * 2, r = m % 7;
          const float f0 = LATE ? sm[2 * hb2 + h2 / 2] : 1.f, f1 = LATE ? sm[2 * hb2 + 2 + h2 / 2] : 1.f, f = t < 2 ? f0 : f1;
          if (r < 3) return pack2(O[hb2][4 * r + h2] * f0, O[hb2][4 * r + h2 + 1] * f0);
          if (r == 3) return pack2((t < 2 ? O[hb2][12 + h2] : O[hb2 + 1][h2]) * f, (t < 2 ? O[hb2][13 + h2] : O[hb2 + 1][h2 + 1]) * f);
          return pack2(O[hb2 + 1][4 * (r - 3) + h2] * f1, O[hb2 + 1][4 * (r - 3) + h2 + 1] * f1);
        };
        auto oput = [&](int n) { stsm4(ost + n * 128, opair(n, 0), opair(n, 2), opair(n + 1, 0), opair(n + 1, 2)); };
        auto pv = [&](int hh, int j) { wgmma_sp_n32(O[hh], A[hh][j], dlo(OFF_KV + KV + hh * 7 / 2 * 128 + (j ? j + 1 : 0) * 3584, 1792), p.db, meta, j); };
#pragma unroll
        for (int i = 0; i < 12; i++) {
          if (i == 10 && !HOLD) named_arrive(N_DONE, 256);
          pv(i & 3, i >> 2);
          if (LATE && i < 8) { sm[i] = P[i][0] + P[i][1]; sm[i] += __shfl_xor_sync(0xffffffffu, sm[i], 1); }
        }
        wg_commit();
        if (LATE) {
#pragma unroll
          for (int i = 0; i < 8; i++) sm[i] = rcp_fast(sm[i] + __shfl_xor_sync(0xffffffffu, sm[i], 2));
        }
        if (HOLD == 1) named_arrive(N_DONE, 256);
        OBS(rel, 19);
        wg_wait<0>();
        OBS(rel, 21);
#pragma unroll
        for (int n = 0; n < 14; n += 2) { if (HOLD > 1 && n == 2 * (HOLD - 2)) named_arrive(N_DONE, 256); oput(n); }
        smem_fence();
        __syncwarp();
        OBS(rel, 14);
        if (elect()) {
          wait_until(clock() + w4 * PS_O);
          store_paced(g_scr + (G_O + mt * 8 + w4 * 2) * GRP + dt * 1792, GRP, base + OFF_U + w4 * 3584, 1792, 2, 4 * PS_O);
          publish(C_O + mt);
        }
        OBS(rel, 120);
        __syncwarp();
        if (w4 < NP_O) { wait_until(clock() + PH_O); watch_flag(2, C_O + mt, 16); }
      }
      named_sync(8, 256);
      fresh(ka);
      OBS0(49, 25);
#pragma unroll
      for (int c = 49; c < 56; c++) stage<0>(ka, p.dx, p.db, c & 7, 0, ok, trc, c == 49, false, nohook);
      wg_wait<0>();
      OBS(rel, 27);
#pragma unroll
      for (int i = 0; i < 8; i++) {
        const float* a = ka + (i >> 1) * 16 + (i & 1) * 2;
        const uint32_t dst = (sx ^ ((i & 1) * 64)) + i * 2048, v0 = pack2(a[0], a[1]), v1 = pack2(a[4], a[5]);
        if (i < 6) sts128(dst, v0, v1, pack2(a[8], a[9]), pack2(a[12], a[13])); else sts64(dst, __uint_as_float(v0), __uint_as_float(v1));
      }
      named_arrive(12 + w4, 64);
      OBS(rel, 121);
    }
  }
}

typedef CUresult (*EncFn)(CUtensorMap*, CUtensorMapDataType, cuuint32_t, void*, const cuuint64_t*, const cuuint64_t*, const cuuint32_t*,
                          const cuuint32_t*, CUtensorMapInterleave, CUtensorMapSwizzle, CUtensorMapL2promotion, CUtensorMapFloatOOBfill);
void enc(EncFn f, CUtensorMap* m, const void* ptr, const cuuint64_t (&gd)[4], const cuuint64_t (&gs)[3], const cuuint32_t (&bx)[4], CUtensorMapSwizzle sw) {
  cuuint32_t es[4] = {1, 1, 1, 1};
  f(m, CU_TENSOR_MAP_DATA_TYPE_BFLOAT16, 4, (void*)ptr, gd, gs, bx, es, CU_TENSOR_MAP_INTERLEAVE_NONE, sw,
    CU_TENSOR_MAP_L2_PROMOTION_L2_128B, CU_TENSOR_MAP_FLOAT_OOB_FILL_NONE);
}
}

extern "C" void kernel_launch(void* const* d_in, const int* in_sizes, int n_in, void* d_out, int out_size) {
  (void)in_sizes; (void)n_in; (void)out_size;
  void* fp = nullptr;
  cudaDriverEntryPointQueryResult qr;
  cudaGetDriverEntryPoint("cuTensorMapEncodeTiled", &fp, cudaEnableDefault, &qr);
  EncFn f = (EncFn)fp;
  CUtensorMap m_w1, m_w2, m_b14, m_a8, m_b7, m_xt;
  void* scr = nullptr;
  cudaGetSymbolAddress(&scr, g_scr);
  enc(f, &m_w1, d_in[4], {F_, 16, 1, S_ / 16}, {F_ * 2, F_ * 2, F_ * 32}, {64, 8, 1, 8}, CU_TENSOR_MAP_SWIZZLE_128B);
  {
    cuuint64_t gd[5] = {64, 7, 8, 2, S_ / 16}, gs[4] = {128, D_ * 4, D_ * 2, D_ * 32};
    cuuint32_t bx[5] = {64, 7, 8, 2, 4}, es[5] = {1, 1, 1, 1, 1};
    f(&m_xt, CU_TENSOR_MAP_DATA_TYPE_BFLOAT16, 5, d_in[0], gd, gs, bx, es, CU_TENSOR_MAP_INTERLEAVE_NONE, CU_TENSOR_MAP_SWIZZLE_128B,
      CU_TENSOR_MAP_L2_PROMOTION_L2_128B, CU_TENSOR_MAP_FLOAT_OOB_FILL_NONE);
  }
  enc(f, &m_w2, d_in[6], {S_, 1, 1, F_}, {S_ * 2, S_ * 2, S_ * 2}, {64, 1, 1, 64}, CU_TENSOR_MAP_SWIZZLE_128B);
  enc(f, &m_b14, scr, {64, 56, 1, G_END}, {128, GRP, GRP}, {64, 14, 1, 8}, CU_TENSOR_MAP_SWIZZLE_NONE);
  enc(f, &m_b7, scr, {64, 56, 1, G_END}, {128, GRP, GRP}, {64, 7, 1, 8}, CU_TENSOR_MAP_SWIZZLE_NONE);
  enc(f, &m_a8, scr, {64, 56, 1, G_END}, {128, GRP, GRP}, {64, 8, 1, 8}, CU_TENSOR_MAP_SWIZZLE_NONE);
  Params p;
  p.x = (const unsigned char*)d_in[0]; p.wqkv = (const unsigned char*)d_in[1]; p.wo = (const unsigned char*)d_in[2];
  p.w1 = (const unsigned char*)d_in[4]; p.b1 = (const unsigned short*)d_in[5];
  p.w2 = (const unsigned char*)d_in[6]; p.b2 = (const unsigned short*)d_in[7];
  p.out = (unsigned char*)d_out;
  p.dw = 0x40000040u; p.dx = 64; p.db = 8; p.dk = 112;
  cudaFuncSetAttribute(fused_kernel, cudaFuncAttributeMaxDynamicSharedMemorySize, SMEM_BYTES);
  fused_kernel<<<128, NTHREADS, SMEM_BYTES, cudaStreamPerThread>>>(p, m_w1, m_w2, m_b14, m_a8, m_b7, m_xt);
}
```

```cpp
#include <cuda_runtime.h>
#include <cuda.h>
#include <cuda_bf16.h>
#include <stdint.h>

template<int TA, int TB> __device__ __forceinline__ void wgmma_n112(float (&d)[56], uint32_t al, uint32_t ah, uint32_t bl, uint32_t bh, int sc) {
  asm volatile("{\n.reg .pred p;\n.reg .b64 a, b;\nsetp.ne.b32 p, %60, 0;\nmov.b64 a, {%56, %57};\nmov.b64 b, {%58, %59};\n"
    "wgmma.mma_async.sync.aligned.m64n112k16.f32.bf16.bf16 {%0, %1, %2, %3, %4, %5, %6, %7, %8, %9, %10, %11, %12, %13, %14, %15, %16, %17, %18, %19, %20, %21, %22, %23, %24, %25, %26, %27, %28, %29, %30, %31, %32, %33, %34, %35, %36, %37, %38, %39, %40, %41, %42, %43, %44, %45, %46, %47, %48, %49, %50, %51, %52, %53, %54, %55}, a, b, p, 1, 1, %61, %62;\n}\n"
    : "+f"(d[0]), "+f"(d[1]), "+f"(d[2]), "+f"(d[3]), "+f"(d[4]), "+f"(d[5]), "+f"(d[6]), "+f"(d[7]), "+f"(d[8]), "+f"(d[9]), "+f"(d[10]), "+f"(d[11]), "+f"(d[12]), "+f"(d[13]), "+f"(d[14]), "+f"(d[15]), "+f"(d[16]), "+f"(d[17]), "+f"(d[18]), "+f"(d[19]), "+f"(d[20]), "+f"(d[21]), "+f"(d[22]), "+f"(d[23]), "+f"(d[24]), "+f"(d[25]), "+f"(d[26]), "+f"(d[27]), "+f"(d[28]), "+f"(d[29]), "+f"(d[30]), "+f"(d[31]), "+f"(d[32]), "+f"(d[33]), "+f"(d[34]), "+f"(d[35]), "+f"(d[36]), "+f"(d[37]), "+f"(d[38]), "+f"(d[39]), "+f"(d[40]), "+f"(d[41]), "+f"(d[42]), "+f"(d[43]), "+f"(d[44]), "+f"(d[45]), "+f"(d[46]), "+f"(d[47]), "+f"(d[48]), "+f"(d[49]), "+f"(d[50]), "+f"(d[51]), "+f"(d[52]), "+f"(d[53]), "+f"(d[54]), "+f"(d[55])
    : "r"(al), "r"(ah), "r"(bl), "r"(bh), "r"(sc), "n"(TA), "n"(TB));
}

template<int TB> __device__ __forceinline__ void wgmma_rs_n80(float (&d)[40], const uint32_t (&a)[4], uint32_t bl, uint32_t bh, int sc) {
  asm volatile("{\n.reg .pred p;\n.reg .b64 b;\nsetp.ne.b32 p, %46, 0;\nmov.b64 b, {%44, %45};\n"
    "wgmma.mma_async.sync.aligned.m64n80k16.f32.bf16.bf16 {%0, %1, %2, %3, %4, %5, %6, %7, %8, %9, %10, %11, %12, %13, %14, %15, %16, %17, %18, %19, %20, %21, %22, %23, %24, %25, %26, %27, %28, %29, %30, %31, %32, %33, %34, %35, %36, %37, %38, %39}, {%40, %41, %42, %43}, b, p, 1, 1, %47;\n}\n"
    : "+f"(d[0]), "+f"(d[1]), "+f"(d[2]), "+f"(d[3]), "+f"(d[4]), "+f"(d[5]), "+f"(d[6]), "+f"(d[7]), "+f"(d[8]), "+f"(d[9]), "+f"(d[10]), "+f"(d[11]), "+f"(d[12]), "+f"(d[13]), "+f"(d[14]), "+f"(d[15]), "+f"(d[16]), "+f"(d[17]), "+f"(d[18]), "+f"(d[19]), "+f"(d[20]), "+f"(d[21]), "+f"(d[22]), "+f"(d[23]), "+f"(d[24]), "+f"(d[25]), "+f"(d[26]), "+f"(d[27]), "+f"(d[28]), "+f"(d[29]), "+f"(d[30]), "+f"(d[31]), "+f"(d[32]), "+f"(d[33]), "+f"(d[34]), "+f"(d[35]), "+f"(d[36]), "+f"(d[37]), "+f"(d[38]), "+f"(d[39])
    : "r"(a[0]), "r"(a[1]), "r"(a[2]), "r"(a[3]), "r"(bl), "r"(bh), "r"(sc), "n"(TB));
}

__device__ __forceinline__ void wgmma_sp_n32(float (&d)[16], const uint32_t (&a)[4], uint32_t bl, uint32_t bh, uint32_t meta, int sc) {
  asm volatile("{\n.reg .pred p;\n.reg .b64 b;\nsetp.ne.b32 p, %23, 0;\nmov.b64 b, {%20, %21};\n"
    "wgmma.mma_async.sp.sync.aligned.m64n32k32.f32.bf16.bf16 {%0, %1, %2, %3, %4, %5, %6, %7, %8, %9, %10, %11, %12, %13, %14, %15}, {%16, %17, %18, %19}, b, %22, 0, p, 1, 1, 1;\n}\n"
    : "+f"(d[0]), "+f"(d[1]), "+f"(d[2]), "+f"(d[3]), "+f"(d[4]), "+f"(d[5]), "+f"(d[6]), "+f"(d[7]), "+f"(d[8]), "+f"(d[9]), "+f"(d[10]), "+f"(d[11]), "+f"(d[12]), "+f"(d[13]), "+f"(d[14]), "+f"(d[15])
    : "r"(a[0]), "r"(a[1]), "r"(a[2]), "r"(a[3]), "r"(bl), "r"(bh), "r"(meta), "r"(sc));
}

template<int TB> __device__ __forceinline__ void wgmma_rs_n112(float (&d)[56], const uint32_t (&a)[4], uint32_t bl, uint32_t bh, int sc) {
  asm volatile("{\n.reg .pred p;\n.reg .b64 b;\nsetp.ne.b32 p, %62, 0;\nmov.b64 b, {%60, %61};\n"
    "wgmma.mma_async.sync.aligned.m64n112k16.f32.bf16.bf16 {%0, %1, %2, %3, %4, %5, %6, %7, %8, %9, %10, %11, %12, %13, %14, %15, %16, %17, %18, %19, %20, %21, %22, %23, %24, %25, %26, %27, %28, %29, %30, %31, %32, %33, %34, %35, %36, %37, %38, %39, %40, %41, %42, %43, %44, %45, %46, %47, %48, %49, %50, %51, %52, %53, %54, %55}, {%56, %57, %58, %59}, b, p, 1, 1, %63;\n}\n"
    : "+f"(d[0]), "+f"(d[1]), "+f"(d[2]), "+f"(d[3]), "+f"(d[4]), "+f"(d[5]), "+f"(d[6]), "+f"(d[7]), "+f"(d[8]), "+f"(d[9]), "+f"(d[10]), "+f"(d[11]), "+f"(d[12]), "+f"(d[13]), "+f"(d[14]), "+f"(d[15]), "+f"(d[16]), "+f"(d[17]), "+f"(d[18]), "+f"(d[19]), "+f"(d[20]), "+f"(d[21]), "+f"(d[22]), "+f"(d[23]), "+f"(d[24]), "+f"(d[25]), "+f"(d[26]), "+f"(d[27]), "+f"(d[28]), "+f"(d[29]), "+f"(d[30]), "+f"(d[31]), "+f"(d[32]), "+f"(d[33]), "+f"(d[34]), "+f"(d[35]), "+f"(d[36]), "+f"(d[37]), "+f"(d[38]), "+f"(d[39]), "+f"(d[40]), "+f"(d[41]), "+f"(d[42]), "+f"(d[43]), "+f"(d[44]), "+f"(d[45]), "+f"(d[46]), "+f"(d[47]), "+f"(d[48]), "+f"(d[49]), "+f"(d[50]), "+f"(d[51]), "+f"(d[52]), "+f"(d[53]), "+f"(d[54]), "+f"(d[55])
    : "r"(a[0]), "r"(a[1]), "r"(a[2]), "r"(a[3]), "r"(bl), "r"(bh), "r"(sc), "n"(TB));
}

namespace {
constexpr int S_ = 2048, D_ = 448, F_ = 1792;
constexpr int SLOT = 22528, BT = 14336;
constexpr int OFF_KV = 8 * SLOT;
constexpr int OFF_X = OFF_KV - 7 * 8192;
constexpr int KV = 10 * 1792;
constexpr int OFF_PART = OFF_KV + 2 * BT;
constexpr int OFF_U = OFF_KV + 10 * 3584;
constexpr int OFF_BAR = OFF_U + BT;
constexpr uint32_t base = 1024, bars = base + OFF_BAR;
constexpr int OFF_OBS = OFF_BAR + 256;
constexpr int SMEM_BYTES = OFF_OBS + 768;
#define DLY_X 1200
#define DLY_W 3400
#define TPW 170
#define PF0 3000
#define PACE1 460
#define PACE2 400
#define SY_H 750
#define SY_U 1400
#define SY_B 900
#define PS_H 150
#define NP_H 3
#define PH_H 300
#define NP_U 2
#define PH_U 300
#define DLY_Q 1300
#define DLY_D 2000
#define DLY_E 2500
#define PQ 160
#define PS_O 90
#define PU0 1200
#define DLY_P 3200
#define SY_G 0
#define NP_O 1
#define PH_O 300
#define SA 0
#define SB 6
#define PVS 0
#define UH 1
#define EARLY 1
#define WU 0
#define TAILDRY 0
#define LATE 0
#define HOLD 0
#define DRY 0
#define HK 1
#define HE 1
#define OBS(c, i) do {} while (0)
constexpr int NTHREADS = 384;
constexpr float LOG2E = 1.4426950408889634f;

constexpr int GRP = 7168;
constexpr int G_H = 0, G_W = 256, G_U = G_W + 168, G_WO = G_U + 224, G_O = G_WO + 56, G_HALO = G_O + 256, G_END = G_HALO + 128;
constexpr int SCR_BYTES = G_END * GRP + S_ * 16;
__device__ __align__(1024) unsigned char g_scr[SCR_BYTES];
constexpr int C_TICKET = 0, C_W = 1, C_H = 2, C_U = 4, C_W2 = 5, C_O = 8, C_HALO = 40, C_END = 168;
__device__ __align__(128) unsigned g_cnt[C_END * 32];

__device__ __forceinline__ uint32_t smem_u32(const void* p) { return (uint32_t)__cvta_generic_to_shared(p); }
__device__ __forceinline__ void mbar_init(uint32_t bar, uint32_t cnt) { asm volatile("mbarrier.init.shared::cta.b64 [%0], %1;" :: "r"(bar), "r"(cnt)); }
__device__ __forceinline__ void mbar_expect_tx(uint32_t bar, uint32_t bytes) { asm volatile("mbarrier.arrive.expect_tx.shared::cta.b64 _, [%0], %1;" :: "r"(bar), "r"(bytes) : "memory"); }
__device__ __forceinline__ void mbar_arrive(uint32_t bar) { asm volatile("mbarrier.arrive.shared::cta.b64 _, [%0];" :: "r"(bar) : "memory"); }
__device__ __forceinline__ void mbar_wait(uint32_t bar, uint32_t parity) {
  asm volatile("{\n.reg .pred p;\n.reg .u32 n;\nmov.u32 n, 0;\nLAB_WAIT:\n"
               "mbarrier.try_wait.parity.shared::cta.b64 p, [%0], %1;\n@p bra DONE;\n"
               "add.u32 n, n, 1;\nsetp.lt.u32 p, n, 4000000;\n@p bra LAB_WAIT;\ntrap;\nDONE:\n}" :: "r"(bar), "r"(parity) : "memory");
}
__device__ __forceinline__ void mbar_wait_u(uint32_t bar, uint32_t parity) {
  asm volatile("{\n.reg .pred p;\nLAB_WAIT:\nmbarrier.try_wait.parity.shared::cta.b64 p, [%0], %1;\n@!p bra LAB_WAIT;\n}" :: "r"(bar), "r"(parity) : "memory");
}
__device__ __forceinline__ uint32_t mbar_try(uint32_t bar, uint32_t parity) {
  uint32_t ok;
  asm volatile("{\n.reg .pred p;\nmbarrier.test_wait.parity.shared::cta.b64 p, [%1], %2;\nselp.u32 %0, 1, 0, p;\n}" : "=r"(ok) : "r"(bar), "r"(parity) : "memory");
  return ok;
}
__device__ __forceinline__ void tma4d(uint32_t dst, const CUtensorMap* m, int c0, int c1, int c3, uint32_t bar) {
  asm volatile("cp.async.bulk.tensor.4d.shared::cluster.global.mbarrier::complete_tx::bytes [%0], [%1, {%3, %4, %6, %5}], [%2];"
               :: "r"(dst), "l"(m), "r"(bar), "r"(c0), "r"(c1), "r"(c3), "r"(0) : "memory");
}
__device__ __forceinline__ void tma_store(const CUtensorMap* m, int c1, int c3, uint32_t src) {
  asm volatile("cp.async.bulk.tensor.4d.global.shared::cta.bulk_group [%0, {%4, %2, %4, %3}], [%1];" :: "l"(m), "r"(src), "r"(c1), "r"(c3), "r"(0) : "memory");
}
__device__ __forceinline__ void bulk_g2s(uint32_t dst, const void* src, uint32_t bytes, uint32_t bar) {
  asm volatile("cp.async.bulk.shared::cluster.global.mbarrier::complete_tx::bytes [%0], [%1], %2, [%3];" :: "r"(dst), "l"(src), "r"(bytes), "r"(bar) : "memory");
}
__device__ __forceinline__ void bulk_s2g(void* dst, uint32_t src, uint32_t bytes) {
  asm volatile("cp.async.bulk.global.shared::cta.bulk_group [%0], [%1], %2;" :: "l"(dst), "r"(src), "r"(bytes) : "memory");
}
__device__ __forceinline__ void wg_fence() { asm volatile("wgmma.fence.sync.aligned;" ::: "memory"); }
__device__ __forceinline__ void wg_commit() { asm volatile("wgmma.commit_group.sync.aligned;" ::: "memory"); }
template <int N> __device__ __forceinline__ void wg_wait() { asm volatile("wgmma.wait_group.sync.aligned %0;" :: "n"(N) : "memory"); }
__device__ __forceinline__ void proxy_fence() { asm volatile("fence.proxy.async.global;" ::: "memory"); }
#define LIGHT 1
__device__ __forceinline__ void smem_fence() {
  if (LIGHT == 2) return;
  if (LIGHT) asm volatile("mbarrier.init.shared::cta.b64 [%0], 1;" :: "r"(base + OFF_BAR + 248) : "memory");
  else asm volatile("fence.proxy.async.shared::cta;" ::: "memory");
}
__device__ __forceinline__ uint32_t gtime() { uint32_t v; asm volatile("mov.u32 %0, %%globaltimer_lo;" : "=r"(v)); return v; }
__device__ __forceinline__ void publish(int i, bool timed = false) {
  asm volatile("cp.async.bulk.commit_group;" ::: "memory");
  if (timed) asm volatile("red.relaxed.gpu.global.max.u32 [%0], %1;" :: "l"(&g_cnt[i * 32 + 1]), "r"(gtime()) : "memory");
  asm volatile("cp.async.bulk.wait_group 0;" ::: "memory");
  asm volatile("red.relaxed.gpu.global.inc.u32 [%0], 0xffffffff;" :: "l"(&g_cnt[i * 32]) : "memory");
}
__device__ __forceinline__ void spin_ge(int i, unsigned target) {
  asm volatile("{\n.reg .pred p;\n.reg .u32 n, v;\nmov.u32 n, 0;\nLAB_SPIN:\n"
               "ld.relaxed.gpu.global.u32 v, [%0];\nsetp.ge.u32 p, v, %1;\n@p bra DONE;\n"
               "add.u32 n, n, 1;\nsetp.lt.u32 p, n, 4000000;\n@p bra LAB_SPIN;\ntrap;\nDONE:\n}" :: "l"(&g_cnt[i * 32]), "r"(target) : "memory");
}
__device__ __forceinline__ unsigned ld_relaxed(int i) { unsigned v; asm volatile("ld.relaxed.gpu.global.u32 %0, [%1];" : "=r"(v) : "l"(&g_cnt[i * 32]) : "memory"); return v; }
__device__ __forceinline__ bool elect() {
  uint32_t r; asm volatile("{\n.reg .pred p;\nelect.sync _|p, 0xffffffff;\nselp.u32 %0, 1, 0, p;\n}" : "=r"(r)); return r != 0;
}
__device__ __forceinline__ void wait_until(uint32_t tn) { while ((int)(clock() - tn) < 0) __nanosleep(20); }
__device__ __forceinline__ void store_paced(unsigned char* dst, int dstep, uint32_t src, int sstep, int n, int gap, int bytes = 1792) {
  uint32_t tn = clock();
#pragma unroll 1
  for (int i = 0; i < n; i++) { wait_until(tn); bulk_s2g(dst, src, bytes); dst += dstep; src += sstep; tn += gap; }
}
__device__ __forceinline__ uint4 lds128(uint32_t a) { uint4 v; asm volatile("ld.shared.v4.u32 {%0,%1,%2,%3}, [%4];" : "=r"(v.x), "=r"(v.y), "=r"(v.z), "=r"(v.w) : "r"(a) : "memory"); return v; }
__device__ __forceinline__ uint4 lds128_if(uint32_t a, int on) {
  uint4 v;
  asm volatile("{\n.reg .pred p;\nsetp.ne.u32 p, %5, 0;\n@p ld.shared.v4.u32 {%0,%1,%2,%3}, [%4];\n}" : "=r"(v.x), "=r"(v.y), "=r"(v.z), "=r"(v.w) : "r"(a), "r"(on) : "memory");
  return v;
}
__device__ __forceinline__ uint32_t lds32(uint32_t a) { uint32_t v; asm volatile("ld.shared.u32 %0, [%1];" : "=r"(v) : "r"(a) : "memory"); return v; }
__device__ __forceinline__ void sts128(uint32_t p, uint32_t a, uint32_t b, uint32_t c, uint32_t d) { asm volatile("st.shared.v4.u32 [%0], {%1,%2,%3,%4};" :: "r"(p), "r"(a), "r"(b), "r"(c), "r"(d) : "memory"); }
__device__ __forceinline__ void sts64(uint32_t p, float a, float b) { asm volatile("st.shared.v2.f32 [%0], {%1,%2};" :: "r"(p), "f"(a), "f"(b) : "memory"); }
__device__ __forceinline__ void named_sync(int id, int n) { asm volatile("bar.sync %0, %1;" :: "r"(id), "r"(n) : "memory"); }
__device__ __forceinline__ void named_arrive(int id, int n) { asm volatile("bar.arrive %0, %1;" :: "r"(id), "r"(n) : "memory"); }
__device__ __forceinline__ constexpr uint32_t dlo(uint32_t off, uint32_t lbo) { return ((base + off) >> 4) | (lbo >> 4 << 16); }
__device__ __forceinline__ uint32_t pack2(float lo, float hi) { uint32_t r; asm("cvt.rn.bf16x2.f32 %0, %1, %2;" : "=r"(r) : "f"(hi), "f"(lo)); return r; }
__device__ __forceinline__ float bf_lo(uint32_t v) { return __uint_as_float(v << 16); }
__device__ __forceinline__ float bf_hi(uint32_t v) { return __uint_as_float(v & 0xffff0000u); }
__device__ __forceinline__ float rbf(float x) { return bf_lo(pack2(x, 0.f)); }
__device__ __forceinline__ uint32_t hsub2(uint32_t a, uint32_t b) { uint32_t r; asm("sub.rn.bf16x2 %0, %1, %2;" : "=r"(r) : "r"(a), "r"(b)); return r; }
__device__ __forceinline__ uint32_t hadd2(uint32_t a, uint32_t b) { uint32_t r; asm("add.rn.bf16x2 %0, %1, %2;" : "=r"(r) : "r"(a), "r"(b)); return r; }
__device__ __forceinline__ uint32_t hmax2(uint32_t a, uint32_t b) { uint32_t r; asm("max.bf16x2 %0, %1, %2;" : "=r"(r) : "r"(a), "r"(b)); return r; }
__device__ __forceinline__ uint32_t hmul2(uint32_t a, uint32_t b) { uint32_t r; asm("mul.rn.bf16x2 %0, %1, %2;" : "=r"(r) : "r"(a), "r"(b)); return r; }
__device__ __forceinline__ uint32_t hfma2(uint32_t a, uint32_t b, uint32_t c) { uint32_t r; asm("fma.rn.bf16x2 %0, %1, %2, %3;" : "=r"(r) : "r"(a), "r"(b), "r"(c)); return r; }
__device__ __forceinline__ float tanh_fast(float x) { float r; asm("tanh.approx.f32 %0, %1;" : "=f"(r) : "f"(x)); return r; }
__device__ __forceinline__ float rcp_fast(float x) { float r; asm("rcp.approx.ftz.f32 %0, %1;" : "=f"(r) : "f"(x)); return r; }
__device__ __forceinline__ float ex2_fast(float x) { float r; asm("ex2.approx.ftz.f32 %0, %1;" : "=f"(r) : "f"(x)); return r; }
__device__ __forceinline__ void mma16816(float (&c)[4], uint32_t a0, uint32_t a1, uint32_t a2, uint32_t a3, uint32_t b0, uint32_t b1) {
  asm volatile("mma.sync.aligned.m16n8k16.row.col.f32.bf16.bf16.f32 {%0,%1,%2,%3}, {%4,%5,%6,%7}, {%8,%9}, {%0,%1,%2,%3};"
               : "+f"(c[0]), "+f"(c[1]), "+f"(c[2]), "+f"(c[3]) : "r"(a0), "r"(a1), "r"(a2), "r"(a3), "r"(b0), "r"(b1));
}
__device__ __forceinline__ void ldsm4(uint32_t (&r)[4], uint32_t addr) {
  asm volatile("ldmatrix.sync.aligned.m8n8.x4.shared.b16 {%0,%1,%2,%3}, [%4];" : "=r"(r[0]), "=r"(r[1]), "=r"(r[2]), "=r"(r[3]) : "r"(addr) : "memory");
}
__device__ __forceinline__ void stsm4(uint32_t addr, uint32_t a, uint32_t b, uint32_t c, uint32_t d) {
  asm volatile("stmatrix.sync.aligned.m8n8.x4.shared.b16 [%0], {%1,%2,%3,%4};" :: "r"(addr), "r"(a), "r"(b), "r"(c), "r"(d) : "memory");
}
__device__ __forceinline__ void stsm2(uint32_t addr, uint32_t a, uint32_t b) {
  asm volatile("stmatrix.sync.aligned.m8n8.x2.shared.b16 [%0], {%1,%2};" :: "r"(addr), "r"(a), "r"(b) : "memory");
}
__device__ __forceinline__ void load_row(uint32_t (&r)[14], const unsigned char* p, int t) {
#pragma unroll
  for (int i = 0; i < 3; i++)
    asm volatile("ld.global.nc.L1::no_allocate.v4.u32 {%0,%1,%2,%3}, [%4];" : "=r"(r[4 * i]), "=r"(r[4 * i + 1]), "=r"(r[4 * i + 2]), "=r"(r[4 * i + 3]) : "l"(p + i * 64 + t * 16));
  asm volatile("ld.global.nc.L1::no_allocate.v2.u32 {%0,%1}, [%2];" : "=r"(r[12]), "=r"(r[13]) : "l"(p + 192 + t * 8));
}
__device__ __forceinline__ void lds_row(uint32_t* r, uint32_t a, int t) {
#pragma unroll
  for (int i = 0; i < 3; i++) { const uint4 v = lds128(a + i * 64 + t * 16); r[4 * i] = v.x; r[4 * i + 1] = v.y; r[4 * i + 2] = v.z; r[4 * i + 3] = v.w; }
  asm volatile("ld.shared.v2.u32 {%0,%1}, [%2];" : "=r"(r[12]), "=r"(r[13]) : "r"(a + 192 + t * 8) : "memory");
}

__device__ __forceinline__ void tile_row(uint32_t* r, int tok, int d, int t) {
  const int xi = (tok >> 1) & 7;
#pragma unroll
  for (int j = 0; j < 4; j++) {
    const int c = d * 14 + (j < 3 ? 4 * j + t : 12 + (t >> 1));
    const uint4 v = lds128(base + OFF_X + ((tok & 48) + (tok & 1) * 8 + xi) * 896 + (c >> 3) * 128 + (((c ^ ((c >> 3) - xi)) & 7) << 4));
    if (j < 3) { r[4 * j] = v.x; r[4 * j + 1] = v.y; r[4 * j + 2] = v.z; r[4 * j + 3] = v.w; }
    else { r[12] = t & 1 ? v.z : v.x; r[13] = t & 1 ? v.w : v.y; }
  }
}

struct LnC { uint32_t m, rh, rl; float r; };
__device__ __forceinline__ LnC ln_consts(float mean, float var) {
  float sd;
  asm("sqrt.approx.ftz.f32 %0, %1;" : "=f"(sd) : "f"(rbf(rbf(var) + 1e-5f)));
  const float r = rcp_fast(rbf(sd)), rh = rbf(r);
  return {pack2(mean, mean), pack2(rh, rh), pack2(r - rh, r - rh), r};
}
__device__ __forceinline__ float variance(float mean, float sq) { return fmaxf(fmaf(-mean, mean, sq * (1.0f / D_)), 0.f); }
__device__ __forceinline__ uint32_t ln_apply(uint32_t x, const LnC& c) { const uint32_t d = hsub2(x, c.m); return hfma2(d, c.rh, hmul2(d, c.rl)); }

template <int N> __device__ __forceinline__ void fresh(float (&a)[N]) {
#pragma unroll
  for (int i = 0; i < N; i++) asm volatile("" : "=f"(a[i]));
}
__device__ __forceinline__ void pin(uint32_t (&a)[4]) { asm volatile("" : "+r"(a[0]), "+r"(a[1]), "+r"(a[2]), "+r"(a[3])); }
constexpr int B_EMPTY = 64, B_F0 = 128, B_F1 = 136, B_F2 = 144, B_F3 = 152, B_HALO = 160, B_RT = 176, B_RES = 184, B_TS = 192, B_F1B = 200, B_XF = 208, B_X = 216, S_FLAG = 224;
constexpr int N_GO = 6, N_DONE = 7;
__device__ __forceinline__ void watch_flag(int slot, int i, unsigned target) {
  asm volatile("{\n.reg .pred p;\n.reg .u32 n, v, t;\nmov.u32 n, 0;\nLAB_SPIN:\n"
               "ld.relaxed.gpu.global.v2.u32 {v, t}, [%1];\nsetp.ge.u32 p, v, %2;\n@p st.volatile.shared.v2.u32 [%0], {v, t};\n"
               "ld.volatile.shared.u32 v, [%0];\nsetp.ne.u32 p, v, 0;\n@p bra DONE;\n"
               "add.u32 n, n, 1;\nsetp.lt.u32 p, n, 4000000;\n@p bra LAB_SPIN;\ntrap;\nDONE:\n}" :: "r"(bars + S_FLAG + slot * 8), "l"(&g_cnt[i * 32]), "r"(target) : "memory");
}
__device__ __forceinline__ void wait_flag(int slot, int delay) {
  uint32_t v, last;
  do asm volatile("ld.volatile.shared.v2.u32 {%0, %1}, [%2];" : "=r"(v), "=r"(last) : "r"(bars + S_FLAG + slot * 8) : "memory"); while (!v);
  while (gtime() - last < (uint32_t)delay);
}
__device__ __forceinline__ void arrive_if(int id, bool on) {
  asm volatile("{\n.reg .pred p;\nsetp.ne.u32 p, %1, 0;\n@p bar.arrive %0, 256;\n}" :: "r"(id), "r"((uint32_t)on) : "memory");
}
template <int TA, class Hook>
__device__ __forceinline__ void stage(float (&acc)[56], uint32_t ah, uint32_t bh, int sb, uint32_t par, uint32_t& ok, int& g_tr, bool first, bool rel, Hook hook, const uint32_t (*X)[4] = nullptr) {
  if (!ok) { if (WU) mbar_wait_u(bars + sb * 8, par); else mbar_wait(bars + sb * 8, par); }
  wg_fence();
#pragma unroll
  for (int k = 0; k < 4; k++) {
    if constexpr (TA == 2) wgmma_rs_n112<1>(acc, X[k], dlo(sb * SLOT + 8192 + k * 3584, 1792), bh, k || !first);
    else wgmma_n112<TA, 1>(acc, dlo(sb * SLOT + k * (TA ? 2048 : 256), TA ? 8192 : 128), ah, dlo(sb * SLOT + 8192 + k * 3584, 1792), bh, k || !first);
    if (k == 1) ok = mbar_try(bars + ((sb + 1) & 7) * 8, sb == 7 ? par ^ 1 : par);
    hook(k);
  }
  wg_commit();
  wg_wait<1>();
  if (rel) mbar_arrive(bars + B_EMPTY + ((sb + 7) & 7) * 8);
}

struct Params {
  const unsigned char *x, *wqkv, *wo, *w1, *w2;
  const unsigned short *b1, *b2;
  unsigned char* out;
  uint32_t dw, dx, db, dk;
};

__global__ void __launch_bounds__(NTHREADS, 1)
fused_kernel(const Params p, const __grid_constant__ CUtensorMap m_w1, const __grid_constant__ CUtensorMap m_w2, const __grid_constant__ CUtensorMap m_b14,
             const __grid_constant__ CUtensorMap m_a8, const __grid_constant__ CUtensorMap m_b7, const __grid_constant__ CUtensorMap m_xt) {
  extern __shared__ __align__(1024) unsigned char smem_raw[];
  const uint32_t t0 = clock();
  const int tid = threadIdx.x, lane = tid & 31, b = blockIdx.x;
  const int g = lane >> 2, t = lane & 3, r8 = lane & 7, mi = lane >> 3;
  uint32_t H[14];
  if (tid < 128) load_row(H, p.x + (b * 16 + g) * (D_ * 2) + (tid >> 5) * 224, t);
  const int warp = __shfl_sync(0xffffffffu, tid >> 5, 0);
  const int dt = b & 3, mt = b >> 2;
  const bool g1 = b < 112;
  const int ft = mt, d1 = dt;
  if (warp >= 8) {
    if (warp == 8) {
      if (elect()) {
        asm volatile("prefetch.tensormap [%0];" :: "l"(&m_xt) : "memory");
        if (smem_u32(smem_raw) != base) asm volatile("trap;");
#pragma unroll
        for (int i = 0; i < 28; i++) mbar_init(bars + i * 8, i * 8 == B_XF ? 8 : 1);
        sts128(bars + S_FLAG, 0, 0, 0, 0); sts64(bars + S_FLAG + 16, 0.f, 0.f);
        asm volatile("fence.mbarrier_init.release.cluster;" ::: "memory");
      }
      __syncwarp();
      named_arrive(12, 160); named_arrive(13, 160);
    }
    named_sync(15, 128);
    asm volatile("setmaxnreg.dec.sync.aligned.u32 80;");
    if (warp == 8) {
      unsigned tk = 0;
      if (elect()) {
        wait_until(t0 + DLY_X);
        mbar_expect_tx(bars + B_X, 7 * 8192);
        asm volatile("cp.async.bulk.tensor.5d.shared::cluster.global.mbarrier::complete_tx::bytes [%0], [%1, {%4, %4, %4, %4, %3}], [%2];"
                     :: "r"(base + OFF_X), "l"(&m_xt), "r"(bars + B_X), "r"(mt * 4), "r"(0) : "memory");
        wait_until(t0 + DLY_D);
        asm volatile("prefetch.tensormap [%0];" :: "l"(&m_w1) : "memory");
        asm volatile("prefetch.tensormap [%0];" :: "l"(&m_b14) : "memory");
        if (g1) {
#pragma unroll 1
          for (int c = 0; c < 8; c++) {
            wait_until(t0 + DLY_W + c * TPW);
            if (c == 6) mbar_wait(bars + B_XF, 0);
            tma4d(base + c * SLOT, &m_w1, ft * 64, 0, c * 8, bars + c * 8);
          }
        } else {
          const int n = dt < 3 ? 16 : 8;
          mbar_expect_tx(bars + B_RT, n * 5376);
#pragma unroll 1
          for (int i = 0; i < n; i++) { wait_until(t0 + DLY_Q + i * PQ); bulk_g2s(base + i * 5376, p.wqkv + ((mt & 3) * 56 + dt * 16 + i) * 5376, 5376, bars + B_RT); }
        }
#pragma unroll 1
        for (int r = g1 ? 1 : 4; r < 4; r++) {
#pragma unroll
          for (int s = 0; s < 8; s++) {
            mbar_wait_u(bars + B_EMPTY + s * 8, (r & 1) ^ 1);
            tma4d(base + s * SLOT, &m_w1, mt * 64, (r & 2) * 4, (r & 1) * 64 + s * 8, bars + s * 8);
          }
        }
        mbar_wait(bars + B_EMPTY + 5 * 8, 1);
        mbar_wait(bars + B_EMPTY + 5 * 8, 0);
        if (!g1) mbar_wait(bars + B_TS, 0);
#pragma unroll 1
        for (int r = 0; ; r++) {
#pragma unroll
          for (int j = 0; j < 8; j++) {
            const int s = (j + 5) & 7;
            mbar_wait_u(bars + B_EMPTY + s * 8, (r + (j < 3)) & 1);
            tma4d(base + s * SLOT, &m_w2, mt * 64, 0, r * 512 + j * 64, bars + s * 8);
            if (j == 3 && r == 3) goto w2_done;
          }
        }
        w2_done:
        wait_flag(2, 0);
        OBS(1, 22);
#pragma unroll
        for (int s = 1; s < 8; s++) {
          mbar_wait_u(bars + B_EMPTY + s * 8, 1);
          tma4d(base + s * SLOT, &m_a8, 0, s * 8 - 8, G_O + mt * 8, bars + s * 8);
        }
        tk = atomicInc(&g_cnt[C_TICKET * 32], 0xffffffffu);
      }
      if (__any_sync(0xffffffffu, tk == 127)) {
#pragma unroll 1
        for (int i = lane; i < C_END; i += 32) *(uint2*)&g_cnt[i * 32] = make_uint2(0, 0);
      }
    } else if (warp == 9) {
      if (elect()) {
        if (ld_relaxed(C_H) + ld_relaxed(C_H + 1) > 256) asm volatile("trap;");
        {
          wait_until(t0 + DLY_E);
          asm volatile("prefetch.tensormap [%0];" :: "l"(&m_b7) : "memory");
          asm volatile("prefetch.tensormap [%0];" :: "l"(&m_w2) : "memory");
          asm volatile("prefetch.tensormap [%0];" :: "l"(&m_a8) : "memory");
        }
        uint32_t bytes = SLOT;
#pragma unroll 1
        for (int r = g1 ? 0 : 4; r < 11; r++) {
#pragma unroll
          for (int s = 0; s < 8; s++) {
            if (s == 0 && r == 0) { if (NP_H & 1) { wait_until(t0 + DLY_P); watch_flag(0, C_H, 128); } wait_flag(0, SY_H); OBS(1, 16); }
            if (s == 0 && (r == 2 || r == 4)) { mbar_wait(bars + B_F0 + (r >> 2) * 8, 0); OBS(1, 16 + (r >> 1)); if (r == 4) bytes = BT; }
            if (s == 5 && r == 0) mbar_wait(bars + B_XF, 0);
            if (s == 7 && r == 4) mbar_wait(bars + B_F1B, 0);
            if (s == 5 && r == 6) { wait_flag(1, SY_U); OBS(1, 20); bytes = SLOT; }
            if (s) mbar_wait_u(bars + B_EMPTY + s * 8, (r & 1) ^ 1); else mbar_wait(bars + B_EMPTY, (r & 1) ^ 1);
            mbar_expect_tx(bars + s * 8, bytes);
            tma4d(base + s * SLOT + 8192, &m_b14, 0, dt * 14, r * 64 + s * 8, bars + s * 8);
          }
        }
      }
    } else if (warp == 10) {
      uint32_t tn = t0 + PF0;
      const unsigned char* src = p.w1 + (b + (b & ~7)) * 3584 + lane * 128;
#pragma unroll 1
      for (int i = 0; i < 32; i++) {
        wait_until(tn);
        if (i == 8) src -= 16 * 458752 - 8 * 3584;
        if (i == 16) src = p.w2 + b * 3584 + lane * 128;
        if (lane < 28) asm volatile("prefetch.global.L2 [%0];" :: "l"(src) : "memory");
        __syncwarp();
        src += i < 16 ? 2 * 458752 : 458752;
        tn += i < 16 ? PACE1 : PACE2;
      }
      watch_flag(1, C_U, 128);
      watch_flag(2, C_O + mt, 16);
    } else {
      unsigned char* dst = g_scr + (G_H + b) * GRP;
      asm volatile("" : "+l"(dst));
      named_sync(10, 160);
      smem_fence();
      if (elect()) { bulk_s2g(dst, base + OFF_KV, GRP); publish(C_H, true); OBS(1, 3); }
      __syncwarp();
      if (g1 && (NP_H & 2)) { wait_until(t0 + DLY_P + PH_H); watch_flag(0, C_H, 128); }
      named_sync(9, 160);
      smem_fence();
      if (elect()) {
        if (g1 && SY_B) { wait_flag(0, SY_B); store_paced(dst + 128 * GRP, 1792, base + OFF_KV + GRP, 1792, 4, PS_H); }
        else bulk_s2g(dst + 128 * GRP, base + OFF_KV + GRP, GRP);
        bulk_s2g(g_scr + G_END * GRP + b * 256, base + OFF_PART + 1024, 256);
        publish(C_H + 1);
        OBS(1, 4);
      }
      __syncwarp();
      if (!g1) {
        const int kg0 = (mt & 3) * 14 + dt * 4, nk = dt < 3 ? 4 : 2;
#pragma unroll 1
        for (int m = 0; m < 3; m++) {
          named_sync(m == 0 ? 14 : (m == 1 ? 4 : 15), 160);
          smem_fence();
          if (elect()) {
            if (m == 2) {
              mbar_expect_tx(bars + B_RT, nk * GRP);
#pragma unroll 1
              for (int i = 0; i < nk; i++) bulk_g2s(base + i * SLOT, p.wo + (kg0 + i) * GRP, GRP, bars + B_RT);
            }
            bulk_s2g(g_scr + (G_W + m * 56 + kg0) * GRP, base + (12 + m * 4) * GRP, nk * GRP);
            if (m != 1) publish(m ? C_W2 : C_W);
            OBS(m != 1, 5 + (m >> 1));
          }
          __syncwarp();
        }
      }
      spin_ge(C_H + 1, 128);
      if (lane == 0) mbar_arrive(bars + B_F0);
      spin_ge(C_W, 16);
      if (lane == 0) mbar_arrive(bars + B_F1);
      spin_ge(C_W2, 16);
      if (lane == 0) mbar_arrive(bars + B_F1B);
      if (mt == 0) {
#pragma unroll
        for (int i = 0; i < 14; i++) sts128(base + OFF_KV + (i / 7) * KV + (i % 7) * 512 + lane * 16, 0, 0, 0, 0);
        smem_fence();
        __syncwarp();
        if (lane < 2) mbar_arrive(bars + B_HALO + lane * 8);
      }
      const unsigned have = EARLY && mt > 0 ? ld_relaxed(C_HALO + b - 4) : 0;
      if (g1) {
        named_sync(14, 160);
        smem_fence();
        if (elect()) tma_store(&m_b7, d1 * 14, G_U + ft * 8, base + OFF_U);
        named_sync(10, 160);
        smem_fence();
        if (elect()) { tma_store(&m_b7, d1 * 14 + 7, G_U + ft * 8, base + OFF_U + GRP); publish(C_U, true); OBS(1, 7); }
        __syncwarp();
      }
#pragma unroll 1
      for (int i = 0; i < 2; i++) {
        unsigned char* hg = g_scr + (G_HALO + b) * GRP + i * 3584;
        named_sync(i ? 0 : 11, 64);
        smem_fence();
        if (mt < 31 && elect()) { bulk_s2g(hg, base + OFF_KV + i * KV + 8 * 1792, 3584); publish(C_HALO + b); }
        OBS(lane == 0, i ? 15 : 23);
        if (mt > 0) {
          if (have <= i) spin_ge(C_HALO + b - 4, i + 1);
          if (elect()) { mbar_expect_tx(bars + B_HALO + i * 8, 3584); bulk_g2s(base + OFF_KV + i * KV, hg - 4 * GRP, 3584, bars + B_HALO + i * 8); }
        }
        __syncwarp();
      }
    }
  } else {
    const int wg = warp >> 2, w4 = warp & 3;
    const bool rel = (tid & 127) == 0;
#pragma unroll 1
    for (int trip = wg && DRY ? 0 : 1; trip < 2; trip++) {
      if (wg && trip) { named_sync(13, 160); mbar_wait(bars + B_X, 0); OBS(rel, 29); tile_row(H, dt * 16 + 8 + g, w4, t); }
      const uint32_t part = base + OFF_PART + (wg + trip) * 256 + g * 32, st = base + OFF_KV + wg * GRP + (w4 * 14 + mi) * 128 + r8 * 16;
      float s0 = 0.f, s1 = 0.f, q0 = 0.f, q1 = 0.f;
#pragma unroll
      for (int j = 0; j < 14; j++) { const float a = bf_lo(H[j]), c = bf_hi(H[j]); s0 += a; s1 += c; q0 = fmaf(a, a, q0); q1 = fmaf(c, c, q1); }
      s0 += s1; q0 += q1;
#pragma unroll
      for (int o = 1; o < 4; o <<= 1) { s0 += __shfl_xor_sync(0xffffffffu, s0, o); q0 += __shfl_xor_sync(0xffffffffu, q0, o); }
      if (t == 0) sts64(part + wg * 256 + w4 * 8, s0, q0);
      OBS(tid == 0, 0);
      named_sync(1 + wg, 128);
      const uint4 u = lds128(part + wg * 256), v = lds128(part + wg * 256 + 16);
      const float mean = ((__uint_as_float(u.x) + __uint_as_float(u.z)) + (__uint_as_float(v.x) + __uint_as_float(v.z))) * (1.0f / D_);
      const float var = variance(mean, (__uint_as_float(u.y) + __uint_as_float(u.w)) + (__uint_as_float(v.y) + __uint_as_float(v.w)));
      const LnC l = ln_consts(mean, var), l2 = ln_consts((mean - bf_lo(l.m)) * l.r, var * l.r * l.r);
      if (w4 == 0 && t == 0) sts128(base + OFF_PART + 1024 + wg * 128 + g * 16, l.m, l.rh, l.rl, 0);
#pragma unroll
      for (int j = 0; j < 14; j++) H[j] = ln_apply(ln_apply(H[j], l), l2);
#pragma unroll
      for (int i = 0; i < 3; i++) stsm4(st + i * 512, H[4 * i], H[4 * i + 1], H[4 * i + 2], H[4 * i + 3]);
      stsm2(st + 1536, H[12], H[13]);
      if (trip) named_arrive(10 - wg, 160);
      OBS(rel, 1 + wg);
    }
    uint32_t ok = 0;
    int trc = 0;
    auto nohook = [](int) {};
#define OBS0(c, i) ok = 0
    const uint32_t sx = base + OFF_KV + (tid & 127) * 16;
    if (wg == 0) {
      uint32_t hb[4], R[28];
#pragma unroll
      for (int i = 0; i < 4; i++)
        asm volatile("ld.relaxed.cta.global.u16 %0, [%1];" : "=r"(hb[i]) : "l"((i < 2 ? p.b1 + (g1 ? mt * 64 : 0) : p.b2 + mt * 64) + w4 * 16 + g + (i & 1) * 8) : "memory");
      named_sync(12, 160);
      mbar_wait(bars + B_X, 0);
#pragma unroll
      for (int h = 0; h < 2; h++) tile_row(R + h * 14, w4 * 16 + h * 8 + g, dt, t);
#pragma unroll
      for (int i = 0; i < 28; i++) asm volatile("" : "+r"(R[i]));
      if (lane == 0) mbar_arrive(bars + B_XF + (R[0] | R[4] | R[8] | R[12] | R[14] | R[18] | R[22] | R[26]) * threadIdx.y);
      float acc[56];
      if (g1) {
#pragma unroll
        for (int i = 0; i < 56; i++) { acc[i] = bf_lo(hb[(i >> 1) & 1]); asm volatile("" : "+f"(acc[i])); }
        if (w4 < (NP_H >> 2)) { wait_until(clock() + w4 * PH_H); watch_flag(0, C_H, 128); }
        OBS0(0, 5);
#pragma unroll 1
        for (int r = 0; r < 4; r++)
#pragma unroll
          for (int c = 0; c < 8; c++) stage<1>(acc, p.dw, p.db, c, r & 1, ok, trc, false, rel && (c || r), [&](int k) { if (c == 7 && k == 3 - HK) arrive_if(3, r == 3); });
        wg_wait<0>();
        if (rel) mbar_arrive(bars + B_EMPTY + 7 * 8);
        OBS(rel, 6);
        const uint32_t us = base + OFF_U + (w4 * 2 + (mi & 1)) * 896 + (mi >> 1) * 128 + r8 * 16;
#pragma unroll
        for (int hf = 0; hf < 2; hf++) {
          uint32_t U[14];
#pragma unroll
          for (int j = 0; j < 14; j++) {
            const float a = acc[hf * 28 + 2 * j], c = acc[hf * 28 + 2 * j + 1];
            U[j] = pack2(fmaf(a, tanh_fast(a * fmaf(a * a, 0.0356774081f, 0.7978845608f)), a), fmaf(c, tanh_fast(c * fmaf(c * c, 0.0356774081f, 0.7978845608f)), c));
          }
#pragma unroll
          for (int j = 0; j < 3; j++) stsm4(us + hf * GRP + j * 256, U[4 * j], U[4 * j + 1], U[4 * j + 2], U[4 * j + 3]);
          stsm2(us + hf * GRP + 768, U[12], U[13]);
          named_arrive(hf ? 10 : 14, 160);
          if (!hf) mbar_wait(bars + B_X, 0);
        }
        OBS(rel, 30);
      } else {
        named_arrive(3, 256);
        const int kg0 = (mt & 3) * 14 + dt * 4, nk = dt < 3 ? 4 : 2;
        mbar_wait(bars + B_XF, 0);
        mbar_wait(bars + B_RT, 0);
        OBS(tid == 0, 7);
#pragma unroll 1
        for (int m = 1; m < 4; m++) {
          if (w4 < nk) {
            uint4 v[14];
#pragma unroll
            for (int l = 0; l < 14; l++) v[l] = lds128(base + (w4 * 8 + r8) * 2688 + (m % 3) * 896 + (l >> 1) * 128 + ((r8 + mi + (l & 1) * 4) & 7) * 16);
#pragma unroll
            for (int l = 0; l < 14; l++) sts128(base + (8 + m * 4 + w4) * GRP + (l >> 1) * 1024 + ((r8 + mi + (l & 1) * 4) & 7) * 128 + r8 * 16, v[l].x, v[l].y, v[l].z, v[l].w);
          }
          named_arrive(m == 1 ? 14 : (m == 2 ? 4 : 15), 160);
        }
        mbar_wait(bars + B_RT, 1);
        uint32_t W[4][14];
#pragma unroll
        for (int i = 0; i < 4; i++) lds_row(W[i], base + i * SLOT + g * 896 + w4 * 224, t);
        named_sync(1, 128);
#pragma unroll
        for (int i = 0; i < 4; i++) {
          const uint32_t st = base + i * SLOT + (w4 * 14 + mi) * 128 + r8 * 16;
#pragma unroll
          for (int j = 0; j < 3; j++) stsm4(st + j * 512, W[i][4 * j], W[i][4 * j + 1], W[i][4 * j + 2], W[i][4 * j + 3]);
          stsm2(st + 1536, W[i][12], W[i][13]);
        }
        smem_fence();
        named_sync(1, 128);
        if (w4 == 0 && elect()) {
#pragma unroll 1
          for (int i = 0; i < nk; i++) bulk_s2g(g_scr + (G_WO + kg0 + i) * GRP, base + i * SLOT, GRP);
          publish(C_U);
          mbar_arrive(bars + B_TS);
          OBS(1, 16);
        }
        __syncwarp();
      }
#pragma unroll
      for (int i = 0; i < 56; i++) { acc[i] = 0.f; asm volatile("" : "+f"(acc[i])); }
#pragma unroll
      for (int i = 2; i < 4; i++) { hb[i] = hmul2(hb[i] * 0x10001u, 0x3f003f00u); asm volatile("" : "+r"(hb[i])); }
      const int ro = (mt * 64 + w4 * 16 + g) * (D_ * 2) + dt * 224;
      unsigned char *outp = p.out + ro + t * 16, *outq = p.out + ro + 192 + t * 8;
      asm volatile("" : "+l"(outp), "+l"(outq));
      if (w4 < NP_U) { wait_until(clock() + PU0 + w4 * PH_U); watch_flag(1, C_U, 128); }
      if (SY_G) wait_flag(1, SY_G);
      named_sync(5, 256);
      OBS0(21, 10);
#pragma unroll 1
      for (int r = 0; ; r++) {
#pragma unroll
        for (int j = 0; j < 8; j++) {
          const bool site = j == SA % 8 || j == SB % 8, yield = (j == SA % 8 && r == SA / 8) || (j == SB % 8 && r == SB / 8);
          stage<1>(acc, p.dw, p.db, (j + 5) & 7, (r + (j > 2)) & 1, ok, trc, false, rel && (j || r), [&](int k) {
            if (k == 3 - HK) { if (site) arrive_if(N_GO, yield); if (j == 3) arrive_if(8, r == 3); } });
          if (site && yield) named_sync(N_DONE, 256);
          if (j == 3 && r == 3) goto gemm2_done;
        }
      }
      gemm2_done:
      wg_wait<0>();
      OBS(rel, 24);
      uint32_t G[28], dep = 0;
#pragma unroll
      for (int j = 0; j < 28; j++) {
        const uint32_t hh = hfma2(pack2(acc[2 * j], acc[2 * j + 1]), 0x3e803e80u, hb[2 + (j & 1)]);
        const float a = bf_lo(hh), c = bf_hi(hh);
        G[j] = pack2(fmaf(a, tanh_fast(a), a), fmaf(c, tanh_fast(c), c));
        dep |= G[j];
      }
      OBS(rel, 26);
#pragma unroll 1
      for (int trip = TAILDRY ? 0 : 1; trip < 2; trip++) {
        if (trip) named_sync(12 + w4 + dep * threadIdx.y, 64);
        uint4 S4[8];
#pragma unroll
        for (int i = 0; i < 8; i++) S4[i] = lds128_if(sx + i * 2048, trip);
        OBS(rel, 123);
#pragma unroll
        for (int i = 0; i < 8; i++) {
          const uint32_t Sv[4] = {S4[i].x, S4[i].y, S4[i].z, S4[i].w};
          const int h = i & 1, n = i >> 1;
          uint32_t Y[4];
#pragma unroll
          for (int j = 0; j < (n < 3 ? 4 : 2); j++) Y[j] = hadd2(R[h * 14 + 4 * n + j], hmul2(Sv[j], G[8 * n + 2 * j + h]));
          if (n < 3) asm volatile("{\n.reg .pred p;\nsetp.ne.u32 p, %5, 0;\n@p st.global.v4.u32 [%0], {%1,%2,%3,%4};\n}" :: "l"(outp + h * 8 * D_ * 2 + n * 64), "r"(Y[0]), "r"(Y[1]), "r"(Y[2]), "r"(Y[3]), "r"(trip) : "memory");
          else asm volatile("{\n.reg .pred p;\nsetp.ne.u32 p, %3, 0;\n@p st.global.v2.u32 [%0], {%1,%2};\n}" :: "l"(outq + h * 8 * D_ * 2), "r"(Y[0]), "r"(Y[1]), "r"(trip) : "memory");
        }
      }
      OBS(rel, 28);
    } else {
      asm volatile("setmaxnreg.inc.sync.aligned.u32 256;");
      float ka[56];
      const uint32_t nat = w4 * 3584 + (mi >> 1) * 128 + (r8 >> 2) * 1792 + (((2 * r8) & 7) + ((mi & 1) ^ (r8 >> 2))) * 16;
      {
        uint32_t X[28][4];
#pragma unroll
        for (int k = 0; k < 28; k++)
          ldsm4(X[k], base + OFF_X + (w4 * 16 + (mi & 1) * 8 + r8) * 896 + (k >> 2) * 128 + ((((2 * (k & 3) + (mi >> 1)) ^ ((k >> 2) - r8)) & 7) << 4));
        uint32_t all = 0;
#pragma unroll
        for (int k = 0; k < 28; k++) all |= X[k][0];
        if (lane == 0) mbar_arrive(bars + B_XF + all * threadIdx.y);
        mbar_wait(bars + B_F0, 0);
        LnC l[2];
#pragma unroll
        for (int h = 0; h < 2; h++)
          asm volatile("ld.relaxed.gpu.global.v4.u32 {%0,%1,%2,%3}, [%4];" : "=r"(l[h].m), "=r"(l[h].rh), "=r"(l[h].rl), "=f"(l[h].r) : "l"(g_scr + G_END * GRP + (mt * 64 + w4 * 16 + 2 * g + h) * 16) : "memory");
        int once = threadIdx.y;
#pragma unroll 1
        do {
#pragma unroll
          for (int k = 0; k < 112; k++) X[k >> 2][k & 3] = ln_apply(X[k >> 2][k & 3], l[k & 1]);
        } while (once--);
        OBS(rel, 122);
        float va[56];
        const uint32_t kst = base + OFF_KV + (2 + 2 * w4 + (mi & 1)) * 1792 + (mi >> 1) * 128 + r8 * 16;
        const uint32_t vst = base + OFF_KV + KV + 3584 + nat;
        auto put = [&](const float (&a)[56], uint32_t dst, int n) {
          stsm4(dst + n * 128, pack2(a[4 * n], a[4 * n + 1]), pack2(a[4 * n + 2], a[4 * n + 3]), pack2(a[4 * n + 4], a[4 * n + 5]), pack2(a[4 * n + 6], a[4 * n + 7])); };
        named_sync(3, 256);
        fresh(ka);
        OBS0(0, 8);
#pragma unroll
        for (int c = 0; c < 7; c++) stage<2>(ka, 0, p.db, c, 0, ok, trc, c == 0, rel && c, nohook, &X[c * 4]);
        fresh(va);
#pragma unroll
        for (int c = 7; c < 14; c++)
          stage<2>(va, 0, p.db, c & 7, c >> 3, ok, trc, c == 7, rel, [&](int k) {
            if (c > 7 && (c - 8) * 4 + k < 7) put(ka, kst, (c - 8) * 8 + k * 2);
            if (c == 9 && k == 3 && w4 == 3) named_arrive(11, 64); }, &X[(c - 7) * 4]);
        fresh(ka);
        OBS(rel, 9);
#pragma unroll
        for (int c = 14; c < 21; c++)
          stage<2>(ka, 0, p.db, c & 7, (c >> 3) & 1, ok, trc, c == 14, rel, [&](int k) {
            if (c > 14 && (c - 15) * 4 + k < 7) put(va, vst, (c - 15) * 8 + k * 2);
            if (c == 16 && k == 3 && w4 == 3) named_arrive(0, 64);
            if (SA >= 0 && c == 20 && k == 3 - HK) named_arrive(5, 256); }, &X[(c - 14) * 4]);
        smem_fence();
        wg_wait<0>();
        if (rel) mbar_arrive(bars + B_EMPTY + 4 * 8);
      }
      {
        uint32_t Q[8][4];
#pragma unroll
        for (int i = 0; i < 16; i++) {
          const int n = i - (i + 4) / 8;
#pragma unroll
          for (int h = 0; h < 2; h++) {
            const uint32_t v = pack2(ka[4 * n + 2 * h], ka[4 * n + 2 * h + 1]);
            Q[i >> 1][(i & 1) * 2 + h] = (i & 7) == 3 ? (t < 2 ? v : 0u) : ((i & 7) == 4 ? (t < 2 ? 0u : v) : v);
          }
        }
#pragma unroll
        for (int i = 0; i < 8; i++) pin(Q[i]);
        float Sc[4][40], O[4][16];
        mbar_wait(bars + B_HALO, 0);
        OBS(rel, 11);
#pragma unroll
        for (int hh = 0; hh < 4; hh++) fresh(Sc[hh]);
        wg_fence();
        if (SA >= 0) named_sync(N_GO, 256); else named_sync(2, 128);
#pragma unroll
        for (int k = 0; k < 2; k++)
#pragma unroll
          for (int hh = 0; hh < 4; hh++) {
            if (k == 1 && hh == (SA < 0 ? 2 : 3)) named_arrive(SA < 0 ? 5 : N_DONE, 256);
            wgmma_rs_n80<0>(Sc[hh], Q[hh * 2 + k], dlo(OFF_KV + (hh * 7 / 2 + 2 * k) * 128, 128), p.dk, k);
          }
        wg_commit();
        const bool e0 = 2 * t > g, e1 = 2 * t + 1 > g;
        const uint32_t em = (e0 ? 0xffffu : 0u) | (e1 ? 0xffff0000u : 0u);
        uint32_t L[4][2], M[6];
#pragma unroll
        for (int j = 0; j < 5; j++) { M[j] = j == w4 ? em : (j == w4 + 1 ? ~em : 0u); asm volatile("" : "+r"(M[j])); }
        M[5] = threadIdx.y;
        const uint32_t meta = 0x88dddd88u + M[5];
        wg_wait<0>();
        OBS(rel, 12);
        const uint32_t edge = mt == 0 ? em : 0u;
        auto pick = [&](int w) {
#pragma unroll
          for (int hh = 0; hh < 4; hh++)
#pragma unroll
            for (int h = 0; h < 2; h++) {
              const int i = (2 * w + h) * 4 + 2 * h;
              const uint32_t v = pack2(e0 ? Sc[hh][i] : Sc[hh][i + 8], e1 ? Sc[hh][i + 1] : Sc[hh][i + 9]);
              L[hh][h] = hfma2(v, 0x3e423e42u, hmul2(v, 0xb9f7b9f7u));
              if (w == 0) L[hh][h] = (L[hh][h] & ~edge) | (0xce6ece6eu & edge);
              asm volatile("" : "+r"(L[hh][h]));
            }
        };
        if (w4 == 0) pick(0); else if (w4 == 1) pick(1); else if (w4 == 2) pick(2); else pick(3);
        uint32_t A[4][3][4], mx[4];
        float P[8][2], sm[8];
#pragma unroll
        for (int hh = 0; hh < 4; hh++) mx[hh] = hmax2(__byte_perm(L[hh][0], L[hh][1], 0x5410), __byte_perm(L[hh][0], L[hh][1], 0x7632));
        const uint32_t x1 = 1 + ((mx[0] | mx[1] | mx[2] | mx[3]) & M[5]);
#pragma unroll
        for (int hh = 0; hh < 4; hh++) mx[hh] = hmax2(mx[hh], __shfl_xor_sync(0xffffffffu, mx[hh], x1));
#pragma unroll
        for (int hh = 0; hh < 4; hh++) mx[hh] = hmax2(mx[hh], __shfl_xor_sync(0xffffffffu, mx[hh], 2));
        uint32_t x2 = 0;
#pragma unroll
        for (int i = 0; i < 8; i++) {
          const float m = (i & 1 ? bf_hi(mx[i >> 1]) : bf_lo(mx[i >> 1])) * -LOG2E;
          P[i][0] = ex2_fast(fmaf(bf_lo(L[i >> 1][i & 1]), LOG2E, m)); P[i][1] = ex2_fast(fmaf(bf_hi(L[i >> 1][i & 1]), LOG2E, m));
          sm[i] = P[i][0] + P[i][1];
          x2 |= __float_as_uint(sm[i]);
        }
        x2 = 1 + (x2 & M[5]);
#pragma unroll
        for (int i = 0; i < 8; i++) sm[i] += __shfl_xor_sync(0xffffffffu, sm[i], x2);
#pragma unroll
        for (int i = 0; i < 8; i++) sm[i] += __shfl_xor_sync(0xffffffffu, sm[i], 2);
#pragma unroll
        for (int i = 0; i < 8; i++) {
          const float inv = rcp_fast(sm[i]);
          const uint32_t pp = pack2(P[i][0] * inv, P[i][1] * inv);
#pragma unroll
          for (int j = 0; j < 6; j++) A[i >> 1][j >> 1][(j & 1) * 2 + (i & 1)] = pp & M[j < 4 ? j : 9 - j];
        }
#pragma unroll
        for (int hh = 0; hh < 4; hh++) fresh(O[hh]);
#pragma unroll
        for (int i = 0; i < 12; i++) pin(A[i / 3][i % 3]);
        OBS(rel, 13);
        mbar_wait(bars + B_HALO + 8, 0);
        OBS(rel, 31);
        named_sync(N_GO, 256);
        wg_fence();
        const uint32_t ost = base + OFF_U + nat;
        auto opair = [&](int m, int h2) {
          const int hb2 = m / 7 * 2, r = m % 7;
          const float f0 = LATE ? sm[2 * hb2 + h2 / 2] : 1.f, f1 = LATE ? sm[2 * hb2 + 2 + h2 / 2] : 1.f, f = t < 2 ? f0 : f1;
          if (r < 3) return pack2(O[hb2][4 * r + h2] * f0, O[hb2][4 * r + h2 + 1] * f0);
          if (r == 3) return pack2((t < 2 ? O[hb2][12 + h2] : O[hb2 + 1][h2]) * f, (t < 2 ? O[hb2][13 + h2] : O[hb2 + 1][h2 + 1]) * f);
          return pack2(O[hb2 + 1][4 * (r - 3) + h2] * f1, O[hb2 + 1][4 * (r - 3) + h2 + 1] * f1);
        };
        auto oput = [&](int n) { stsm4(ost + n * 128, opair(n, 0), opair(n, 2), opair(n + 1, 0), opair(n + 1, 2)); };
        auto pv = [&](int hh, int j) { wgmma_sp_n32(O[hh], A[hh][j], dlo(OFF_KV + KV + hh * 7 / 2 * 128 + (j ? j + 1 : 0) * 3584, 1792), p.db, meta, j); };
#pragma unroll
        for (int i = 0; i < 12; i++) {
          if (i == 10 && !HOLD) named_arrive(N_DONE, 256);
          pv(i & 3, i >> 2);
          if (LATE && i < 8) { sm[i] = P[i][0] + P[i][1]; sm[i] += __shfl_xor_sync(0xffffffffu, sm[i], 1); }
        }
        wg_commit();
        if (LATE) {
#pragma unroll
          for (int i = 0; i < 8; i++) sm[i] = rcp_fast(sm[i] + __shfl_xor_sync(0xffffffffu, sm[i], 2));
        }
        if (HOLD == 1) named_arrive(N_DONE, 256);
        OBS(rel, 19);
        wg_wait<0>();
        OBS(rel, 21);
#pragma unroll
        for (int n = 0; n < 14; n += 2) { if (HOLD > 1 && n == 2 * (HOLD - 2)) named_arrive(N_DONE, 256); oput(n); }
        smem_fence();
        __syncwarp();
        OBS(rel, 14);
        if (elect()) {
          wait_until(clock() + w4 * PS_O);
          store_paced(g_scr + (G_O + mt * 8 + w4 * 2) * GRP + dt * 1792, GRP, base + OFF_U + w4 * 3584, 1792, 2, 4 * PS_O);
          publish(C_O + mt);
        }
        OBS(rel, 120);
        __syncwarp();
        if (w4 < NP_O) { wait_until(clock() + PH_O); watch_flag(2, C_O + mt, 16); }
      }
      named_sync(8, 256);
      fresh(ka);
      OBS0(49, 25);
#pragma unroll
      for (int c = 49; c < 56; c++) stage<0>(ka, p.dx, p.db, c & 7, 0, ok, trc, c == 49, false, nohook);
      wg_wait<0>();
      OBS(rel, 27);
#pragma unroll
      for (int i = 0; i < 8; i++) {
        const float* a = ka + (i >> 1) * 16 + (i & 1) * 2;
        const uint32_t dst = (sx ^ ((i & 1) * 64)) + i * 2048, v0 = pack2(a[0], a[1]), v1 = pack2(a[4], a[5]);
        if (i < 6) sts128(dst, v0, v1, pack2(a[8], a[9]), pack2(a[12], a[13])); else sts64(dst, __uint_as_float(v0), __uint_as_float(v1));
      }
      named_arrive(12 + w4, 64);
      OBS(rel, 121);
    }
  }
}

typedef CUresult (*EncFn)(CUtensorMap*, CUtensorMapDataType, cuuint32_t, void*, const cuuint64_t*, const cuuint64_t*, const cuuint32_t*,
                          const cuuint32_t*, CUtensorMapInterleave, CUtensorMapSwizzle, CUtensorMapL2promotion, CUtensorMapFloatOOBfill);
void enc(EncFn f, CUtensorMap* m, const void* ptr, const cuuint64_t (&gd)[4], const cuuint64_t (&gs)[3], const cuuint32_t (&bx)[4], CUtensorMapSwizzle sw) {
  cuuint32_t es[4] = {1, 1, 1, 1};
  f(m, CU_TENSOR_MAP_DATA_TYPE_BFLOAT16, 4, (void*)ptr, gd, gs, bx, es, CU_TENSOR_MAP_INTERLEAVE_NONE, sw,
    CU_TENSOR_MAP_L2_PROMOTION_L2_128B, CU_TENSOR_MAP_FLOAT_OOB_FILL_NONE);
}
}

extern "C" void kernel_launch(void* const* d_in, const int* in_sizes, int n_in, void* d_out, int out_size) {
  (void)in_sizes; (void)n_in; (void)out_size;
  void* fp = nullptr;
  cudaDriverEntryPointQueryResult qr;
  cudaGetDriverEntryPoint("cuTensorMapEncodeTiled", &fp, cudaEnableDefault, &qr);
  EncFn f = (EncFn)fp;
  CUtensorMap m_w1, m_w2, m_b14, m_a8, m_b7, m_xt;
  void* scr = nullptr;
  cudaGetSymbolAddress(&scr, g_scr);
  enc(f, &m_w1, d_in[4], {F_, 16, 1, S_ / 16}, {F_ * 2, F_ * 2, F_ * 32}, {64, 8, 1, 8}, CU_TENSOR_MAP_SWIZZLE_128B);
  {
    cuuint64_t gd[5] = {64, 7, 8, 2, S_ / 16}, gs[4] = {128, D_ * 4, D_ * 2, D_ * 32};
    cuuint32_t bx[5] = {64, 7, 8, 2, 4}, es[5] = {1, 1, 1, 1, 1};
    f(&m_xt, CU_TENSOR_MAP_DATA_TYPE_BFLOAT16, 5, d_in[0], gd, gs, bx, es, CU_TENSOR_MAP_INTERLEAVE_NONE, CU_TENSOR_MAP_SWIZZLE_128B,
      CU_TENSOR_MAP_L2_PROMOTION_L2_128B, CU_TENSOR_MAP_FLOAT_OOB_FILL_NONE);
  }
  enc(f, &m_w2, d_in[6], {S_, 1, 1, F_}, {S_ * 2, S_ * 2, S_ * 2}, {64, 1, 1, 64}, CU_TENSOR_MAP_SWIZZLE_128B);
  enc(f, &m_b14, scr, {64, 56, 1, G_END}, {128, GRP, GRP}, {64, 14, 1, 8}, CU_TENSOR_MAP_SWIZZLE_NONE);
  enc(f, &m_b7, scr, {64, 56, 1, G_END}, {128, GRP, GRP}, {64, 7, 1, 8}, CU_TENSOR_MAP_SWIZZLE_NONE);
  enc(f, &m_a8, scr, {64, 56, 1, G_END}, {128, GRP, GRP}, {64, 8, 1, 8}, CU_TENSOR_MAP_SWIZZLE_NONE);
  Params p;
  p.x = (const unsigned char*)d_in[0]; p.wqkv = (const unsigned char*)d_in[1]; p.wo = (const unsigned char*)d_in[2];
  p.w1 = (const unsigned char*)d_in[4]; p.b1 = (const unsigned short*)d_in[5];
  p.w2 = (const unsigned char*)d_in[6]; p.b2 = (const unsigned short*)d_in[7];
  p.out = (unsigned char*)d_out;
  p.dw = 0x40000040u; p.dx = 64; p.db = 8; p.dk = 112;
  cudaFuncSetAttribute(fused_kernel, cudaFuncAttributeMaxDynamicSharedMemorySize, SMEM_BYTES);
  fused_kernel<<<128, NTHREADS, SMEM_BYTES, cudaStreamPerThread>>>(p, m_w1, m_w2, m_b14, m_a8, m_b7, m_xt);
}
```

```cpp
#include <cuda_runtime.h>
#include <cuda.h>
#include <cuda_bf16.h>
#include <stdint.h>

template<int TA, int TB> __device__ __forceinline__ void wgmma_n112(float (&d)[56], uint32_t al, uint32_t ah, uint32_t bl, uint32_t bh, int sc) {
  asm volatile("{\n.reg .pred p;\n.reg .b64 a, b;\nsetp.ne.b32 p, %60, 0;\nmov.b64 a, {%56, %57};\nmov.b64 b, {%58, %59};\n"
    "wgmma.mma_async.sync.aligned.m64n112k16.f32.bf16.bf16 {%0, %1, %2, %3, %4, %5, %6, %7, %8, %9, %10, %11, %12, %13, %14, %15, %16, %17, %18, %19, %20, %21, %22, %23, %24, %25, %26, %27, %28, %29, %30, %31, %32, %33, %34, %35, %36, %37, %38, %39, %40, %41, %42, %43, %44, %45, %46, %47, %48, %49, %50, %51, %52, %53, %54, %55}, a, b, p, 1, 1, %61, %62;\n}\n"
    : "+f"(d[0]), "+f"(d[1]), "+f"(d[2]), "+f"(d[3]), "+f"(d[4]), "+f"(d[5]), "+f"(d[6]), "+f"(d[7]), "+f"(d[8]), "+f"(d[9]), "+f"(d[10]), "+f"(d[11]), "+f"(d[12]), "+f"(d[13]), "+f"(d[14]), "+f"(d[15]), "+f"(d[16]), "+f"(d[17]), "+f"(d[18]), "+f"(d[19]), "+f"(d[20]), "+f"(d[21]), "+f"(d[22]), "+f"(d[23]), "+f"(d[24]), "+f"(d[25]), "+f"(d[26]), "+f"(d[27]), "+f"(d[28]), "+f"(d[29]), "+f"(d[30]), "+f"(d[31]), "+f"(d[32]), "+f"(d[33]), "+f"(d[34]), "+f"(d[35]), "+f"(d[36]), "+f"(d[37]), "+f"(d[38]), "+f"(d[39]), "+f"(d[40]), "+f"(d[41]), "+f"(d[42]), "+f"(d[43]), "+f"(d[44]), "+f"(d[45]), "+f"(d[46]), "+f"(d[47]), "+f"(d[48]), "+f"(d[49]), "+f"(d[50]), "+f"(d[51]), "+f"(d[52]), "+f"(d[53]), "+f"(d[54]), "+f"(d[55])
    : "r"(al), "r"(ah), "r"(bl), "r"(bh), "r"(sc), "n"(TA), "n"(TB));
}

template<int TB> __device__ __forceinline__ void wgmma_rs_n80(float (&d)[40], const uint32_t (&a)[4], uint32_t bl, uint32_t bh, int sc) {
  asm volatile("{\n.reg .pred p;\n.reg .b64 b;\nsetp.ne.b32 p, %46, 0;\nmov.b64 b, {%44, %45};\n"
    "wgmma.mma_async.sync.aligned.m64n80k16.f32.bf16.bf16 {%0, %1, %2, %3, %4, %5, %6, %7, %8, %9, %10, %11, %12, %13, %14, %15, %16, %17, %18, %19, %20, %21, %22, %23, %24, %25, %26, %27, %28, %29, %30, %31, %32, %33, %34, %35, %36, %37, %38, %39}, {%40, %41, %42, %43}, b, p, 1, 1, %47;\n}\n"
    : "+f"(d[0]), "+f"(d[1]), "+f"(d[2]), "+f"(d[3]), "+f"(d[4]), "+f"(d[5]), "+f"(d[6]), "+f"(d[7]), "+f"(d[8]), "+f"(d[9]), "+f"(d[10]), "+f"(d[11]), "+f"(d[12]), "+f"(d[13]), "+f"(d[14]), "+f"(d[15]), "+f"(d[16]), "+f"(d[17]), "+f"(d[18]), "+f"(d[19]), "+f"(d[20]), "+f"(d[21]), "+f"(d[22]), "+f"(d[23]), "+f"(d[24]), "+f"(d[25]), "+f"(d[26]), "+f"(d[27]), "+f"(d[28]), "+f"(d[29]), "+f"(d[30]), "+f"(d[31]), "+f"(d[32]), "+f"(d[33]), "+f"(d[34]), "+f"(d[35]), "+f"(d[36]), "+f"(d[37]), "+f"(d[38]), "+f"(d[39])
    : "r"(a[0]), "r"(a[1]), "r"(a[2]), "r"(a[3]), "r"(bl), "r"(bh), "r"(sc), "n"(TB));
}

__device__ __forceinline__ void wgmma_sp_n32(float (&d)[16], const uint32_t (&a)[4], uint32_t bl, uint32_t bh, uint32_t meta, int sc) {
  asm volatile("{\n.reg .pred p;\n.reg .b64 b;\nsetp.ne.b32 p, %23, 0;\nmov.b64 b, {%20, %21};\n"
    "wgmma.mma_async.sp.sync.aligned.m64n32k32.f32.bf16.bf16 {%0, %1, %2, %3, %4, %5, %6, %7, %8, %9, %10, %11, %12, %13, %14, %15}, {%16, %17, %18, %19}, b, %22, 0, p, 1, 1, 1;\n}\n"
    : "+f"(d[0]), "+f"(d[1]), "+f"(d[2]), "+f"(d[3]), "+f"(d[4]), "+f"(d[5]), "+f"(d[6]), "+f"(d[7]), "+f"(d[8]), "+f"(d[9]), "+f"(d[10]), "+f"(d[11]), "+f"(d[12]), "+f"(d[13]), "+f"(d[14]), "+f"(d[15])
    : "r"(a[0]), "r"(a[1]), "r"(a[2]), "r"(a[3]), "r"(bl), "r"(bh), "r"(meta), "r"(sc));
}

template<int TB> __device__ __forceinline__ void wgmma_rs_n112(float (&d)[56], const uint32_t (&a)[4], uint32_t bl, uint32_t bh, int sc) {
  asm volatile("{\n.reg .pred p;\n.reg .b64 b;\nsetp.ne.b32 p, %62, 0;\nmov.b64 b, {%60, %61};\n"
    "wgmma.mma_async.sync.aligned.m64n112k16.f32.bf16.bf16 {%0, %1, %2, %3, %4, %5, %6, %7, %8, %9, %10, %11, %12, %13, %14, %15, %16, %17, %18, %19, %20, %21, %22, %23, %24, %25, %26, %27, %28, %29, %30, %31, %32, %33, %34, %35, %36, %37, %38, %39, %40, %41, %42, %43, %44, %45, %46, %47, %48, %49, %50, %51, %52, %53, %54, %55}, {%56, %57, %58, %59}, b, p, 1, 1, %63;\n}\n"
    : "+f"(d[0]), "+f"(d[1]), "+f"(d[2]), "+f"(d[3]), "+f"(d[4]), "+f"(d[5]), "+f"(d[6]), "+f"(d[7]), "+f"(d[8]), "+f"(d[9]), "+f"(d[10]), "+f"(d[11]), "+f"(d[12]), "+f"(d[13]), "+f"(d[14]), "+f"(d[15]), "+f"(d[16]), "+f"(d[17]), "+f"(d[18]), "+f"(d[19]), "+f"(d[20]), "+f"(d[21]), "+f"(d[22]), "+f"(d[23]), "+f"(d[24]), "+f"(d[25]), "+f"(d[26]), "+f"(d[27]), "+f"(d[28]), "+f"(d[29]), "+f"(d[30]), "+f"(d[31]), "+f"(d[32]), "+f"(d[33]), "+f"(d[34]), "+f"(d[35]), "+f"(d[36]), "+f"(d[37]), "+f"(d[38]), "+f"(d[39]), "+f"(d[40]), "+f"(d[41]), "+f"(d[42]), "+f"(d[43]), "+f"(d[44]), "+f"(d[45]), "+f"(d[46]), "+f"(d[47]), "+f"(d[48]), "+f"(d[49]), "+f"(d[50]), "+f"(d[51]), "+f"(d[52]), "+f"(d[53]), "+f"(d[54]), "+f"(d[55])
    : "r"(a[0]), "r"(a[1]), "r"(a[2]), "r"(a[3]), "r"(bl), "r"(bh), "r"(sc), "n"(TB));
}

namespace {
constexpr int S_ = 2048, D_ = 448, F_ = 1792;
constexpr int SLOT = 22528, BT = 14336;
constexpr int KV = 10 * 1792;
constexpr int OFF_KV = 8 * SLOT;
constexpr int OFF_X = OFF_KV - 64 * 896;
constexpr int OFF_U = OFF_KV + 2 * KV;
constexpr int OFF_PART = OFF_U + BT;
constexpr int OFF_BAR = OFF_PART + 768;
constexpr int OFF_OBS = OFF_BAR + 400;
constexpr int SMEM_BYTES = OFF_OBS + 512;
constexpr uint32_t base = 1024, bars = base + OFF_BAR;
#define DLY_X 1200
#define DLY_W 3100
#define TPW 170
#define PF0 3000
#define PACE1 490
#define PACE2 400
#define SY_H 750
#define SY_U 1550
#define SY_B 900
#define PS_H 75
#define PH_U 300
#define DLY_Q 2200
#define DLY_D 2600
#define DLY_E 2500
#define PQ 240
#define PS_O 75
#define PU0 1000
#define DLY_P 3200
#define PH_O 400
#define SY_O 1200
#define SY_C 400
#define PL_U 600
#define NP_O 2
#define PK0 400
#define SA 0
#define SB 6
#define HK 1
#define LATE 0
#define NAP 30
#define CHK 8
#define KF 2
#define HLL 1
#define SPD 1
#define KP 1
#define OBS(c, i) do {} while (0)
constexpr int NTHREADS = 384;
constexpr float LOG2E = 1.4426950408889634f;

constexpr int GRP = 7168;
constexpr int G_H = 0, G_W = 256, G_U = G_W + 168, G_WO = G_U + 224, G_O = G_WO + 56, G_HALO = G_O + 256, G_END = G_HALO + 128;
constexpr int SCR_LN = -S_ * 16, SCR_CNT = -65536;
constexpr int C_H = 0, C_U = 2, C_O = 3, C_L = 35, C_TICKET = 70, C_W = 71, C_HALO = 74, C_END = 202;
#define PAGE_LOG 21
constexpr int PAGE = 1 << PAGE_LOG;
__device__ unsigned char g_scr[PAGE - SCR_CNT + G_END * GRP];

__device__ __forceinline__ uint32_t smem_u32(const void* p) { return (uint32_t)__cvta_generic_to_shared(p); }
__device__ __forceinline__ void mbar_init(uint32_t bar, uint32_t cnt) { asm volatile("mbarrier.init.shared::cta.b64 [%0], %1;" :: "r"(bar), "r"(cnt)); }
__device__ __forceinline__ void mbar_expect_tx(uint32_t bar, uint32_t bytes) { asm volatile("mbarrier.arrive.expect_tx.shared::cta.b64 _, [%0], %1;" :: "r"(bar), "r"(bytes) : "memory"); }
__device__ __forceinline__ void mbar_arrive(uint32_t bar) { asm volatile("mbarrier.arrive.shared::cta.b64 _, [%0];" :: "r"(bar) : "memory"); }
__device__ __forceinline__ void mbar_wait(uint32_t bar, uint32_t parity) {
  asm volatile("{\n.reg .pred p;\n.reg .u32 n;\nmov.u32 n, 0;\nLAB_WAIT:\n"
               "mbarrier.try_wait.parity.shared::cta.b64 p, [%0], %1;\n@p bra DONE;\n"
               "add.u32 n, n, 1;\nsetp.lt.u32 p, n, 4000000;\n@p bra LAB_WAIT;\ntrap;\nDONE:\n}" :: "r"(bar), "r"(parity) : "memory");
}
__device__ __forceinline__ void mbar_wait_u(uint32_t bar, uint32_t parity) {
  asm volatile("{\n.reg .pred p;\nLAB_WAIT:\nmbarrier.try_wait.parity.shared::cta.b64 p, [%0], %1;\n@!p bra LAB_WAIT;\n}" :: "r"(bar), "r"(parity) : "memory");
}
__device__ __forceinline__ uint32_t mbar_try(uint32_t bar, uint32_t parity) {
  uint32_t ok;
  asm volatile("{\n.reg .pred p;\nmbarrier.test_wait.parity.shared::cta.b64 p, [%1], %2;\nselp.u32 %0, 1, 0, p;\n}" : "=r"(ok) : "r"(bar), "r"(parity) : "memory");
  return ok;
}
__device__ __forceinline__ void tma4d(uint32_t dst, const CUtensorMap* m, int c0, int c1, int c3, uint32_t bar) {
  asm volatile("cp.async.bulk.tensor.4d.shared::cluster.global.mbarrier::complete_tx::bytes [%0], [%1, {%3, %4, %6, %5}], [%2];"
               :: "r"(dst), "l"(m), "r"(bar), "r"(c0), "r"(c1), "r"(c3), "r"(0) : "memory");
}
__device__ __forceinline__ void tma_store(const CUtensorMap* m, int c1, int c3, uint32_t src) {
  asm volatile("cp.async.bulk.tensor.4d.global.shared::cta.bulk_group [%0, {%4, %2, %4, %3}], [%1];" :: "l"(m), "r"(src), "r"(c1), "r"(c3), "r"(0) : "memory");
}
__device__ __forceinline__ void bulk_g2s(uint32_t dst, const void* src, uint32_t bytes, uint32_t bar) {
  asm volatile("cp.async.bulk.shared::cluster.global.mbarrier::complete_tx::bytes [%0], [%1], %2, [%3];" :: "r"(dst), "l"(src), "r"(bytes), "r"(bar) : "memory");
}
__device__ __forceinline__ void bulk_s2g(void* dst, uint32_t src, uint32_t bytes) {
  asm volatile("cp.async.bulk.global.shared::cta.bulk_group [%0], [%1], %2;" :: "l"(dst), "r"(src), "r"(bytes) : "memory");
}
__device__ __forceinline__ void wg_fence() { asm volatile("wgmma.fence.sync.aligned;" ::: "memory"); }
__device__ __forceinline__ void wg_commit() { asm volatile("wgmma.commit_group.sync.aligned;" ::: "memory"); }
template <int N> __device__ __forceinline__ void wg_wait() { asm volatile("wgmma.wait_group.sync.aligned %0;" :: "n"(N) : "memory"); }
__device__ __forceinline__ void smem_fence() { asm volatile("mbarrier.init.shared::cta.b64 [%0], 1;" :: "r"(bars + 304) : "memory"); }
__device__ __forceinline__ bool elect() {
  uint32_t r; asm volatile("{\n.reg .pred p;\nelect.sync _|p, 0xffffffff;\nselp.u32 %0, 1, 0, p;\n}" : "=r"(r)); return r != 0;
}
__device__ __forceinline__ void trap_if(bool c) { asm volatile("{\n.reg .pred p;\nsetp.ne.u32 p, %0, 0;\n@p trap;\n}" :: "r"((uint32_t)c)); }
__device__ __forceinline__ uint32_t gtime() { uint32_t v; asm volatile("mov.u32 %0, %%globaltimer_lo;" : "=r"(v)); return v; }
__device__ __forceinline__ void wait_until(uint32_t tn) { while ((int)(clock() - tn) < 0) __nanosleep(20); }
__device__ __forceinline__ uint32_t keep(uint32_t v) { return __shfl_sync(0xffffffffu, v, threadIdx.x & 31); }
__device__ __forceinline__ uint32_t ld_l2(const void* p) { uint32_t v; asm volatile("ld.relaxed.gpu.global.u32 %0, [%1];" : "=r"(v) : "l"(p) : "memory"); return v; }
__device__ __forceinline__ void bump(unsigned char* cnt) { asm volatile("red.relaxed.gpu.global.inc.u32 [%0], 0xffffffff;" :: "l"(cnt) : "memory"); }
__device__ __forceinline__ void mark(unsigned char* cnt) {
  asm volatile("red.relaxed.gpu.global.max.u32 [%0+4], %1;" :: "l"(cnt), "r"(gtime()) : "memory");
}
__device__ __forceinline__ void stamp(unsigned char* cnt) { mark(cnt); bump(cnt); }
__device__ __forceinline__ void bulk_wait() {
  asm volatile("cp.async.bulk.commit_group;" ::: "memory");
  asm volatile("cp.async.bulk.wait_group 0;" ::: "memory");
}
__device__ __forceinline__ void landed() { asm volatile("fence.proxy.async;" ::: "memory"); }
__device__ __forceinline__ uint32_t touch_ask(const void* p, bool on) {
  uint32_t v = 0;
  asm volatile("{\n.reg .pred p;\nsetp.ne.u32 p, %2, 0;\n@p atom.relaxed.gpu.global.or.b32 %0, [%1], 0;\n}" : "+r"(v) : "l"(p), "r"((uint32_t)on) : "memory");
  return v;
}
__device__ __forceinline__ int touch_got(uint32_t v) { return __any_sync(0xffffffffu, v & threadIdx.y); }
__device__ __forceinline__ int touch(const void* p, bool on) { return touch_got(touch_ask(p, on)); }
__device__ __forceinline__ void spin_ge(const unsigned char* cnt, unsigned target) {
  asm volatile("{\n.reg .pred p;\n.reg .u32 n, v;\nmov.u32 n, 0;\nLAB_SPIN:\n"
               "ld.relaxed.gpu.global.u32 v, [%0];\nsetp.ge.u32 p, v, %1;\n@p bra DONE;\n"
               "add.u32 n, n, 1;\nsetp.lt.u32 p, n, 4000000;\n@p bra LAB_SPIN;\ntrap;\nDONE:\n}" :: "l"(cnt), "r"(target) : "memory");
}
__device__ __forceinline__ uint4 lds128(uint32_t a) { uint4 v; asm volatile("ld.shared.v4.u32 {%0,%1,%2,%3}, [%4];" : "=r"(v.x), "=r"(v.y), "=r"(v.z), "=r"(v.w) : "r"(a) : "memory"); return v; }
__device__ __forceinline__ uint32_t lds32(uint32_t a) { uint32_t v; asm volatile("ld.volatile.shared.u32 %0, [%1];" : "=r"(v) : "r"(a) : "memory"); return v; }
__device__ __forceinline__ void sts32(uint32_t a, uint32_t v) { asm volatile("st.shared.u32 [%0], %1;" :: "r"(a), "r"(v) : "memory"); }
__device__ __forceinline__ void sts128(uint32_t p, uint32_t a, uint32_t b, uint32_t c, uint32_t d) { asm volatile("st.shared.v4.u32 [%0], {%1,%2,%3,%4};" :: "r"(p), "r"(a), "r"(b), "r"(c), "r"(d) : "memory"); }
__device__ __forceinline__ void sts64(uint32_t p, float a, float b) { asm volatile("st.shared.v2.f32 [%0], {%1,%2};" :: "r"(p), "f"(a), "f"(b) : "memory"); }
__device__ __forceinline__ void named_sync(int id, int n) { asm volatile("bar.sync %0, %1;" :: "r"(id), "r"(n) : "memory"); }
__device__ __forceinline__ void named_arrive(int id, int n) { asm volatile("bar.arrive %0, %1;" :: "r"(id), "r"(n) : "memory"); }
__device__ __forceinline__ constexpr uint32_t dlo(uint32_t off, uint32_t lbo) { return ((base + off) >> 4) | (lbo >> 4 << 16); }
__device__ __forceinline__ uint32_t pack2(float lo, float hi) { uint32_t r; asm("cvt.rn.bf16x2.f32 %0, %1, %2;" : "=r"(r) : "f"(hi), "f"(lo)); return r; }
__device__ __forceinline__ float bf_lo(uint32_t v) { return __uint_as_float(v << 16); }
__device__ __forceinline__ float bf_hi(uint32_t v) { return __uint_as_float(v & 0xffff0000u); }
__device__ __forceinline__ float rbf(float x) { return bf_lo(pack2(x, 0.f)); }
__device__ __forceinline__ uint32_t hsub2(uint32_t a, uint32_t b) { uint32_t r; asm("sub.rn.bf16x2 %0, %1, %2;" : "=r"(r) : "r"(a), "r"(b)); return r; }
__device__ __forceinline__ uint32_t hadd2(uint32_t a, uint32_t b) { uint32_t r; asm("add.rn.bf16x2 %0, %1, %2;" : "=r"(r) : "r"(a), "r"(b)); return r; }
__device__ __forceinline__ uint32_t hmax2(uint32_t a, uint32_t b) { uint32_t r; asm("max.bf16x2 %0, %1, %2;" : "=r"(r) : "r"(a), "r"(b)); return r; }
__device__ __forceinline__ uint32_t hmul2(uint32_t a, uint32_t b) { uint32_t r; asm("mul.rn.bf16x2 %0, %1, %2;" : "=r"(r) : "r"(a), "r"(b)); return r; }
__device__ __forceinline__ uint32_t hfma2(uint32_t a, uint32_t b, uint32_t c) { uint32_t r; asm("fma.rn.bf16x2 %0, %1, %2, %3;" : "=r"(r) : "r"(a), "r"(b), "r"(c)); return r; }
__device__ __forceinline__ float tanh_fast(float x) { float r; asm("tanh.approx.f32 %0, %1;" : "=f"(r) : "f"(x)); return r; }
__device__ __forceinline__ float rcp_fast(float x) { float r; asm("rcp.approx.ftz.f32 %0, %1;" : "=f"(r) : "f"(x)); return r; }
__device__ __forceinline__ float ex2_fast(float x) { float r; asm("ex2.approx.ftz.f32 %0, %1;" : "=f"(r) : "f"(x)); return r; }
__device__ __forceinline__ void ldsm4(uint32_t (&r)[4], uint32_t addr) {
  asm volatile("ldmatrix.sync.aligned.m8n8.x4.shared.b16 {%0,%1,%2,%3}, [%4];" : "=r"(r[0]), "=r"(r[1]), "=r"(r[2]), "=r"(r[3]) : "r"(addr) : "memory");
}
__device__ __forceinline__ void stsm4(uint32_t addr, uint32_t a, uint32_t b, uint32_t c, uint32_t d) {
  asm volatile("stmatrix.sync.aligned.m8n8.x4.shared.b16 [%0], {%1,%2,%3,%4};" :: "r"(addr), "r"(a), "r"(b), "r"(c), "r"(d) : "memory");
}
__device__ __forceinline__ void stsm2(uint32_t addr, uint32_t a, uint32_t b) {
  asm volatile("stmatrix.sync.aligned.m8n8.x2.shared.b16 [%0], {%1,%2};" :: "r"(addr), "r"(a), "r"(b) : "memory");
}
__device__ __forceinline__ void stg128(void* p, const uint32_t* r) { asm volatile("st.global.v4.u32 [%0], {%1,%2,%3,%4};" :: "l"(p), "r"(r[0]), "r"(r[1]), "r"(r[2]), "r"(r[3]) : "memory"); }
__device__ __forceinline__ void stg64(void* p, const uint32_t* r) { asm volatile("st.global.v2.u32 [%0], {%1,%2};" :: "l"(p), "r"(r[0]), "r"(r[1]) : "memory"); }
__device__ __forceinline__ void load_row(uint32_t (&r)[14], const unsigned char* p, int t) {
#pragma unroll
  for (int i = 0; i < 3; i++)
    asm volatile("ld.global.nc.L1::no_allocate.v4.u32 {%0,%1,%2,%3}, [%4];" : "=r"(r[4 * i]), "=r"(r[4 * i + 1]), "=r"(r[4 * i + 2]), "=r"(r[4 * i + 3]) : "l"(p + i * 64 + t * 16));
  asm volatile("ld.global.nc.L1::no_allocate.v2.u32 {%0,%1}, [%2];" : "=r"(r[12]), "=r"(r[13]) : "l"(p + 192 + (t & 1) * 16 + (t >> 1) * 8));
}
__device__ __forceinline__ void lds_row(uint32_t* r, uint32_t a, int t) {
#pragma unroll
  for (int i = 0; i < 3; i++) { const uint4 v = lds128(a + i * 64 + t * 16); r[4 * i] = v.x; r[4 * i + 1] = v.y; r[4 * i + 2] = v.z; r[4 * i + 3] = v.w; }
  asm volatile("ld.shared.v2.u32 {%0,%1}, [%2];" : "=r"(r[12]), "=r"(r[13]) : "r"(a + 192 + (t & 1) * 16 + (t >> 1) * 8) : "memory");
}
__device__ __forceinline__ void tile_row(uint32_t* r, int tok, int d, int t) {
  const int xi = (tok >> 1) & 7;
#pragma unroll
  for (int j = 0; j < 4; j++) {
    const int c = d * 14 + (j < 3 ? 4 * j + t : 12 + (t & 1));
    const uint4 v = lds128(base + OFF_X + ((tok & 48) + (tok & 1) * 8 + xi) * 896 + (c >> 3) * 128 + (((c ^ ((c >> 3) - xi)) & 7) << 4));
    if (j < 3) { r[4 * j] = v.x; r[4 * j + 1] = v.y; r[4 * j + 2] = v.z; r[4 * j + 3] = v.w; }
    else { r[12] = t >> 1 ? v.z : v.x; r[13] = t >> 1 ? v.w : v.y; }
  }
}

struct LnC { uint32_t m, rh, rl; float r; };
__device__ __forceinline__ LnC ln_consts(float mean, float var) {
  float sd;
  asm("sqrt.approx.ftz.f32 %0, %1;" : "=f"(sd) : "f"(rbf(rbf(var) + 1e-5f)));
  const float r = rcp_fast(rbf(sd)), rh = rbf(r);
  return {pack2(mean, mean), pack2(rh, rh), pack2(r - rh, r - rh), r};
}
__device__ __forceinline__ float variance(float mean, float sq) { return fmaxf(fmaf(-mean, mean, sq * (1.0f / D_)), 0.f); }
__device__ __forceinline__ uint32_t ln_apply(uint32_t x, const LnC& c) { const uint32_t d = hsub2(x, c.m); return hfma2(d, c.rh, hmul2(d, c.rl)); }

template <int N> __device__ __forceinline__ void fresh(float (&a)[N]) {
#pragma unroll
  for (int i = 0; i < N; i++) asm volatile("" : "=f"(a[i]));
}
__device__ __forceinline__ void pin(uint32_t (&a)[4]) { asm volatile("" : "+r"(a[0]), "+r"(a[1]), "+r"(a[2]), "+r"(a[3])); }
constexpr int B_EMPTY = 64, B_F0 = 128, B_F1 = 136, B_F2 = 144, B_HALO = 160, B_RT = 176, B_WO = 184, B_XF = 192, B_SP = 200, B_X = 216, B_HL = 224, B_RL = 240, B_RS = 272, S_FLAG = 320;
constexpr int N_GO = 6, N_DONE = 7;
constexpr int F_H = 0, F_U = 1, F_O = 2, F_LH = 3, F_LU = 5, F_LO = 6, F_G1 = 7, F_AU = 8, F_AO = 9;
__device__ __forceinline__ void watch_flag(int slot, const unsigned char* cnt, unsigned target) {
  asm volatile("{\n.reg .pred p;\n.reg .u32 n, v, t;\nmov.u32 n, 0;\nLAB_SPIN:\n"
               "ld.relaxed.gpu.global.v2.u32 {v, t}, [%1];\nsetp.ge.u32 p, v, %2;\n@p st.volatile.shared.v2.u32 [%0], {v, t};\n"
               "ld.volatile.shared.u32 v, [%0];\nsetp.ne.u32 p, v, 0;\n@p bra DONE;\n"
               "add.u32 n, n, 1;\nsetp.lt.u32 p, n, 4000000;\n@p bra LAB_SPIN;\ntrap;\nDONE:\n}" :: "r"(bars + S_FLAG + slot * 8), "l"(cnt), "r"(target) : "memory");
}
__device__ __forceinline__ uint2 peek_flag(int slot) {
  uint2 v;
  asm volatile("ld.volatile.shared.v2.u32 {%0, %1}, [%2];" : "=r"(v.x), "=r"(v.y) : "r"(bars + S_FLAG + slot * 8) : "memory");
  return v;
}
__device__ __forceinline__ uint32_t wait_flag(int slot) {
  uint2 v;
  while (!(v = peek_flag(slot)).x) __nanosleep(NAP);
  return v.y;
}
__device__ __forceinline__ uint32_t wait_flag(int slot, int delay) {
  const uint32_t last = wait_flag(slot);
  uint32_t now;
  while ((now = gtime()) - last < (uint32_t)delay);
  return now;
}
__device__ __forceinline__ void set_flag(int slot, uint32_t v) { asm volatile("st.volatile.shared.v2.u32 [%0], {%1, %2};" :: "r"(bars + S_FLAG + slot * 8), "r"(1), "r"(v) : "memory"); }
__device__ __forceinline__ bool too_early(uint32_t asked, int landed_flag, uint2 seen = make_uint2(0, 0)) {
  if (!seen.x) seen.y = wait_flag(landed_flag);
  const bool redo = asked < seen.y + 64 || seen.y > 0xf0000000u;
  return redo;
}
__device__ __forceinline__ void arrive_if(int id, bool on) {
  asm volatile("{\n.reg .pred p;\nsetp.ne.u32 p, %1, 0;\n@p bar.arrive %0, 256;\n}" :: "r"(id), "r"((uint32_t)on) : "memory");
}
template <int TA, class Hook>
__device__ __forceinline__ void stage(float (&acc)[56], uint32_t ah, uint32_t bh, int sb, uint32_t par, uint32_t& ok, int& g_tr, bool first, bool rel, Hook hook, const uint32_t (*X)[4] = nullptr) {
  if (!ok) mbar_wait(bars + sb * 8, par);
  wg_fence();
#pragma unroll
  for (int k = 0; k < 4; k++) {
    if constexpr (TA == 2) wgmma_rs_n112<1>(acc, X[k], dlo(sb * SLOT + 8192 + k * 3584, 1792), bh, k || !first);
    else wgmma_n112<TA, 1>(acc, dlo(sb * SLOT + k * (TA ? 2048 : 256), TA ? 8192 : 128), ah, dlo(sb * SLOT + 8192 + k * 3584, 1792), bh, k || !first);
    if (k == 1) ok = mbar_try(bars + ((sb + 1) & 7) * 8, sb == 7 ? par ^ 1 : par);
    hook(k);
  }
  wg_commit();
  wg_wait<1>();
  if (rel) mbar_arrive(bars + B_EMPTY + ((sb + 7) & 7) * 8);
}

struct Params {
  const unsigned char* x;
  unsigned char *scr, *out;
  uint32_t dw, dx, db, dk;
  const unsigned char *wo, *w1, *w2;
  const unsigned short *b1, *b2;
};

__global__ void __launch_bounds__(NTHREADS, 1)
fused_kernel(const Params p, const __grid_constant__ CUtensorMap m_w1, const __grid_constant__ CUtensorMap m_w2, const __grid_constant__ CUtensorMap m_b14,
             const __grid_constant__ CUtensorMap m_a8, const __grid_constant__ CUtensorMap m_b7, const __grid_constant__ CUtensorMap m_xt, const __grid_constant__ CUtensorMap m_wi) {
  extern __shared__ __align__(1024) unsigned char smem_raw[];
  const uint32_t t0 = clock();
  const int tid = threadIdx.x, lane = tid & 31, b = blockIdx.x;
  const int g = lane >> 2, t = lane & 3, r8 = lane & 7, mi = lane >> 3;
  uint32_t H[14];
  if (tid < 128) load_row(H, p.x + (b * 16 + g) * (D_ * 2) + (tid >> 5) * 224, t);
  const int warp = __shfl_sync(0xffffffffu, tid >> 5, 0);
  const int dt = b & 3, mt = b >> 2;
  const bool g1 = b < 112;
  const int kg0 = (mt & 3) * 14 + dt * 4, nk = dt < 3 ? 4 : 2;
  auto cnt = [&](int i) { return p.scr + (SCR_CNT + i * 128); };
  auto get_tag = [&]() { return (wait_flag(F_H) >> 5) & 0x3fffbfffu; };
  auto tag_at = [&](int i) { return base + OFF_KV + i * KV + min(lane, 27) * 128 + (lane < 14 ? 0 : 112 - i * 16); };
  auto fetch_halo = [&](int i, uint32_t tag) {
    if (mt > 0) {
      const uint32_t tp = keep(tag_at(i));
      uint32_t ph = 0;
      spin_ge(cnt(C_HALO + b - 4), i + 1);
      do {
        trap_if(ph > 1000000);
        if (elect()) { mbar_expect_tx(bars + B_HL + i * 8, 3584); bulk_g2s(base + OFF_KV + i * KV, p.scr + ((G_HALO + b - 4) * GRP + i * 3584), 3584, bars + B_HL + i * 8); }
        mbar_wait(bars + B_HL + i * 8, ph++ & 1);
      } while (HLL && __any_sync(0xffffffffu, lds32(tp) != tag));
    }
    if (lane == 0) mbar_arrive(bars + B_HALO + i * 8);
    OBS(lane == 0, i ? 122 : 29);
  };
  if (warp >= 8) {
    if (warp == 8) {
      if (elect()) {
        asm volatile("prefetch.tensormap [%0];" :: "l"(&m_xt) : "memory");
        trap_if(smem_u32(smem_raw) != base);
#pragma unroll
        for (int i = 0; i < B_RL; i += 8) mbar_init(bars + i, i == B_XF ? 8 : (i == B_HALO || i == B_HALO + 8 || ((i == B_F1 || i == B_WO) && !g1) ? 2 : 1));
        if (!g1) {
#pragma unroll
          for (int i = 0; i < 64; i += 8) mbar_init(bars + B_RL + i, i < 32 ? 1 : 4);
        }

#pragma unroll
        for (int i = 0; i < 80; i += 16) sts128(bars + S_FLAG + i, 0, 0, 0, 0);
        asm volatile("fence.mbarrier_init.release.cluster;" ::: "memory");
      }
      __syncwarp();
      named_arrive(12, 160); named_arrive(13, 160);
    }
    named_sync(15, 128);
    asm volatile("setmaxnreg.dec.sync.aligned.u32 80;");
    if (warp == 8) {
      if (elect()) {
        wait_until(t0 + DLY_X);
        mbar_expect_tx(bars + B_X, 64 * 896);
        asm volatile("cp.async.bulk.tensor.5d.shared::cluster.global.mbarrier::complete_tx::bytes [%0], [%1, {%4, %4, %4, %4, %3}], [%2];"
                     :: "r"(base + OFF_X), "l"(&m_xt), "r"(bars + B_X), "r"(mt * 4), "r"(0) : "memory");
        if (g1) {
          wait_until(t0 + DLY_D);
          asm volatile("prefetch.tensormap [%0];" :: "l"(&m_w1) : "memory");
          asm volatile("prefetch.tensormap [%0];" :: "l"(&m_b14) : "memory");
#pragma unroll 1
          for (int c = 0; c < 8; c++) {
            wait_until(t0 + DLY_W + c * TPW);
            if (c == 6) mbar_wait(bars + B_XF, 0);
            tma4d(base + c * SLOT, &m_w1, mt * 64, 0, c * 8, bars + c * 8);
          }
        } else {
          asm volatile("prefetch.tensormap [%0];" :: "l"(&m_wi) : "memory");
#pragma unroll 1
          for (int i = 0; i < 16; i++) {
            const int m = i >> 2, j = i & 3;
            if (j == 0) mbar_expect_tx(bars + B_RL + m * 8, nk * GRP);
            wait_until(t0 + DLY_Q + i * PQ);
            if (j >= nk) continue;
            if (m < 3) tma4d(base + i * GRP, &m_wi, 0, (m + 1) % 3 * 7, (kg0 + j) * 8, bars + B_RL + m * 8);
            else bulk_g2s(base + OFF_KV + j * GRP, p.wo + (kg0 + j) * GRP, GRP, bars + B_RL + 24);
          }
        }
#pragma unroll 1
        for (int r = g1 ? 1 : 4, rounds = 4; r < rounds; r++) {
#pragma unroll
          for (int s = 0; s < 8; s++) {
            mbar_wait_u(bars + B_EMPTY + s * 8, (r & 1) ^ 1);
            tma4d(base + s * SLOT, &m_w1, mt * 64, (r & 2) * 4, (r & 1) * 64 + s * 8, bars + s * 8);
          }
          if ((CHK & 1) && r == 3) rounds = wait_flag(F_G1);
        }
        mbar_wait(bars + B_WO, 0);
#pragma unroll 1
        for (int r = 0; ; r++) {
#pragma unroll
          for (int j = 0; j < 8; j++) {
            const int s = (j + 5) & 7;
            mbar_wait_u(bars + B_EMPTY + s * 8, (r + (j < 3)) & 1);
            tma4d(base + s * SLOT, &m_w2, mt * 64, 0, r * 512 + j * 64, bars + s * 8);
            if (j == 3 && r == 3) goto w2_done;
          }
        }
        w2_done:
        mbar_wait_u(bars + B_EMPTY + SPD * 8, 1);
        const uint32_t asked = wait_flag(F_O, SY_O);
        OBS(1, 22);
#pragma unroll
        for (int s = 1; s < 8; s++) {
          if (s > SPD) mbar_wait_u(bars + B_EMPTY + s * 8, 1);
          if ((CHK & 4) && s == 7) set_flag(F_AO, asked);
          tma4d(base + s * SLOT, &m_a8, 0, s * 8 - 8, G_O + mt * 8, bars + s * 8);
        }
      }
    } else if (warp == 9) {
      if (elect()) {
        trap_if(ld_l2(cnt(C_H)) + ld_l2(cnt(C_H + 1)) + ld_l2(cnt(C_L + C_H)) + ld_l2(cnt(C_L + C_H + 1)) > 512);
        wait_until(t0 + DLY_E);
        asm volatile("prefetch.tensormap [%0];" :: "l"(&m_b7) : "memory");
        asm volatile("prefetch.tensormap [%0];" :: "l"(&m_w2) : "memory");
        asm volatile("prefetch.tensormap [%0];" :: "l"(&m_a8) : "memory");
        uint32_t bytes = SLOT, asked0 = 0, asked1 = 0;
        if (g1) {
#pragma unroll
          for (int s = 0; s < 8; s++) mbar_expect_tx(bars + s * 8, SLOT);
          wait_until(t0 + DLY_P);
          watch_flag(F_H, cnt(C_H), 128);
          asked0 = wait_flag(F_H, SY_H);
#pragma unroll
          for (int s = 0; s < 8; s++) {
            if (s == 5) mbar_wait(bars + B_XF, 0);
            tma4d(base + s * SLOT + 8192, &m_b14, 0, dt * 14, s * 8, bars + s * 8);
            if (s == 0) OBS(1, 16);
          }
        }
        int again = 0;
#pragma unroll 1
        for (int r = g1 ? 1 : 4; r < 11; r++) {
          if (r == 2) { mbar_wait(bars + B_F0, 0); OBS(1, 17); }
          if ((CHK & 1) && r == 3 && again == 0) { again = too_early(asked0, F_LH) | too_early(asked1, F_LH + 1); set_flag(F_G1, again ? 8 : 4); }
          if (r == 4 && again == 1) { again = 2; r = 0; }
          if (r == 4) { mbar_wait(bars + B_F1, 0); OBS(1, 18); bytes = BT; }
#pragma unroll
          for (int s = 0; s < 8; s++) {
            if (KF == 0 && s == 7 && r == 4) mbar_wait(bars + B_F2, 0);
            if (KF == 1 && s == 6 && r == 5) mbar_wait(bars + B_F2, 0);
            if (s) mbar_wait_u(bars + B_EMPTY + s * 8, (r & 1) ^ 1); else { mbar_wait(bars + B_EMPTY, (r & 1) ^ 1); if ((CHK & 1) && r == 2) asked1 = gtime(); }
            if (s == 5 && r == 6) { bytes = SLOT; const uint32_t now = wait_flag(F_U, SY_U); if (CHK & 2) set_flag(F_AU, now); OBS(1, 20); }
            mbar_expect_tx(bars + s * 8, bytes);
            tma4d(base + s * SLOT + 8192, &m_b14, 0, dt * 14, r * 64 + s * 8, bars + s * 8);
          }
        }
      }
    } else if (warp == 10) {
      uint32_t tn = t0 + PF0;
      const unsigned char* src = p.w1 + (b + b / 7 * 7) * 4096 + lane * 128;
#pragma unroll 1
      for (int i = g1 ? 0 : 32; i < 32; i++) {
        wait_until(tn);
        if (i == 8) src -= 16 * 458752 - 8 * 3584;
        if (i == 16) src = p.w2 + b * 4096 + lane * 128;
        asm volatile("prefetch.global.L2 [%0];" :: "l"(src) : "memory");
        src += i < 16 ? 2 * 458752 : 458752;
        tn += i < 16 ? PACE1 : PACE2;
      }
      if (!g1 && elect()) {
#pragma unroll 1
        for (int m = 0; m < 3; m++) {
          mbar_wait(bars + B_RS + m * 8, 0);
          bulk_s2g(p.scr + (G_W + m * 56 + kg0) * GRP, base + (12 + m * 4) * GRP, nk * GRP);
          if (m == 2 || m == KF) {
            bulk_wait();
            if (m == 2) mbar_arrive(bars + B_F1);
            if (CHK & 8) landed();
            bump(cnt(C_W + (m >> 1)));
            OBS(1, 5 + (m >> 1));
          }
        }
        mbar_wait(bars + B_RS + 24, 0);
#pragma unroll 1
        for (int i = 0; i < nk; i++) bulk_s2g(p.scr + (G_WO + kg0 + i) * GRP, base + i * SLOT, GRP);
        bulk_wait();
        mbar_arrive(bars + B_WO);
        if (CHK & 8) landed();
        bump(cnt(C_U));
        if (CHK & 2) bump(cnt(C_L + C_U));
        OBS(1, 16);
      }
      __syncwarp();
      wait_flag(F_U, PL_U);
      if (CHK & 2) watch_flag(F_LU, cnt(C_L + C_U), 128);
      watch_flag(F_O, cnt(C_O + mt), 16);
      if (CHK & 4) wait_flag(F_LO);
      unsigned tk = 0;
      if (lane == 0) tk = atomicAdd((unsigned*)cnt(C_TICKET), 1);
      if (__any_sync(0xffffffffu, tk == 127)) {
#pragma unroll 1
        for (int i = lane; i < C_END; i += 32) *(uint2*)cnt(i) = make_uint2(0, 0);
      }
    } else {
      const int hc = keep((G_H + b) * GRP + lane * 256 + 128);
      unsigned char* hg = p.scr + keep((G_H + b) * GRP);
      if (mt == 0) {
#pragma unroll
        for (int i = 0; i < 14; i++) sts128(base + OFF_KV + (i / 7) * KV + (i % 7) * 512 + lane * 16, 0, 0, 0, 0);
      }
      named_sync(10, 160);
      smem_fence();
      if (elect()) { bulk_s2g(hg, base + OFF_U, GRP); mark(cnt(C_H)); bulk_wait(); bump(cnt(C_H)); OBS(1, 3); }
      __syncwarp();
      if ((CHK & 1) && lane == touch(p.scr + hc, lane < 28)) stamp(cnt(C_L + C_H));
      OBS(lane == 0, 121);
      named_sync(9, 160);
      if (!g1) {
        smem_fence();
        if (elect()) { bulk_s2g(hg + 128 * GRP, base + OFF_U + GRP, GRP); bulk_wait(); bump(cnt(C_H + 1)); }
        __syncwarp();
        watch_flag(F_H, cnt(C_H), 128);
      }
      const uint32_t tag = get_tag();
      if (lane < 16) sts32(base + OFF_PART + 512 + lane * 16 + 12, tag);
      smem_fence();
      __syncwarp();
      if (elect()) {
        bulk_s2g(p.scr + (SCR_LN + b * 256), base + OFF_PART + 512, 256);
        if (g1) {
          wait_flag(F_H, SY_B);
          const uint32_t tn = clock();
#pragma unroll 1
          for (int i = 0; i < 4; i++) { wait_until(tn + i * PS_H); bulk_s2g(hg + (128 * GRP + i * 1792), base + OFF_U + GRP + i * 1792, 1792); }
          bulk_wait();
          bump(cnt(C_H + 1));
        }
        OBS(1, 4);
      }
      __syncwarp();
      if ((CHK & 1) && lane == touch(p.scr + hc + 128 * GRP, lane < 28)) stamp(cnt(C_L + C_H + 1));
      OBS(lane == 0, 124);
      if (CHK & 1) watch_flag(F_LH, cnt(C_L + C_H), 128);
      watch_flag(F_LH + 1, cnt((CHK & 1 ? C_L : 0) + C_H + 1), 128);
      if (!(CHK & 1) && g1 && lane == 0) mbar_arrive(bars + B_F0);
      if (KF < 2) { spin_ge(cnt(C_W), 16); if (lane == 0) mbar_arrive(bars + B_F1); }
      spin_ge(cnt(C_W + 1), 16);
      if (lane == 0) mbar_arrive(bars + (KF < 2 ? B_F2 : B_F1));
      trap_if(ld_l2(cnt(C_U)) + ld_l2(cnt(C_L + C_U)) + ld_l2(cnt(C_HALO + b)) > 258);
      if (g1) {
        named_sync(14, 160);
        smem_fence();
        if (elect()) tma_store(&m_b7, dt * 14, G_U + mt * 8, base + OFF_U);
        named_sync(10, 160);
        smem_fence();
        if (elect()) { tma_store(&m_b7, dt * 14 + 7, G_U + mt * 8, base + OFF_U + GRP); mark(cnt(C_U)); bulk_wait(); bump(cnt(C_U)); if (CHK & 2) mbar_arrive(bars + B_RT); OBS(1, 7); }
        __syncwarp();
      }
      wait_until(clock() + PK0);
#pragma unroll 1
      for (int i = 0; i < 2; i++) fetch_halo(i, tag);
      if (CHK & 4) {
        if (ld_l2(cnt(C_L + C_O + mt)) < 16) wait_flag(F_O);
        watch_flag(F_LO, cnt(C_L + C_O + mt), 16);
      }
    }
  } else {
    const int wg = warp >> 2, w4 = warp & 3;
    const bool rel = (tid & 127) == 0;
    auto put_row = [&](uint32_t st, const uint32_t* r) {
#pragma unroll
      for (int i = 0; i < 3; i++) stsm4(st + i * 512, r[4 * i], r[4 * i + 1], r[4 * i + 2], r[4 * i + 3]);
      stsm2(st + 1536, r[12], r[13]);
    };
    auto send = [&](int piece, int grp, int d) { if (elect()) bulk_s2g(p.scr + (grp * GRP + d * 1792), base + OFF_U + piece * 1792, 1792); __syncwarp(); };
    const int blk = lane < 7 ? lane * 256 + 128 : GRP + (lane - 7) * 256 + 128;
    {
      if (wg) { named_sync(13, 160); mbar_wait(bars + B_X, 0); tile_row(H, dt * 16 + 8 + g, w4, t); }
      const uint32_t part = base + OFF_PART + wg * 256 + g * 32;
      float s0 = 0.f, s1 = 0.f, q0 = 0.f, q1 = 0.f;
#pragma unroll
      for (int j = 0; j < 14; j++) { const float a = bf_lo(H[j]), c = bf_hi(H[j]); s0 += a; s1 += c; q0 = fmaf(a, a, q0); q1 = fmaf(c, c, q1); }
      s0 += s1; q0 += q1;
#pragma unroll
      for (int o = 1; o < 4; o <<= 1) { s0 += __shfl_xor_sync(0xffffffffu, s0, o); q0 += __shfl_xor_sync(0xffffffffu, q0, o); }
      if (t == 0) sts64(part + w4 * 8, s0, q0);
      OBS(tid == 0, 0);
      named_sync(1 + wg, 128);
      const uint4 u = lds128(part), v = lds128(part + 16);
      const float mean = ((__uint_as_float(u.x) + __uint_as_float(u.z)) + (__uint_as_float(v.x) + __uint_as_float(v.z))) * (1.0f / D_);
      const float var = variance(mean, (__uint_as_float(u.y) + __uint_as_float(u.w)) + (__uint_as_float(v.y) + __uint_as_float(v.w)));
      const LnC l = ln_consts(mean, var), l2 = ln_consts((mean - bf_lo(l.m)) * l.r, var * l.r * l.r);
#pragma unroll
      for (int j = 0; j < 14; j++) H[j] = ln_apply(ln_apply(H[j], l), l2);
      put_row(base + OFF_U + warp * 1792 + lane * 16, H);
      if (w4 == 0 && t == 0) sts128(base + OFF_PART + 512 + wg * 128 + g * 16, l.m, l.rh, l.rl, 0);
      named_arrive(10 - wg, 160);
      OBS(rel, 1 + wg);
    }
    uint32_t ok = 0;
    int trc = 0;
    auto nohook = [](int) {};
#define OBS0(c, i) ok = 0
    if (wg == 0) {
      uint32_t hb[4], R[28];
      named_sync(12, 160);
#pragma unroll
      for (int i = 0; i < 4; i++)
        asm volatile("ld.relaxed.cta.global.u16 %0, [%1];" : "=r"(hb[i]) : "l"((i < 2 ? p.b1 + (g1 ? mt * 64 : 0) : p.b2 + mt * 64) + w4 * 16 + g + (i & 1) * 8) : "memory");
      mbar_wait(bars + B_X, 0);
#pragma unroll
      for (int h = 0; h < 2; h++) tile_row(R + h * 14, w4 * 16 + h * 8 + g, dt, t);
      if (lane == 0) mbar_arrive(bars + B_XF + (R[0] | R[4] | R[8] | R[12] | R[14] | R[18] | R[22] | R[26]) * threadIdx.y);
      float acc[56];
      if (g1) {
        const int uc = keep((G_U + mt * 8 + lane / 7) * GRP + dt * 1792 + lane % 7 * 256 + 128);
        uint32_t r = 0, rounds = CHK & 1 ? 0 : 4;
#pragma unroll 1
        do {
#pragma unroll
          for (int i = 0; i < 56; i++) { acc[i] = bf_lo(hb[(i >> 1) & 1]); asm volatile("" : "+f"(acc[i])); }
          OBS0(0, 5);
#pragma unroll 1
          do {
#pragma unroll
            for (int c = 0; c < 8; c++) stage<1>(acc, p.dw, p.db, c, r & 1, ok, trc, false, rel && (c || r), [&](int k) {
              if ((CHK & 1) && c == 1 && k == 0) asm volatile("ld.volatile.shared.u32 %0, [%1];" : "=r"(rounds) : "r"(bars + S_FLAG + F_G1 * 8 + 4) : "memory");
              if (c == 7 && k == 3 - HK) arrive_if(3, r + 1 == rounds); });
          } while (++r & 3);
          wg_wait<0>();
        } while ((CHK & 1) && r < rounds);
        if (rel) mbar_arrive(bars + B_EMPTY + 7 * 8);
        OBS(rel, 6);
        const uint32_t us = base + OFF_U + (w4 * 2 + (mi & 1)) * 896 + (mi >> 1) * 128 + r8 * 16;
#pragma unroll
        for (int hf = 0; hf < 2; hf++) {
          uint32_t U[14];
#pragma unroll
          for (int j = 0; j < 14; j++) {
            const float a = acc[hf * 28 + 2 * j], c = acc[hf * 28 + 2 * j + 1];
            U[j] = pack2(fmaf(a, tanh_fast(a * fmaf(a * a, 0.0356774081f, 0.7978845608f)), a), fmaf(c, tanh_fast(c * fmaf(c * c, 0.0356774081f, 0.7978845608f)), c));
          }
#pragma unroll
          for (int j = 0; j < 3; j++) stsm4(us + hf * GRP + j * 256, U[4 * j], U[4 * j + 1], U[4 * j + 2], U[4 * j + 3]);
          stsm2(us + hf * GRP + 768, U[12], U[13]);
          named_arrive(hf ? 10 : 14, 160);
          if (!hf) mbar_wait(bars + B_X, 0);
        }
        OBS(rel, 30);
        if ((CHK & 2) && w4 == 0) {
          mbar_wait(bars + B_RT, 0);
          const uint32_t word = touch_ask(p.scr + uc, lane < 28) | touch_ask(p.scr + uc + 4 * GRP, lane < 28);
          if (lane == touch_got(word)) stamp(cnt(C_L + C_U));
          OBS(lane == 0, 123);
        }
      } else {
#pragma unroll 1
        for (int m = 0; m < 3; m++) {
          mbar_wait(bars + B_RL + m * 8, 0);
          OBS(tid == 0 && m == 0, 7);
          if (w4 < nk) {
            uint4 v[14];
#pragma unroll
            for (int l = 0; l < 14; l++) v[l] = lds128(base + (m * 4 + w4) * GRP + r8 * 896 + (l >> 1) * 128 + ((r8 + mi + (l & 1) * 4) & 7) * 16);
#pragma unroll
            for (int l = 0; l < 14; l++) sts128(base + (12 + m * 4 + w4) * GRP + (l >> 1) * 1024 + ((r8 + mi + (l & 1) * 4) & 7) * 128 + r8 * 16, v[l].x, v[l].y, v[l].z, v[l].w);
          }
          smem_fence();
          __syncwarp();
          if (lane == 0) mbar_arrive(bars + B_RS + m * 8);
          if (m == 0) mbar_wait(bars + B_XF, 0);
        }
        named_sync(1, 128);
        mbar_wait(bars + B_RL + 24, 0);
#pragma unroll 1
        for (int i = 0; i < nk; i++) {
          uint32_t W[14];
          lds_row(W, base + OFF_KV + i * GRP + g * 896 + w4 * 224, t);
          put_row(base + i * SLOT + w4 * 1792 + lane * 16, W);
        }
        smem_fence();
        __syncwarp();
        if (lane == 0) mbar_arrive(bars + B_RS + 24);
        named_sync(1, 128);
        named_arrive(3, 256);
      }
#pragma unroll
      for (int i = 0; i < 56; i++) { acc[i] = 0.f; asm volatile("" : "+f"(acc[i])); }
#pragma unroll
      for (int i = 2; i < 4; i++) hb[i] = keep(hmul2(hb[i] * 0x10001u, 0x3f003f00u));
      const uint32_t oo = keep((mt * 64 + w4 * 16 + g) * (D_ * 2) + dt * 224 + t * 16), oq = keep(oo + 192 - (t >> 1) * 24);
      const uint32_t sx = keep(base + OFF_KV + w4 * 512 + ((g & 1) * 4 + ((g >> 1) ^ (g & 1))) * 64 + t * 16);
      if (w4 == 3) {
        const uint32_t tag = get_tag();
#pragma unroll 1
        for (int i = 0; i < 2; i++) {
          const uint32_t tp = keep(tag_at(i) + 8 * 1792);
          named_sync(i ? 0 : 11, 64);
          if (mt < 31) {
            const uint32_t own = HLL ? lds32(tp) : 0;
            if (HLL) sts32(tp, tag);
            smem_fence();
            __syncwarp();
            if (elect()) { bulk_s2g(p.scr + ((G_HALO + b) * GRP + i * 3584), base + OFF_KV + i * KV + 8 * 1792, 3584); bulk_wait(); bump(cnt(C_HALO + b)); }
            __syncwarp();
            OBS(lane == 0, i ? 15 : 23);
            if (HLL) { sts32(tp, own); smem_fence(); }
            __syncwarp();
          }
          if (lane == 0) mbar_arrive(bars + B_HALO + i * 8);
        }
      } else if (w4) { wait_until(clock() + PU0 + w4 * PH_U); watch_flag(F_U, cnt(C_U), 128); }
      named_sync(5, 256);
      OBS0(21, 10);
#pragma unroll 1
      for (int r = 0; ; r++) {
#pragma unroll
        for (int j = 0; j < 8; j++) {
          const bool site = j == SA % 8 || j == SB % 8, yield = (j == SA % 8 && r == SA / 8) || (j == SB % 8 && r == SB / 8);
          stage<1>(acc, p.dw, p.db, (j + 5) & 7, (r + (j > 2)) & 1, ok, trc, false, rel && (j || r), [&](int k) {
            if (k == 3 - HK) { if (site) arrive_if(N_GO, yield); if (j == 3) arrive_if(8, r == 3); } });
          if ((CHK & 2) && j == 0 && r == 0 && too_early(peek_flag(F_AU).y, F_LU)) {
            wg_wait<0>();
#pragma unroll 1
            for (int i = 0; i < 8; i++) mbar_wait(bars + ((i + 5) & 7) * 8, i > 2);
            named_sync(1, 128);
            if (rel) {
              mbar_expect_tx(bars + B_SP, 8 * BT);
#pragma unroll 1
              for (int i = 0; i < 8; i++) tma4d(base + ((i + 5) & 7) * SLOT + 8192, &m_b14, 0, dt * 14, G_U + i * 8, bars + B_SP);
            }
            __syncwarp();
            mbar_wait(bars + B_SP, 0);
            uint32_t yes = 1;
            stage<1>(acc, p.dw, p.db, 5, 0, yes, trc, true, false, nohook);
          }
          if (site && yield) named_sync(N_DONE, 256);
          if (j == 3 && r == 3) goto gemm2_done;
        }
      }
      gemm2_done:
      wg_wait<0>();
      OBS(rel, 24);
      uint32_t G[28], dep = 0;
#pragma unroll
      for (int j = 0; j < 28; j++) {
        const uint32_t hh = hfma2(pack2(acc[2 * j], acc[2 * j + 1]), 0x3e803e80u, hb[2 + (j & 1)]);
        const float a = bf_lo(hh), c = bf_hi(hh);
        G[j] = pack2(fmaf(a, tanh_fast(a), a), fmaf(c, tanh_fast(c), c));
        dep |= G[j];
      }
      OBS(rel, 26);
      named_sync(12 + w4 + dep * threadIdx.y, 64);
      uint4 S4[8];
#pragma unroll
      for (int i = 0; i < 8; i++) S4[i] = lds128(sx + i * 2048);
#pragma unroll
      for (int i = 0; i < 8; i++) {
        const uint32_t Sv[4] = {S4[i].x, S4[i].y, S4[i].z, S4[i].w};
        const int h = i & 1, n = i >> 1;
        uint32_t Y[4];
#pragma unroll
        for (int j = 0; j < (n < 3 ? 4 : 2); j++) Y[j] = hadd2(R[h * 14 + 4 * n + j], hmul2(Sv[j], G[8 * n + 2 * j + h]));
        if (n < 3) stg128(p.out + oo + (h * 8 * D_ * 2 + n * 64), Y); else stg64(p.out + oq + h * 8 * D_ * 2, Y);
      }
      OBS(rel, 28);
    } else {
      asm volatile("setmaxnreg.inc.sync.aligned.u32 256;");
      float ka[56];
      {
        uint32_t X[28][4];
#pragma unroll
        for (int k = 0; k < 28; k++)
          ldsm4(X[k], base + OFF_X + (w4 * 16 + (mi & 1) * 8 + r8) * 896 + (k >> 2) * 128 + ((((2 * (k & 3) + (mi >> 1)) ^ ((k >> 2) - r8)) & 7) << 4));
        uint32_t all = 0;
#pragma unroll
        for (int k = 0; k < 28; k++) all |= X[k][0];
        if (lane == 0) mbar_arrive(bars + B_XF + all * threadIdx.y);
        if ((CHK & 1) && g1 && w4 == 1) { wait_flag(F_H, SY_B + SY_C); spin_ge(cnt(C_H + 1), 128); if (lane == 0) mbar_arrive(bars + B_F0); }
        wait_flag(F_LH + 1);
        LnC l[2];
        asm volatile("{\n.reg .pred p;\n.reg .u32 n, a, b;\nmov.u32 n, 0;\nLAB_LN:\n"
                     "ld.relaxed.gpu.global.v4.u32 {%0,%1,%2,a}, [%6];\nld.relaxed.gpu.global.v4.u32 {%3,%4,%5,b}, [%6+16];\n"
                     "setp.eq.u32 p, a, %7;\nsetp.eq.and.u32 p, b, %7, p;\nvote.sync.all.pred p, p, 0xffffffff;\n@p bra DONE;\n"
                     "add.u32 n, n, 1;\nsetp.lt.u32 p, n, 1000000;\n@p bra LAB_LN;\ntrap;\nDONE:\n}"
                     : "=&r"(l[0].m), "=&r"(l[0].rh), "=&r"(l[0].rl), "=&r"(l[1].m), "=&r"(l[1].rh), "=&r"(l[1].rl)
                     : "l"(p.scr + (SCR_LN + (mt * 64 + w4 * 16 + 2 * g) * 16)), "r"(get_tag()) : "memory");
        const int kc = mi & 1 ? 7 - r8 : r8;
        const uint32_t kst = keep(base + OFF_KV + (2 + 2 * w4 + (mi & 1)) * 1792 + (mi >> 1) * 128 + kc * 16);
        const uint32_t vst = keep(base + OFF_KV + KV + (2 + 2 * w4 + (kc >> 2)) * 1792 + (mi >> 1) * 128 + (((2 * kc) & 7) + ((mi & 1) ^ (kc >> 2))) * 16);
        int once = threadIdx.y;
#pragma unroll 1
        do {
#pragma unroll
          for (int k = 0; k < 112; k++) X[k >> 2][k & 3] = ln_apply(X[k >> 2][k & 3], l[k & 1]);
        } while (once--);
        float va[56];
        auto put = [&](const float (&a)[56], uint32_t dst, int i, int id) {
#pragma unroll
          for (int n = 2 * KP * i; n < 2 * KP * (i + 1) && n < 14; n += 2)
            if (i >= 0) stsm4(dst + n * 128, pack2(a[4 * n], a[4 * n + 1]), pack2(a[4 * n + 2], a[4 * n + 3]), pack2(a[4 * n + 4], a[4 * n + 5]), pack2(a[4 * n + 6], a[4 * n + 7]));
          if (i == (6 / KP | 3) && w4 == 3) named_arrive(id, 64);
        };
        named_sync(3, 256);
        fresh(ka);
        OBS0(0, 8);
#pragma unroll
        for (int c = 0; c < 7; c++) stage<2>(ka, 0, p.db, c, 0, ok, trc, c == 0, rel && c, nohook, &X[c * 4]);
        if (rel) mbar_arrive(bars + B_WO);
        fresh(va);
#pragma unroll
        for (int c = 7; c < 14; c++)
          stage<2>(va, 0, p.db, c & 7, c >> 3, ok, trc, c == 7, rel, [&](int k) { put(ka, kst, (c - 8) * 4 + k, 11); }, &X[(c - 7) * 4]);
        fresh(ka);
        OBS(rel, 9);
#pragma unroll
        for (int c = 14; c < 21; c++)
          stage<2>(ka, 0, p.db, c & 7, (c >> 3) & 1, ok, trc, c == 14, rel, [&](int k) {
            put(va, vst, (c - 15) * 4 + k, 0);
            if (SA >= 0 && c == 20 && k == 3 - HK) named_arrive(5, 256); }, &X[(c - 14) * 4]);
        smem_fence();
        wg_wait<0>();
        if (rel) mbar_arrive(bars + B_EMPTY + 4 * 8);
      }
      {
        const int oc = keep((G_O + mt * 8 + w4 * 2) * GRP + dt * 1792 + blk);
        uint32_t Q[8][4];
#pragma unroll
        for (int i = 0; i < 16; i++) {
          const int n = i - (i + 4) / 8;
#pragma unroll
          for (int h = 0; h < 2; h++) {
            const uint32_t v = pack2(ka[4 * n + 2 * h], ka[4 * n + 2 * h + 1]);
            Q[i >> 1][(i & 1) * 2 + h] = (i & 7) == 3 ? (t < 2 ? v : 0u) : ((i & 7) == 4 ? (t < 2 ? 0u : v) : v);
          }
        }
#pragma unroll
        for (int i = 0; i < 8; i++) pin(Q[i]);
        const bool in[2][2] = {{2 * t > g, 2 * t + 1 > g}, {7 - 2 * t > g, 6 - 2 * t > g}};
        const uint32_t zero = threadIdx.y, meta = 0x88dddd88u + zero;
        uint32_t M[2][5];
#pragma unroll
        for (int i = 0; i < 10; i++) {
          const uint32_t em = (in[i / 5][0] ? 0xffffu : 0u) | (in[i / 5][1] ? 0xffff0000u : 0u);
          M[i / 5][i % 5] = keep(i % 5 == w4 ? em : (i % 5 == w4 + 1 ? ~em : 0u));
        }
        float Sc[4][40], O[4][16];
        mbar_wait(bars + B_HALO, 0);
        OBS(rel, 11);
#pragma unroll
        for (int hh = 0; hh < 4; hh++) fresh(Sc[hh]);
        wg_fence();
        if (SA >= 0) named_sync(N_GO, 256); else named_sync(2, 128);
#pragma unroll
        for (int k = 0; k < 2; k++)
#pragma unroll
          for (int hh = 0; hh < 4; hh++) {
            if (k == 1 && hh == (SA < 0 ? 2 : 3)) named_arrive(SA < 0 ? 5 : N_DONE, 256);
            wgmma_rs_n80<0>(Sc[hh], Q[hh * 2 + k], dlo(OFF_KV + (hh * 7 / 2 + 2 * k) * 128, 128), p.dk, k);
          }
        wg_commit();
        uint32_t L[4][2];
        wg_wait<0>();
        OBS(rel, 12);
        auto pick = [&](int w) {
#pragma unroll
          for (int hh = 0; hh < 4; hh++)
#pragma unroll
            for (int h = 0; h < 2; h++) {
              const int i = (2 * w + h) * 4 + 2 * h;
              const uint32_t v = pack2(in[h][0] ? Sc[hh][i] : Sc[hh][i + 8], in[h][1] ? Sc[hh][i + 1] : Sc[hh][i + 9]);
              L[hh][h] = hfma2(v, 0x3e423e42u, hmul2(v, 0xb9f7b9f7u));
              const uint32_t edge = mt == 0 ? M[h][0] : 0u;
              if (w == 0) L[hh][h] = (L[hh][h] & ~edge) | (0xce6ece6eu & edge);
              asm volatile("" : "+r"(L[hh][h]));
            }
        };
        if (w4 == 0) pick(0); else if (w4 == 1) pick(1); else if (w4 == 2) pick(2); else pick(3);
        uint32_t A[4][3][4], mx[4];
        float P[8][2], sm[8];
#pragma unroll
        for (int hh = 0; hh < 4; hh++) mx[hh] = hmax2(__byte_perm(L[hh][0], L[hh][1], 0x5410), __byte_perm(L[hh][0], L[hh][1], 0x7632));
        const uint32_t x1 = 1 + ((mx[0] | mx[1] | mx[2] | mx[3]) & zero);
#pragma unroll
        for (int hh = 0; hh < 4; hh++) mx[hh] = hmax2(mx[hh], __shfl_xor_sync(0xffffffffu, mx[hh], x1));
#pragma unroll
        for (int hh = 0; hh < 4; hh++) mx[hh] = hmax2(mx[hh], __shfl_xor_sync(0xffffffffu, mx[hh], 2));
        uint32_t x2 = 0;
#pragma unroll
        for (int i = 0; i < 8; i++) {
          const float m = (i & 1 ? bf_hi(mx[i >> 1]) : bf_lo(mx[i >> 1])) * -LOG2E;
          P[i][0] = ex2_fast(fmaf(bf_lo(L[i >> 1][i & 1]), LOG2E, m)); P[i][1] = ex2_fast(fmaf(bf_hi(L[i >> 1][i & 1]), LOG2E, m));
          sm[i] = P[i][0] + P[i][1];
          x2 |= __float_as_uint(sm[i]);
        }
        x2 = 1 + (x2 & zero);
#pragma unroll
        for (int i = 0; i < 8; i++) sm[i] += __shfl_xor_sync(0xffffffffu, sm[i], x2);
#pragma unroll
        for (int i = 0; i < 8; i++) sm[i] += __shfl_xor_sync(0xffffffffu, sm[i], 2);
#pragma unroll
        for (int i = 0; i < 8; i++) {
          const float inv = rcp_fast(sm[i]);
          const uint32_t pp = pack2(P[i][0] * inv, P[i][1] * inv);
#pragma unroll
          for (int j = 0; j < 6; j++) A[i >> 1][j >> 1][(j & 1) * 2 + (i & 1)] = pp & (j == 4 ? zero : M[i & 1][j - (j > 4)]);
        }
#pragma unroll
        for (int hh = 0; hh < 4; hh++) fresh(O[hh]);
#pragma unroll
        for (int i = 0; i < 12; i++) pin(A[i / 3][i % 3]);
        OBS(rel, 13);
        mbar_wait(bars + B_HALO + 8, 0);
        OBS(rel, 31);
        named_sync(N_GO, 256);
        wg_fence();
        auto opair = [&](int m, int h2) {
          const int hb2 = m / 7 * 2, r = m % 7;
          const float f0 = LATE ? sm[2 * hb2 + h2 / 2] : 1.f, f1 = LATE ? sm[2 * hb2 + 2 + h2 / 2] : 1.f, f = t < 2 ? f0 : f1;
          if (r < 3) return pack2(O[hb2][4 * r + h2] * f0, O[hb2][4 * r + h2 + 1] * f0);
          if (r == 3) return pack2((t < 2 ? O[hb2][12 + h2] : O[hb2 + 1][h2]) * f, (t < 2 ? O[hb2][13 + h2] : O[hb2 + 1][h2 + 1]) * f);
          return pack2(O[hb2 + 1][4 * (r - 3) + h2] * f1, O[hb2 + 1][4 * (r - 3) + h2 + 1] * f1);
        };
        auto pv = [&](int hh, int j) { wgmma_sp_n32(O[hh], A[hh][j], dlo(OFF_KV + KV + hh * 7 / 2 * 128 + (j ? j + 1 : 0) * 3584, 1792), p.db, meta, j); };
#pragma unroll
        for (int i = 0; i < 12; i++) {
          if (i == 10) named_arrive(N_DONE, 256);
          pv(i & 3, i >> 2);
          if (LATE && i < 8) { sm[i] = P[i][0] + P[i][1]; sm[i] += __shfl_xor_sync(0xffffffffu, sm[i], 1); }
        }
        wg_commit();
        if (LATE) {
#pragma unroll
          for (int i = 0; i < 8; i++) sm[i] = rcp_fast(sm[i] + __shfl_xor_sync(0xffffffffu, sm[i], 2));
        }
        OBS(rel, 19);
        wg_wait<0>();
        OBS(rel, 21);
#pragma unroll
        for (int h = 0; h < 2; h++) {
          uint32_t U[14];
#pragma unroll
          for (int j = 0; j < 14; j++) U[j] = opair(j, h * 2);
          put_row(base + OFF_U + (w4 * 2 + h) * 1792 + lane * 16, U);
        }
        smem_fence();
        __syncwarp();
        OBS(rel, 14);
        const uint32_t tn = clock() + w4 * PS_O;
#pragma unroll 1
        for (int h = 0; h < 2; h++) { wait_until(tn + h * 4 * PS_O); send(w4 * 2 + h, G_O + mt * 8 + w4 * 2 + h, dt); }
        if (tid == 224 && SY_O) mark(cnt(C_O + mt));
        bulk_wait();
        __syncwarp();
        const uint32_t word = CHK & 4 ? touch_ask(p.scr + oc, lane < 14) : 0;
        if (lane == 0) bump(cnt(C_O + mt));
        OBS(tid == 224, 120);
        if ((CHK & 4) && lane == touch_got(word)) stamp(cnt(C_L + C_O + mt));
        OBS(tid == 224, 125);
        if (w4 < NP_O) { wait_until(clock() + PH_O); watch_flag(F_O, cnt(C_O + mt), 16); }
      }
      const uint32_t sx = keep(base + OFF_KV + w4 * 512 + (g >> 2) * 2048 + (g & 3) * 64 + t * 16);
      named_sync(8, 256);
      OBS0(49, 25);
#pragma unroll 1
      for (int go = 0; ; go++) {
        uint32_t asked;
        uint2 seen;
        fresh(ka);
#pragma unroll
        for (int c = 49; c < 56; c++)
          stage<0>(ka, p.dx, p.db, c & 7, 0, ok, trc, c == 49, false, [&](int k) { if ((CHK & 4) && c == 55 && k == 0) { asked = peek_flag(F_AO).y; seen = peek_flag(F_LO); } });
        const bool redo = (CHK & 4) && !go && too_early(asked, F_LO, seen);
        wg_wait<0>();
        if (!redo) break;
        named_sync(2, 128);
        if (rel) {
          mbar_expect_tx(bars + B_SP + 8, 7 * 8192);
#pragma unroll 1
          for (int s = 1; s < 8; s++) tma4d(base + s * SLOT, &m_a8, 0, s * 8 - 8, G_O + mt * 8, bars + B_SP + 8);
        }
        __syncwarp();
        mbar_wait(bars + B_SP + 8, 0);
      }
      OBS(rel, 27);
#pragma unroll
      for (int i = 0; i < 8; i++) {
        const float* a = ka + (i >> 1) * 16 + (i & 1) * 2;
        const uint32_t dst = (sx ^ ((i & 1) * 320)) + (i >> 1) * 4096, v0 = pack2(a[0], a[1]), v1 = pack2(a[4], a[5]);
        if (i < 6) sts128(dst, v0, v1, pack2(a[8], a[9]), pack2(a[12], a[13])); else sts64(dst, __uint_as_float(v0), __uint_as_float(v1));
      }
      named_arrive(12 + w4, 64);
    }
  }
}

typedef CUresult (*EncFn)(CUtensorMap*, CUtensorMapDataType, cuuint32_t, void*, const cuuint64_t*, const cuuint64_t*, const cuuint32_t*,
                          const cuuint32_t*, CUtensorMapInterleave, CUtensorMapSwizzle, CUtensorMapL2promotion, CUtensorMapFloatOOBfill);
void enc(EncFn f, CUtensorMap* m, const void* ptr, const cuuint64_t (&gd)[4], const cuuint64_t (&gs)[3], const cuuint32_t (&bx)[4], CUtensorMapSwizzle sw) {
  cuuint32_t es[4] = {1, 1, 1, 1};
  f(m, CU_TENSOR_MAP_DATA_TYPE_BFLOAT16, 4, (void*)ptr, gd, gs, bx, es, CU_TENSOR_MAP_INTERLEAVE_NONE, sw,
    CU_TENSOR_MAP_L2_PROMOTION_L2_128B, CU_TENSOR_MAP_FLOAT_OOB_FILL_NONE);
}
}

extern "C" void kernel_launch(void* const* d_in, const int* in_sizes, int n_in, void* d_out, int out_size) {
  (void)in_sizes; (void)n_in; (void)out_size;
  void* fp = nullptr;
  cudaDriverEntryPointQueryResult qr;
  cudaGetDriverEntryPoint("cuTensorMapEncodeTiled", &fp, cudaEnableDefault, &qr);
  EncFn f = (EncFn)fp;
  CUtensorMap m_w1, m_w2, m_b14, m_a8, m_b7, m_xt, m_wi;
  void* scr = nullptr;
  cudaGetSymbolAddress(&scr, g_scr);
  scr = (void*)((((uintptr_t)scr + PAGE - 1) & ~(uintptr_t)(PAGE - 1)) + -SCR_CNT);
  enc(f, &m_w1, d_in[4], {F_, 16, 1, S_ / 16}, {F_ * 2, F_ * 2, F_ * 32}, {64, 8, 1, 8}, CU_TENSOR_MAP_SWIZZLE_128B);
  {
    cuuint64_t gd[5] = {64, 7, 8, 2, S_ / 16}, gs[4] = {128, D_ * 4, D_ * 2, D_ * 32};
    cuuint32_t bx[5] = {64, 7, 8, 2, 4}, es[5] = {1, 1, 1, 1, 1};
    f(&m_xt, CU_TENSOR_MAP_DATA_TYPE_BFLOAT16, 5, d_in[0], gd, gs, bx, es, CU_TENSOR_MAP_INTERLEAVE_NONE, CU_TENSOR_MAP_SWIZZLE_128B,
      CU_TENSOR_MAP_L2_PROMOTION_L2_128B, CU_TENSOR_MAP_FLOAT_OOB_FILL_NONE);
  }
  enc(f, &m_w2, d_in[6], {S_, 1, 1, F_}, {S_ * 2, S_ * 2, S_ * 2}, {64, 1, 1, 64}, CU_TENSOR_MAP_SWIZZLE_128B);
  enc(f, &m_b14, scr, {64, 56, 1, G_END}, {128, GRP, GRP}, {64, 14, 1, 8}, CU_TENSOR_MAP_SWIZZLE_NONE);
  enc(f, &m_wi, d_in[1], {64, 21, 1, D_}, {128, D_ * 6, D_ * 6}, {64, 7, 1, 8}, CU_TENSOR_MAP_SWIZZLE_NONE);
  enc(f, &m_b7, scr, {64, 56, 1, G_END}, {128, GRP, GRP}, {64, 7, 1, 8}, CU_TENSOR_MAP_SWIZZLE_NONE);
  enc(f, &m_a8, scr, {64, 56, 1, G_END}, {128, GRP, GRP}, {64, 8, 1, 8}, CU_TENSOR_MAP_SWIZZLE_NONE);
  Params p;
  p.x = (const unsigned char*)d_in[0]; p.wo = (const unsigned char*)d_in[2];
  p.w1 = (const unsigned char*)d_in[4]; p.b1 = (const unsigned short*)d_in[5];
  p.w2 = (const unsigned char*)d_in[6]; p.b2 = (const unsigned short*)d_in[7];
  p.out = (unsigned char*)d_out; p.scr = (unsigned char*)scr;
  p.dw = 0x40000040u; p.dx = 64; p.db = 8; p.dk = 112;
  cudaFuncSetAttribute(fused_kernel, cudaFuncAttributeMaxDynamicSharedMemorySize, SMEM_BYTES);
  fused_kernel<<<128, NTHREADS, SMEM_BYTES, cudaStreamPerThread>>>(p, m_w1, m_w2, m_b14, m_a8, m_b7, m_xt, m_wi);
}
```

```cpp
#include <cuda_runtime.h>
#include <cuda.h>
#include <cuda_bf16.h>
#include <stdint.h>

template<int TA, int TB> __device__ __forceinline__ void wgmma_n112(float (&d)[56], uint32_t al, uint32_t ah, uint32_t bl, uint32_t bh, int sc) {
  asm volatile("{\n.reg .pred p;\n.reg .b64 a, b;\nsetp.ne.b32 p, %60, 0;\nmov.b64 a, {%56, %57};\nmov.b64 b, {%58, %59};\n"
    "wgmma.mma_async.sync.aligned.m64n112k16.f32.bf16.bf16 {%0, %1, %2, %3, %4, %5, %6, %7, %8, %9, %10, %11, %12, %13, %14, %15, %16, %17, %18, %19, %20, %21, %22, %23, %24, %25, %26, %27, %28, %29, %30, %31, %32, %33, %34, %35, %36, %37, %38, %39, %40, %41, %42, %43, %44, %45, %46, %47, %48, %49, %50, %51, %52, %53, %54, %55}, a, b, p, 1, 1, %61, %62;\n}\n"
    : "+f"(d[0]), "+f"(d[1]), "+f"(d[2]), "+f"(d[3]), "+f"(d[4]), "+f"(d[5]), "+f"(d[6]), "+f"(d[7]), "+f"(d[8]), "+f"(d[9]), "+f"(d[10]), "+f"(d[11]), "+f"(d[12]), "+f"(d[13]), "+f"(d[14]), "+f"(d[15]), "+f"(d[16]), "+f"(d[17]), "+f"(d[18]), "+f"(d[19]), "+f"(d[20]), "+f"(d[21]), "+f"(d[22]), "+f"(d[23]), "+f"(d[24]), "+f"(d[25]), "+f"(d[26]), "+f"(d[27]), "+f"(d[28]), "+f"(d[29]), "+f"(d[30]), "+f"(d[31]), "+f"(d[32]), "+f"(d[33]), "+f"(d[34]), "+f"(d[35]), "+f"(d[36]), "+f"(d[37]), "+f"(d[38]), "+f"(d[39]), "+f"(d[40]), "+f"(d[41]), "+f"(d[42]), "+f"(d[43]), "+f"(d[44]), "+f"(d[45]), "+f"(d[46]), "+f"(d[47]), "+f"(d[48]), "+f"(d[49]), "+f"(d[50]), "+f"(d[51]), "+f"(d[52]), "+f"(d[53]), "+f"(d[54]), "+f"(d[55])
    : "r"(al), "r"(ah), "r"(bl), "r"(bh), "r"(sc), "n"(TA), "n"(TB));
}

template<int TB> __device__ __forceinline__ void wgmma_rs_n80(float (&d)[40], const uint32_t (&a)[4], uint32_t bl, uint32_t bh, int sc) {
  asm volatile("{\n.reg .pred p;\n.reg .b64 b;\nsetp.ne.b32 p, %46, 0;\nmov.b64 b, {%44, %45};\n"
    "wgmma.mma_async.sync.aligned.m64n80k16.f32.bf16.bf16 {%0, %1, %2, %3, %4, %5, %6, %7, %8, %9, %10, %11, %12, %13, %14, %15, %16, %17, %18, %19, %20, %21, %22, %23, %24, %25, %26, %27, %28, %29, %30, %31, %32, %33, %34, %35, %36, %37, %38, %39}, {%40, %41, %42, %43}, b, p, 1, 1, %47;\n}\n"
    : "+f"(d[0]), "+f"(d[1]), "+f"(d[2]), "+f"(d[3]), "+f"(d[4]), "+f"(d[5]), "+f"(d[6]), "+f"(d[7]), "+f"(d[8]), "+f"(d[9]), "+f"(d[10]), "+f"(d[11]), "+f"(d[12]), "+f"(d[13]), "+f"(d[14]), "+f"(d[15]), "+f"(d[16]), "+f"(d[17]), "+f"(d[18]), "+f"(d[19]), "+f"(d[20]), "+f"(d[21]), "+f"(d[22]), "+f"(d[23]), "+f"(d[24]), "+f"(d[25]), "+f"(d[26]), "+f"(d[27]), "+f"(d[28]), "+f"(d[29]), "+f"(d[30]), "+f"(d[31]), "+f"(d[32]), "+f"(d[33]), "+f"(d[34]), "+f"(d[35]), "+f"(d[36]), "+f"(d[37]), "+f"(d[38]), "+f"(d[39])
    : "r"(a[0]), "r"(a[1]), "r"(a[2]), "r"(a[3]), "r"(bl), "r"(bh), "r"(sc), "n"(TB));
}

__device__ __forceinline__ void wgmma_sp_n32(float (&d)[16], const uint32_t (&a)[4], uint32_t bl, uint32_t bh, uint32_t meta, int sc) {
  asm volatile("{\n.reg .pred p;\n.reg .b64 b;\nsetp.ne.b32 p, %23, 0;\nmov.b64 b, {%20, %21};\n"
    "wgmma.mma_async.sp.sync.aligned.m64n32k32.f32.bf16.bf16 {%0, %1, %2, %3, %4, %5, %6, %7, %8, %9, %10, %11, %12, %13, %14, %15}, {%16, %17, %18, %19}, b, %22, 0, p, 1, 1, 1;\n}\n"
    : "+f"(d[0]), "+f"(d[1]), "+f"(d[2]), "+f"(d[3]), "+f"(d[4]), "+f"(d[5]), "+f"(d[6]), "+f"(d[7]), "+f"(d[8]), "+f"(d[9]), "+f"(d[10]), "+f"(d[11]), "+f"(d[12]), "+f"(d[13]), "+f"(d[14]), "+f"(d[15])
    : "r"(a[0]), "r"(a[1]), "r"(a[2]), "r"(a[3]), "r"(bl), "r"(bh), "r"(meta), "r"(sc));
}

template<int TB> __device__ __forceinline__ void wgmma_rs_n112(float (&d)[56], const uint32_t (&a)[4], uint32_t bl, uint32_t bh, int sc) {
  asm volatile("{\n.reg .pred p;\n.reg .b64 b;\nsetp.ne.b32 p, %62, 0;\nmov.b64 b, {%60, %61};\n"
    "wgmma.mma_async.sync.aligned.m64n112k16.f32.bf16.bf16 {%0, %1, %2, %3, %4, %5, %6, %7, %8, %9, %10, %11, %12, %13, %14, %15, %16, %17, %18, %19, %20, %21, %22, %23, %24, %25, %26, %27, %28, %29, %30, %31, %32, %33, %34, %35, %36, %37, %38, %39, %40, %41, %42, %43, %44, %45, %46, %47, %48, %49, %50, %51, %52, %53, %54, %55}, {%56, %57, %58, %59}, b, p, 1, 1, %63;\n}\n"
    : "+f"(d[0]), "+f"(d[1]), "+f"(d[2]), "+f"(d[3]), "+f"(d[4]), "+f"(d[5]), "+f"(d[6]), "+f"(d[7]), "+f"(d[8]), "+f"(d[9]), "+f"(d[10]), "+f"(d[11]), "+f"(d[12]), "+f"(d[13]), "+f"(d[14]), "+f"(d[15]), "+f"(d[16]), "+f"(d[17]), "+f"(d[18]), "+f"(d[19]), "+f"(d[20]), "+f"(d[21]), "+f"(d[22]), "+f"(d[23]), "+f"(d[24]), "+f"(d[25]), "+f"(d[26]), "+f"(d[27]), "+f"(d[28]), "+f"(d[29]), "+f"(d[30]), "+f"(d[31]), "+f"(d[32]), "+f"(d[33]), "+f"(d[34]), "+f"(d[35]), "+f"(d[36]), "+f"(d[37]), "+f"(d[38]), "+f"(d[39]), "+f"(d[40]), "+f"(d[41]), "+f"(d[42]), "+f"(d[43]), "+f"(d[44]), "+f"(d[45]), "+f"(d[46]), "+f"(d[47]), "+f"(d[48]), "+f"(d[49]), "+f"(d[50]), "+f"(d[51]), "+f"(d[52]), "+f"(d[53]), "+f"(d[54]), "+f"(d[55])
    : "r"(a[0]), "r"(a[1]), "r"(a[2]), "r"(a[3]), "r"(bl), "r"(bh), "r"(sc), "n"(TB));
}

namespace {
constexpr int S_ = 2048, D_ = 448, F_ = 1792;
constexpr int SLOT = 22528, BT = 14336;
constexpr int KV = 10 * 1792;
constexpr int OFF_KV = 8 * SLOT;
constexpr int OFF_X = OFF_KV - 64 * 896;
constexpr int OFF_U = OFF_KV + 2 * KV;
constexpr int OFF_PART = OFF_U + BT;
constexpr int OFF_BAR = OFF_PART + 768;
constexpr int OFF_OBS = OFF_BAR + 320;
constexpr int SMEM_BYTES = OFF_OBS + 512;
constexpr uint32_t base = 1024, bars = base + OFF_BAR;
#define DLY_X 1200
#define DLY_W 3100
#define TPW 170
#define PF0 3000
#define PACE1 450
#define PACE2 330
#define SY_H 750
#define SY_U 1470
#define SY_B 900
#define PS_H 75
#define PH_U 300
#define DLY_Q 2200
#define DLY_D 2600
#define DLY_E 2500
#define PQ 240
#define PS_O 440
#define PU0 1300
#define DLY_P 3200
#define PH_O 800
#define SY_O 1150
#define SY_C 1000
#define NP_O 3
#define PK0 200
#define PB0 400
#define PFN 23
#define PF1 600
#define PACE3 350
#define NP_U 2
#define SA 0
#define SB 7
#define HK 1
#define NAP 30
#define KP 2
#define OBS(c, i) do {} while (0)
constexpr int NTHREADS = 384;
constexpr float LOG2E = 1.4426950408889634f;

constexpr int GRP = 7168;
constexpr int G_H = 0, G_W = 256, G_U = G_W + 168, G_WO = G_U + 224, G_O = G_WO + 56, G_HALO = G_O + 256, G_END = G_HALO + 128;
constexpr int SCR_LN = -S_ * 16, SCR_CNT = -65536;
constexpr int C_H = 0, C_U = 2, C_W = 3, C_TICKET = 4, C_O = 5, C_HALO = 37, C_END = 165;
#define PAGE_LOG 21
constexpr int PAGE = 1 << PAGE_LOG;
__device__ unsigned char g_scr[PAGE - SCR_CNT + G_END * GRP];

__device__ __forceinline__ uint32_t smem_u32(const void* p) { return (uint32_t)__cvta_generic_to_shared(p); }
__device__ __forceinline__ void mbar_init(uint32_t bar, uint32_t cnt) { asm volatile("mbarrier.init.shared::cta.b64 [%0], %1;" :: "r"(bar), "r"(cnt)); }
__device__ __forceinline__ void mbar_expect_tx(uint32_t bar, uint32_t bytes) { asm volatile("mbarrier.arrive.expect_tx.shared::cta.b64 _, [%0], %1;" :: "r"(bar), "r"(bytes) : "memory"); }
__device__ __forceinline__ void mbar_arrive(uint32_t bar) { asm volatile("mbarrier.arrive.shared::cta.b64 _, [%0];" :: "r"(bar) : "memory"); }
__device__ __forceinline__ void mbar_wait(uint32_t bar, uint32_t parity) {
  asm volatile("{\n.reg .pred p;\n.reg .u32 n;\nmov.u32 n, 0;\nLAB_WAIT:\n"
               "mbarrier.try_wait.parity.shared::cta.b64 p, [%0], %1;\n@p bra DONE;\n"
               "add.u32 n, n, 1;\nsetp.lt.u32 p, n, 4000000;\n@p bra LAB_WAIT;\ntrap;\nDONE:\n}" :: "r"(bar), "r"(parity) : "memory");
}
__device__ __forceinline__ void mbar_wait_u(uint32_t bar, uint32_t parity) {
  asm volatile("{\n.reg .pred p;\nLAB_WAIT:\nmbarrier.try_wait.parity.shared::cta.b64 p, [%0], %1;\n@!p bra LAB_WAIT;\n}" :: "r"(bar), "r"(parity) : "memory");
}
__device__ __forceinline__ uint32_t mbar_try(uint32_t bar, uint32_t parity) {
  uint32_t ok;
  asm volatile("{\n.reg .pred p;\nmbarrier.test_wait.parity.shared::cta.b64 p, [%1], %2;\nselp.u32 %0, 1, 0, p;\n}" : "=r"(ok) : "r"(bar), "r"(parity) : "memory");
  return ok;
}
__device__ __forceinline__ void tma4d(uint32_t dst, const CUtensorMap* m, int c0, int c1, int c3, uint32_t bar) {
  asm volatile("cp.async.bulk.tensor.4d.shared::cluster.global.mbarrier::complete_tx::bytes [%0], [%1, {%3, %4, %6, %5}], [%2];"
               :: "r"(dst), "l"(m), "r"(bar), "r"(c0), "r"(c1), "r"(c3), "r"(0) : "memory");
}
__device__ __forceinline__ void tma_store(const CUtensorMap* m, int c1, int c3, uint32_t src) {
  asm volatile("cp.async.bulk.tensor.4d.global.shared::cta.bulk_group [%0, {%4, %2, %4, %3}], [%1];" :: "l"(m), "r"(src), "r"(c1), "r"(c3), "r"(0) : "memory");
}
__device__ __forceinline__ void bulk_g2s(uint32_t dst, const void* src, uint32_t bytes, uint32_t bar) {
  asm volatile("cp.async.bulk.shared::cluster.global.mbarrier::complete_tx::bytes [%0], [%1], %2, [%3];" :: "r"(dst), "l"(src), "r"(bytes), "r"(bar) : "memory");
}
__device__ __forceinline__ void bulk_s2g(void* dst, uint32_t src, uint32_t bytes) {
  asm volatile("cp.async.bulk.global.shared::cta.bulk_group [%0], [%1], %2;" :: "l"(dst), "r"(src), "r"(bytes) : "memory");
}
__device__ __forceinline__ void wg_fence() { asm volatile("wgmma.fence.sync.aligned;" ::: "memory"); }
__device__ __forceinline__ void wg_commit() { asm volatile("wgmma.commit_group.sync.aligned;" ::: "memory"); }
template <int N> __device__ __forceinline__ void wg_wait() { asm volatile("wgmma.wait_group.sync.aligned %0;" :: "n"(N) : "memory"); }
__device__ __forceinline__ void smem_fence() { asm volatile("mbarrier.init.shared::cta.b64 [%0], 1;" :: "r"(bars + 280) : "memory"); }
__device__ __forceinline__ bool elect() {
  uint32_t r; asm volatile("{\n.reg .pred p;\nelect.sync _|p, 0xffffffff;\nselp.u32 %0, 1, 0, p;\n}" : "=r"(r)); return r != 0;
}
__device__ __forceinline__ void trap_if(bool c) { asm volatile("{\n.reg .pred p;\nsetp.ne.u32 p, %0, 0;\n@p trap;\n}" :: "r"((uint32_t)c)); }
__device__ __forceinline__ uint32_t gtime() { uint32_t v; asm volatile("mov.u32 %0, %%globaltimer_lo;" : "=r"(v)); return v; }
__device__ __forceinline__ void wait_until(uint32_t tn) {
  asm volatile("{\n.reg .pred p;\n.reg .u32 c;\nLAB_T:\nmov.u32 c, %%clock;\nsub.u32 c, c, %0;\nsetp.lt.s32 p, c, 0;\n@p nanosleep.u32 20;\n@p bra LAB_T;\n}" :: "r"(tn) : "memory");
}
__device__ __forceinline__ uint32_t keep(uint32_t v) { return __shfl_sync(0xffffffffu, v, threadIdx.x & 31); }
__device__ __forceinline__ uint32_t ld_l2(const void* p) { uint32_t v; asm volatile("ld.relaxed.gpu.global.u32 %0, [%1];" : "=r"(v) : "l"(p) : "memory"); return v; }
__device__ __forceinline__ void bump(unsigned char* cnt) { asm volatile("red.relaxed.gpu.global.inc.u32 [%0], 0xffffffff;" :: "l"(cnt) : "memory"); }
__device__ __forceinline__ void mark(unsigned char* cnt) {
  asm volatile("red.relaxed.gpu.global.max.u32 [%0+4], %1;" :: "l"(cnt), "r"(gtime()) : "memory");
}
__device__ __forceinline__ void bulk_wait() {
  asm volatile("cp.async.bulk.commit_group;" ::: "memory");
  asm volatile("cp.async.bulk.wait_group 0;" ::: "memory");
}
__device__ __forceinline__ void publish(unsigned char* cnt) {
  asm volatile("cp.async.bulk.commit_group;" ::: "memory");
  mark(cnt);
  asm volatile("cp.async.bulk.wait_group 0;" ::: "memory");
  bump(cnt);
}
__device__ __forceinline__ void landed() { asm volatile("fence.proxy.async;" ::: "memory"); }
__device__ __forceinline__ void spin_ge(const unsigned char* cnt, unsigned target) {
  asm volatile("{\n.reg .pred p;\n.reg .u32 n, v;\nmov.u32 n, 0;\nLAB_SPIN:\n"
               "ld.relaxed.gpu.global.u32 v, [%0];\nsetp.ge.u32 p, v, %1;\n@p bra DONE;\n"
               "add.u32 n, n, 1;\nsetp.lt.u32 p, n, 4000000;\n@p bra LAB_SPIN;\ntrap;\nDONE:\n}" :: "l"(cnt), "r"(target) : "memory");
}
__device__ __forceinline__ uint4 lds128(uint32_t a) { uint4 v; asm volatile("ld.shared.v4.u32 {%0,%1,%2,%3}, [%4];" : "=r"(v.x), "=r"(v.y), "=r"(v.z), "=r"(v.w) : "r"(a) : "memory"); return v; }
__device__ __forceinline__ uint32_t lds32(uint32_t a) { uint32_t v; asm volatile("ld.volatile.shared.u32 %0, [%1];" : "=r"(v) : "r"(a) : "memory"); return v; }
__device__ __forceinline__ void sts32(uint32_t a, uint32_t v) { asm volatile("st.shared.u32 [%0], %1;" :: "r"(a), "r"(v) : "memory"); }
__device__ __forceinline__ void sts128(uint32_t p, uint32_t a, uint32_t b, uint32_t c, uint32_t d) { asm volatile("st.shared.v4.u32 [%0], {%1,%2,%3,%4};" :: "r"(p), "r"(a), "r"(b), "r"(c), "r"(d) : "memory"); }
__device__ __forceinline__ void sts64(uint32_t p, float a, float b) { asm volatile("st.shared.v2.f32 [%0], {%1,%2};" :: "r"(p), "f"(a), "f"(b) : "memory"); }
__device__ __forceinline__ void named_sync(int id, int n) { asm volatile("bar.sync %0, %1;" :: "r"(id), "r"(n) : "memory"); }
__device__ __forceinline__ void named_arrive(int id, int n) { asm volatile("bar.arrive %0, %1;" :: "r"(id), "r"(n) : "memory"); }
__device__ __forceinline__ constexpr uint32_t dlo(uint32_t off, uint32_t lbo) { return ((base + off) >> 4) | (lbo >> 4 << 16); }
__device__ __forceinline__ uint32_t pack2(float lo, float hi) { uint32_t r; asm("cvt.rn.bf16x2.f32 %0, %1, %2;" : "=r"(r) : "f"(hi), "f"(lo)); return r; }
__device__ __forceinline__ float bf_lo(uint32_t v) { return __uint_as_float(v << 16); }
__device__ __forceinline__ float bf_hi(uint32_t v) { return __uint_as_float(v & 0xffff0000u); }
__device__ __forceinline__ float rbf(float x) { return bf_lo(pack2(x, 0.f)); }
__device__ __forceinline__ uint32_t hsub2(uint32_t a, uint32_t b) { uint32_t r; asm("sub.rn.bf16x2 %0, %1, %2;" : "=r"(r) : "r"(a), "r"(b)); return r; }
__device__ __forceinline__ uint32_t hadd2(uint32_t a, uint32_t b) { uint32_t r; asm("add.rn.bf16x2 %0, %1, %2;" : "=r"(r) : "r"(a), "r"(b)); return r; }
__device__ __forceinline__ uint32_t hmax2(uint32_t a, uint32_t b) { uint32_t r; asm("max.bf16x2 %0, %1, %2;" : "=r"(r) : "r"(a), "r"(b)); return r; }
__device__ __forceinline__ uint32_t hmul2(uint32_t a, uint32_t b) { uint32_t r; asm("mul.rn.bf16x2 %0, %1, %2;" : "=r"(r) : "r"(a), "r"(b)); return r; }
__device__ __forceinline__ uint32_t hfma2(uint32_t a, uint32_t b, uint32_t c) { uint32_t r; asm("fma.rn.bf16x2 %0, %1, %2, %3;" : "=r"(r) : "r"(a), "r"(b), "r"(c)); return r; }
__device__ __forceinline__ float tanh_fast(float x) { float r; asm("tanh.approx.f32 %0, %1;" : "=f"(r) : "f"(x)); return r; }
__device__ __forceinline__ float rcp_fast(float x) { float r; asm("rcp.approx.ftz.f32 %0, %1;" : "=f"(r) : "f"(x)); return r; }
__device__ __forceinline__ float ex2_fast(float x) { float r; asm("ex2.approx.ftz.f32 %0, %1;" : "=f"(r) : "f"(x)); return r; }
__device__ __forceinline__ void ldsm4(uint32_t (&r)[4], uint32_t addr) {
  asm volatile("ldmatrix.sync.aligned.m8n8.x4.shared.b16 {%0,%1,%2,%3}, [%4];" : "=r"(r[0]), "=r"(r[1]), "=r"(r[2]), "=r"(r[3]) : "r"(addr) : "memory");
}
__device__ __forceinline__ void stsm4(uint32_t addr, uint32_t a, uint32_t b, uint32_t c, uint32_t d) {
  asm volatile("stmatrix.sync.aligned.m8n8.x4.shared.b16 [%0], {%1,%2,%3,%4};" :: "r"(addr), "r"(a), "r"(b), "r"(c), "r"(d) : "memory");
}
__device__ __forceinline__ void stsm2(uint32_t addr, uint32_t a, uint32_t b) {
  asm volatile("stmatrix.sync.aligned.m8n8.x2.shared.b16 [%0], {%1,%2};" :: "r"(addr), "r"(a), "r"(b) : "memory");
}
__device__ __forceinline__ void stg128(void* p, const uint32_t* r) { asm volatile("st.global.v4.u32 [%0], {%1,%2,%3,%4};" :: "l"(p), "r"(r[0]), "r"(r[1]), "r"(r[2]), "r"(r[3]) : "memory"); }
__device__ __forceinline__ void stg64(void* p, const uint32_t* r) { asm volatile("st.global.v2.u32 [%0], {%1,%2};" :: "l"(p), "r"(r[0]), "r"(r[1]) : "memory"); }
__device__ __forceinline__ void load_row(uint32_t (&r)[14], const unsigned char* p, int t) {
#pragma unroll
  for (int i = 0; i < 3; i++)
    asm volatile("ld.global.nc.L1::no_allocate.v4.u32 {%0,%1,%2,%3}, [%4];" : "=r"(r[4 * i]), "=r"(r[4 * i + 1]), "=r"(r[4 * i + 2]), "=r"(r[4 * i + 3]) : "l"(p + i * 64 + t * 16));
  asm volatile("ld.global.nc.L1::no_allocate.v2.u32 {%0,%1}, [%2];" : "=r"(r[12]), "=r"(r[13]) : "l"(p + 192 + (t & 1) * 16 + (t >> 1) * 8));
}
__device__ __forceinline__ void lds_row(uint32_t* r, uint32_t a, int t) {
#pragma unroll
  for (int i = 0; i < 3; i++) { const uint4 v = lds128(a + i * 64 + t * 16); r[4 * i] = v.x; r[4 * i + 1] = v.y; r[4 * i + 2] = v.z; r[4 * i + 3] = v.w; }
  asm volatile("ld.shared.v2.u32 {%0,%1}, [%2];" : "=r"(r[12]), "=r"(r[13]) : "r"(a + 192 + (t & 1) * 16 + (t >> 1) * 8) : "memory");
}
__device__ __forceinline__ void tile_row(uint32_t* r, int tok, int d, int t) {
  const int xi = (tok >> 1) & 7;
#pragma unroll
  for (int j = 0; j < 4; j++) {
    const int c = d * 14 + (j < 3 ? 4 * j + t : 12 + (t & 1));
    const uint4 v = lds128(base + OFF_X + ((tok & 48) + (tok & 1) * 8 + xi) * 896 + (c >> 3) * 128 + (((c ^ ((c >> 3) - xi)) & 7) << 4));
    if (j < 3) { r[4 * j] = v.x; r[4 * j + 1] = v.y; r[4 * j + 2] = v.z; r[4 * j + 3] = v.w; }
    else { r[12] = t >> 1 ? v.z : v.x; r[13] = t >> 1 ? v.w : v.y; }
  }
}

struct LnC { uint32_t m, rh, rl; float r; };
__device__ __forceinline__ LnC ln_consts(float mean, float var) {
  float sd;
  asm("sqrt.approx.ftz.f32 %0, %1;" : "=f"(sd) : "f"(rbf(rbf(var) + 1e-5f)));
  const float r = rcp_fast(rbf(sd)), rh = rbf(r);
  return {pack2(mean, mean), pack2(rh, rh), pack2(r - rh, r - rh), r};
}
__device__ __forceinline__ float variance(float mean, float sq) { return fmaxf(fmaf(-mean, mean, sq * (1.0f / D_)), 0.f); }
__device__ __forceinline__ uint32_t ln_apply(uint32_t x, const LnC& c) { const uint32_t d = hsub2(x, c.m); return hfma2(d, c.rh, hmul2(d, c.rl)); }

template <int N> __device__ __forceinline__ void fresh(float (&a)[N]) {
#pragma unroll
  for (int i = 0; i < N; i++) asm volatile("" : "=f"(a[i]));
}
__device__ __forceinline__ void pin(uint32_t (&a)[4]) { asm volatile("" : "+r"(a[0]), "+r"(a[1]), "+r"(a[2]), "+r"(a[3])); }
constexpr int B_EMPTY = 64, B_F0 = 128, B_F1 = 136, B_HALO = 144, B_WO = 160, B_XF = 168, B_X = 176, B_HL = 184, B_OS = 200, B_RL = 216, B_RS = 248, S_FLAG = 288;
constexpr int N_GO = 6, N_DONE = 7;
constexpr int F_H = 0, F_U = 2, F_O = 3;
__device__ __forceinline__ void watch_flag(int slot, const unsigned char* cnt, unsigned target) {
  asm volatile("{\n.reg .pred p;\n.reg .u32 n, v, t;\nmov.u32 n, 0;\nLAB_SPIN:\n"
               "ld.relaxed.gpu.global.v2.u32 {v, t}, [%1];\nsetp.ge.u32 p, v, %2;\n@p st.volatile.shared.v2.u32 [%0], {v, t};\n"
               "ld.volatile.shared.u32 v, [%0];\nsetp.ne.u32 p, v, 0;\n@p bra DONE;\n"
               "add.u32 n, n, 1;\nsetp.lt.u32 p, n, 4000000;\n@p bra LAB_SPIN;\ntrap;\nDONE:\n}" :: "r"(bars + S_FLAG + slot * 8), "l"(cnt), "r"(target) : "memory");
}
__device__ __forceinline__ uint32_t wait_flag(int slot, int delay = 0) {
  uint32_t v, last;
  while (true) {
    asm volatile("ld.volatile.shared.v2.u32 {%0, %1}, [%2];" : "=r"(v), "=r"(last) : "r"(bars + S_FLAG + slot * 8) : "memory");
    if (v) break;
    __nanosleep(NAP);
  }
  while (gtime() - last < (uint32_t)delay);
  return last;
}
__device__ __forceinline__ void arrive_if(int id, bool on) {
  asm volatile("{\n.reg .pred p;\nsetp.ne.u32 p, %1, 0;\n@p bar.arrive %0, 256;\n}" :: "r"(id), "r"((uint32_t)on) : "memory");
}
template <int TA, class Hook>
__device__ __forceinline__ void stage(float (&acc)[56], uint32_t ah, uint32_t bh, int sb, uint32_t par, uint32_t& ok, int& g_tr, bool first, bool rel, Hook hook, const uint32_t (*X)[4] = nullptr) {
  if (!ok) mbar_wait(bars + sb * 8, par);
  wg_fence();
#pragma unroll
  for (int k = 0; k < 4; k++) {
    if constexpr (TA == 2) wgmma_rs_n112<1>(acc, X[k], dlo(sb * SLOT + 8192 + k * 3584, 1792), bh, k || !first);
    else wgmma_n112<TA, 1>(acc, dlo(sb * SLOT + k * (TA ? 2048 : 256), TA ? 8192 : 128), ah, dlo(sb * SLOT + 8192 + k * 3584, 1792), bh, k || !first);
    if (k == 1) ok = mbar_try(bars + ((sb + 1) & 7) * 8, sb == 7 ? par ^ 1 : par);
    hook(k);
  }
  wg_commit();
  wg_wait<1>();
  if (rel) mbar_arrive(bars + B_EMPTY + ((sb + 7) & 7) * 8);
}

struct Params {
  const unsigned char* x;
  unsigned char *scr, *out;
  uint32_t dw, dx, db, dk;
  const unsigned char *wo, *w1, *w2;
  const unsigned short *b1, *b2;
};

__global__ void __launch_bounds__(NTHREADS, 1)
fused_kernel(const Params p, const __grid_constant__ CUtensorMap m_w1, const __grid_constant__ CUtensorMap m_w2, const __grid_constant__ CUtensorMap m_b14,
             const __grid_constant__ CUtensorMap m_a8, const __grid_constant__ CUtensorMap m_b7, const __grid_constant__ CUtensorMap m_xt, const __grid_constant__ CUtensorMap m_wi) {
  extern __shared__ __align__(1024) unsigned char smem_raw[];
  const uint32_t t0 = clock();
  const int tid = threadIdx.x, lane = tid & 31, b = blockIdx.x;
  const int g = lane >> 2, t = lane & 3, r8 = lane & 7, mi = lane >> 3;
  uint32_t H[14];
  if (tid < 128) load_row(H, p.x + (b * 16 + g) * (D_ * 2) + (tid >> 5) * 224, t);
  const int warp = __shfl_sync(0xffffffffu, tid >> 5, 0);
  const int dt = b & 3, mt = b >> 2;
  const bool g1 = b < 112;
  const int kg0 = (mt & 3) * 14 + dt * 4, nk = dt < 3 ? 4 : 2;
  auto cnt = [&](int i) { return p.scr + (SCR_CNT + i * 128); };
  auto get_tag = [&]() { return (wait_flag(F_H) >> 5) & 0x3fffbfffu; };
  auto tag_at = [&](int i) { return base + OFF_KV + i * KV + min(lane, 27) * 128 + (lane < 14 ? 0 : 112 - i * 16); };
  auto fetch_halo = [&](int i, uint32_t tag) {
    if (mt > 0) {
      const uint32_t tp = keep(tag_at(i));
      uint32_t ph = 0;
      spin_ge(cnt(C_HALO + b - 4), i + 1);
      do {
        trap_if(ph > 1000000);
        if (elect()) { mbar_expect_tx(bars + B_HL + i * 8, 3584); bulk_g2s(base + OFF_KV + i * KV, p.scr + ((G_HALO + b - 4) * GRP + i * 3584), 3584, bars + B_HL + i * 8); }
        mbar_wait(bars + B_HL + i * 8, ph++ & 1);
      } while (__any_sync(0xffffffffu, lds32(tp) != tag));
    }
    if (lane == 0) mbar_arrive(bars + B_HALO + i * 8);
    OBS(lane == 0, i ? 122 : 29);
  };
  if (warp >= 8) {
    if (warp == 8) {
      if (elect()) {
        asm volatile("prefetch.tensormap [%0];" :: "l"(&m_xt) : "memory");
        trap_if(smem_u32(smem_raw) != base);
#pragma unroll
        for (int i = 0; i < B_RL; i += 8) mbar_init(bars + i, i == B_XF ? 8 : i >= B_OS ? 4 : (i == B_HALO || i == B_HALO + 8 || ((i == B_F1 || i == B_WO) && !g1) ? 2 : 1));
        if (!g1) {
#pragma unroll
          for (int i = 0; i < 64; i += 8) mbar_init(bars + B_RL + i, i < 32 ? 1 : 4);
        }

#pragma unroll
        for (int i = 0; i < 32; i += 16) sts128(bars + S_FLAG + i, 0, 0, 0, 0);
        asm volatile("fence.mbarrier_init.release.cluster;" ::: "memory");
      }
      __syncwarp();
      named_arrive(12, 160); named_arrive(13, 160);
    }
    named_sync(15, 128);
    asm volatile("setmaxnreg.dec.sync.aligned.u32 80;");
    if (warp == 8) {
      if (elect()) {
        wait_until(t0 + DLY_X);
        mbar_expect_tx(bars + B_X, 64 * 896);
        asm volatile("cp.async.bulk.tensor.5d.shared::cluster.global.mbarrier::complete_tx::bytes [%0], [%1, {%4, %4, %4, %4, %3}], [%2];"
                     :: "r"(base + OFF_X), "l"(&m_xt), "r"(bars + B_X), "r"(mt * 4), "r"(0) : "memory");
        if (g1) {
          wait_until(t0 + DLY_D);
          asm volatile("prefetch.tensormap [%0];" :: "l"(&m_w1) : "memory");
          asm volatile("prefetch.tensormap [%0];" :: "l"(&m_b14) : "memory");
#pragma unroll 1
          for (int c = 0; c < 8; c++) {
            wait_until(t0 + DLY_W + c * TPW);
            if (c == 6) mbar_wait(bars + B_XF, 0);
            tma4d(base + c * SLOT, &m_w1, mt * 64, 0, c * 8, bars + c * 8);
          }
        } else {
          asm volatile("prefetch.tensormap [%0];" :: "l"(&m_wi) : "memory");
#pragma unroll 1
          for (int i = 0; i < 16; i++) {
            const int m = i >> 2, j = i & 3;
            if (j == 0) mbar_expect_tx(bars + B_RL + m * 8, nk * GRP);
            wait_until(t0 + DLY_Q + i * PQ);
            if (j >= nk) continue;
            if (m < 3) tma4d(base + i * GRP, &m_wi, 0, (m + 1) % 3 * 7, (kg0 + j) * 8, bars + B_RL + m * 8);
            else bulk_g2s(base + OFF_KV + j * GRP, p.wo + (kg0 + j) * GRP, GRP, bars + B_RL + 24);
          }
        }
#pragma unroll 1
        for (int r = g1 ? 1 : 4; r < 4; r++) {
#pragma unroll
          for (int s = 0; s < 8; s++) {
            mbar_wait_u(bars + B_EMPTY + s * 8, (r & 1) ^ 1);
            tma4d(base + s * SLOT, &m_w1, mt * 64, (r & 2) * 4, (r & 1) * 64 + s * 8, bars + s * 8);
          }
        }
        mbar_wait(bars + B_WO, 0);
#pragma unroll 1
        for (int r = 0; ; r++) {
#pragma unroll
          for (int j = 0; j < 8; j++) {
            const int s = (j + 5) & 7;
            mbar_wait_u(bars + B_EMPTY + s * 8, (r + (j < 3)) & 1);
            tma4d(base + s * SLOT, &m_w2, mt * 64, 0, r * 512 + j * 64, bars + s * 8);
            if (j == 3 && r == 3) goto w2_done;
          }
        }
        w2_done:
        wait_flag(F_O, SY_O);
        OBS(1, 22);
#pragma unroll
        for (int s = 1; s < 8; s++) {
          mbar_wait_u(bars + B_EMPTY + s * 8, 1);
          tma4d(base + s * SLOT, &m_a8, 0, s * 8 - 8, G_O + mt * 8, bars + s * 8);
        }
      }
    } else if (warp == 9) {
      if (elect()) {
        const uint32_t early = ld_l2(cnt(C_H));
        wait_until(t0 + DLY_E);
        asm volatile("prefetch.tensormap [%0];" :: "l"(&m_b7) : "memory");
        asm volatile("prefetch.tensormap [%0];" :: "l"(&m_w2) : "memory");
        asm volatile("prefetch.tensormap [%0];" :: "l"(&m_a8) : "memory");
        uint32_t bytes = SLOT;
        if (g1) {
#pragma unroll
          for (int s = 0; s < 8; s++) mbar_expect_tx(bars + s * 8, SLOT);
          if (early < 128) wait_until(t0 + DLY_P);
          watch_flag(F_H, cnt(C_H), 128);
          wait_flag(F_H, SY_H);
#pragma unroll
          for (int s = 0; s < 8; s++) {
            if (s == 5) mbar_wait(bars + B_XF, 0);
            tma4d(base + s * SLOT + 8192, &m_b14, 0, dt * 14, s * 8, bars + s * 8);
            if (s == 0) OBS(1, 16);
          }
        }
#pragma unroll 1
        for (int r = g1 ? 1 : 4; r < 11; r++) {
          if (r == 2) { mbar_wait(bars + B_F0, 0); OBS(1, 17); }
          if (r == 4) { mbar_wait(bars + B_F1, 0); OBS(1, 18); bytes = BT; }
#pragma unroll
          for (int s = 0; s < 8; s++) {
            if (s) mbar_wait_u(bars + B_EMPTY + s * 8, (r & 1) ^ 1); else mbar_wait(bars + B_EMPTY, (r & 1) ^ 1);
            if (s == 5 && r == 6) { bytes = SLOT; wait_flag(F_U, SY_U); OBS(1, 20); }
            mbar_expect_tx(bars + s * 8, bytes);
            tma4d(base + s * SLOT + 8192, &m_b14, 0, dt * 14, r * 64 + s * 8, bars + s * 8);
          }
        }
      }
    } else if (warp == 10) {
      uint32_t tn = t0 + PF0;
      const unsigned char* src = p.w1 + (b + b / 7 * 7) * 4096 + lane * 128;
#pragma unroll 1
      for (int i = g1 ? 0 : 32; i < 32; i++) {
        if (i == PFN) { wait_flag(F_U, PF1); tn = clock(); }
        wait_until(tn);
        if (i == 8) src -= 16 * 458752 - 8 * 3584;
        if (i == 16) src = p.w2 + b * 4096 + lane * 128;
        asm volatile("prefetch.global.L2 [%0];" :: "l"(src) : "memory");
        src += i < 16 ? 2 * 458752 : 458752;
        tn += i < 16 ? PACE1 : (i < PFN ? PACE2 : PACE3);
      }
      if (!g1 && elect()) {
#pragma unroll 1
        for (int m = 0; m < 3; m++) {
          mbar_wait(bars + B_RS + m * 8, 0);
          bulk_s2g(p.scr + (G_W + m * 56 + kg0) * GRP, base + (12 + m * 4) * GRP, nk * GRP);
        }
        bulk_wait();
        mbar_arrive(bars + B_F1);
        landed();
        bump(cnt(C_W));
        OBS(1, 6);
        mbar_wait(bars + B_RS + 24, 0);
#pragma unroll 1
        for (int i = 0; i < nk; i++) bulk_s2g(p.scr + (G_WO + kg0 + i) * GRP, base + i * SLOT, GRP);
        bulk_wait();
        mbar_arrive(bars + B_WO);
        landed();
        bump(cnt(C_U));
        OBS(1, 16);
      }
      __syncwarp();
      wait_flag(F_U);
      watch_flag(F_O, cnt(C_O + mt), 4);
      unsigned tk = 0;
      if (lane == 0) tk = atomicAdd((unsigned*)cnt(C_TICKET), 1);
      if (__any_sync(0xffffffffu, tk == 127)) {
#pragma unroll 1
        for (int i = lane; i < C_END; i += 32) *(uint2*)cnt(i) = make_uint2(0, 0);
      }
    } else {
      unsigned char* hg = p.scr + (G_H + b) * GRP;
      const uint32_t early = ld_l2(cnt(C_H + 1));
      if (mt == 0) {
#pragma unroll
        for (int i = 0; i < 14; i++) sts128(base + OFF_KV + (i / 7) * KV + (i % 7) * 512 + lane * 16, 0, 0, 0, 0);
      }
      named_sync(10, 160);
      smem_fence();
      if (elect()) { bulk_s2g(hg, base + OFF_U, GRP); publish(cnt(C_H)); OBS(1, 3); }
      __syncwarp();
      named_sync(9, 160);
      if (!g1) {
        smem_fence();
        if (elect()) { bulk_s2g(hg + 128 * GRP, base + OFF_U + GRP, GRP); publish(cnt(C_H + 1)); }
        __syncwarp();
        watch_flag(F_H, cnt(C_H), 128);
      }
      const uint32_t tag = get_tag();
      if (lane < 16) sts32(base + OFF_PART + 512 + lane * 16 + 12, tag);
      smem_fence();
      __syncwarp();
      if (elect()) {
        bulk_s2g(p.scr + (SCR_LN + b * 256), base + OFF_PART + 512, 256);
        if (g1) {
          wait_flag(F_H, SY_B);
          const uint32_t tn = clock();
#pragma unroll 1
          for (int i = 0; i < 4; i++) { wait_until(tn + i * PS_H); bulk_s2g(hg + (128 * GRP + i * 1792), base + OFF_U + GRP + i * 1792, 1792); }
          publish(cnt(C_H + 1));
        }
        OBS(1, 4);
      }
      __syncwarp();
      if (early < 128) wait_until(clock() + PB0);
      watch_flag(F_H + 1, cnt(C_H + 1), 128);
      wait_flag(F_H + 1, SY_C);
      if (lane == 0) mbar_arrive(bars + B_F0);
      spin_ge(cnt(C_W), 16);
      if (lane == 0) mbar_arrive(bars + B_F1);
      const uint32_t have = ld_l2(cnt(C_HALO + max(b - 4, 0)));
      if (g1) {
        named_sync(14, 160);
        smem_fence();
        if (elect()) tma_store(&m_b7, dt * 14, G_U + mt * 8, base + OFF_U);
        named_sync(10, 160);
        smem_fence();
        if (elect()) { tma_store(&m_b7, dt * 14 + 7, G_U + mt * 8, base + OFF_U + GRP); publish(cnt(C_U)); OBS(1, 7); }
        __syncwarp();
      }
      if (!have) wait_until(clock() + PK0);
#pragma unroll 1
      for (int i = 0; i < 2; i++) fetch_halo(i, tag);
      if (elect()) {
        mbar_wait(bars + B_OS, 0);
        const uint32_t tn = clock() + PS_O;
        tma_store(&m_b7, dt * 14, G_O + mt * 8, base + OFF_U);
        mbar_wait(bars + B_OS + 8, 0);
        wait_until(tn);
        tma_store(&m_b7, dt * 14 + 7, G_O + mt * 8, base + OFF_U + GRP);
        OBS(1, 14);
        publish(cnt(C_O + mt));
        OBS(1, 120);
      }
    }
  } else {
    const int wg = warp >> 2, w4 = warp & 3;
    const bool rel = (tid & 127) == 0;
    auto put_row = [&](uint32_t st, const uint32_t* r) {
#pragma unroll
      for (int i = 0; i < 3; i++) stsm4(st + i * 512, r[4 * i], r[4 * i + 1], r[4 * i + 2], r[4 * i + 3]);
      stsm2(st + 1536, r[12], r[13]);
    };
    auto put_half = [&](int hf, const uint32_t* r) {
      const uint32_t st = base + OFF_U + hf * GRP + (w4 * 2 + (mi & 1)) * 896 + (mi >> 1) * 128 + r8 * 16;
#pragma unroll
      for (int j = 0; j < 3; j++) stsm4(st + j * 256, r[4 * j], r[4 * j + 1], r[4 * j + 2], r[4 * j + 3]);
      stsm2(st + 768, r[12], r[13]);
    };
    {
      if (wg) { named_sync(13, 160); mbar_wait(bars + B_X, 0); tile_row(H, dt * 16 + 8 + g, w4, t); }
      const uint32_t part = base + OFF_PART + wg * 256 + g * 32;
      float s0 = 0.f, s1 = 0.f, q0 = 0.f, q1 = 0.f;
#pragma unroll
      for (int j = 0; j < 14; j++) { const float a = bf_lo(H[j]), c = bf_hi(H[j]); s0 += a; s1 += c; q0 = fmaf(a, a, q0); q1 = fmaf(c, c, q1); }
      s0 += s1; q0 += q1;
#pragma unroll
      for (int o = 1; o < 4; o <<= 1) { s0 += __shfl_xor_sync(0xffffffffu, s0, o); q0 += __shfl_xor_sync(0xffffffffu, q0, o); }
      if (t == 0) sts64(part + w4 * 8, s0, q0);
      OBS(tid == 0, 0);
      named_sync(1 + wg, 128);
      const uint4 u = lds128(part), v = lds128(part + 16);
      const float mean = ((__uint_as_float(u.x) + __uint_as_float(u.z)) + (__uint_as_float(v.x) + __uint_as_float(v.z))) * (1.0f / D_);
      const float var = variance(mean, (__uint_as_float(u.y) + __uint_as_float(u.w)) + (__uint_as_float(v.y) + __uint_as_float(v.w)));
      const LnC l = ln_consts(mean, var), l2 = ln_consts((mean - bf_lo(l.m)) * l.r, var * l.r * l.r);
#pragma unroll
      for (int j = 0; j < 14; j++) H[j] = ln_apply(ln_apply(H[j], l), l2);
      put_row(base + OFF_U + warp * 1792 + lane * 16, H);
      if (w4 == 0 && t == 0) sts128(base + OFF_PART + 512 + wg * 128 + g * 16, l.m, l.rh, l.rl, 0);
      named_arrive(10 - wg, 160);
      OBS(rel, 1 + wg);
    }
    uint32_t ok = 0;
    int trc = 0;
    auto nohook = [](int) {};
#define OBS0(c, i) ok = 0
    if (wg == 0) {
      uint32_t hb[4], R[28];
      named_sync(12, 160);
#pragma unroll
      for (int i = 0; i < 4; i++)
        asm volatile("ld.relaxed.cta.global.u16 %0, [%1];" : "=r"(hb[i]) : "l"((i < 2 ? p.b1 + (g1 ? mt * 64 : 0) : p.b2 + mt * 64) + w4 * 16 + g + (i & 1) * 8) : "memory");
      mbar_wait(bars + B_X, 0);
#pragma unroll
      for (int h = 0; h < 2; h++) tile_row(R + h * 14, w4 * 16 + h * 8 + g, dt, t);
      if (lane == 0) mbar_arrive(bars + B_XF + (R[0] | R[4] | R[8] | R[12] | R[14] | R[18] | R[22] | R[26]) * threadIdx.y);
      float acc[56];
      if (g1) {
#pragma unroll
        for (int i = 0; i < 56; i++) { acc[i] = bf_lo(hb[(i >> 1) & 1]); asm volatile("" : "+f"(acc[i])); }
        OBS0(0, 5);
#pragma unroll 1
        for (int r = 0; r < 4; r++)
#pragma unroll
          for (int c = 0; c < 8; c++) stage<1>(acc, p.dw, p.db, c, r & 1, ok, trc, false, rel && (c || r), [&](int k) { if (c == 7 && k == 3 - HK) arrive_if(3, r == 3); });
        wg_wait<0>();
        if (rel) mbar_arrive(bars + B_EMPTY + 7 * 8);
        OBS(rel, 6);
#pragma unroll
        for (int hf = 0; hf < 2; hf++) {
          uint32_t U[14];
#pragma unroll
          for (int j = 0; j < 14; j++) {
            const float a = acc[hf * 28 + 2 * j], c = acc[hf * 28 + 2 * j + 1];
            U[j] = pack2(fmaf(a, tanh_fast(a * fmaf(a * a, 0.0356774081f, 0.7978845608f)), a), fmaf(c, tanh_fast(c * fmaf(c * c, 0.0356774081f, 0.7978845608f)), c));
          }
          put_half(hf, U);
          named_arrive(hf ? 10 : 14, 160);
          if (!hf) mbar_wait(bars + B_X, 0);
        }
        OBS(rel, 30);
      } else {
#pragma unroll 1
        for (int m = 0; m < 3; m++) {
          mbar_wait(bars + B_RL + m * 8, 0);
          OBS(tid == 0 && m == 0, 7);
          if (w4 < nk) {
            uint4 v[14];
#pragma unroll
            for (int l = 0; l < 14; l++) v[l] = lds128(base + (m * 4 + w4) * GRP + r8 * 896 + (l >> 1) * 128 + ((r8 + mi + (l & 1) * 4) & 7) * 16);
#pragma unroll
            for (int l = 0; l < 14; l++) sts128(base + (12 + m * 4 + w4) * GRP + (l >> 1) * 1024 + ((r8 + mi + (l & 1) * 4) & 7) * 128 + r8 * 16, v[l].x, v[l].y, v[l].z, v[l].w);
          }
          smem_fence();
          __syncwarp();
          if (lane == 0) mbar_arrive(bars + B_RS + m * 8);
          if (m == 0) mbar_wait(bars + B_XF, 0);
        }
        named_sync(1, 128);
        mbar_wait(bars + B_RL + 24, 0);
#pragma unroll 1
        for (int i = 0; i < nk; i++) {
          uint32_t W[14];
          lds_row(W, base + OFF_KV + i * GRP + g * 896 + w4 * 224, t);
          put_row(base + i * SLOT + w4 * 1792 + lane * 16, W);
        }
        smem_fence();
        __syncwarp();
        if (lane == 0) mbar_arrive(bars + B_RS + 24);
        named_sync(1, 128);
        named_arrive(3, 256);
      }
#pragma unroll
      for (int i = 0; i < 56; i++) { acc[i] = 0.f; asm volatile("" : "+f"(acc[i])); }
#pragma unroll
      for (int i = 2; i < 4; i++) hb[i] = keep(hmul2(hb[i] * 0x10001u, 0x3f003f00u));
      const uint32_t oo = keep((mt * 64 + w4 * 16 + g) * (D_ * 2) + dt * 224 + t * 16), oq = keep(oo + 192 - (t >> 1) * 24);
      const uint32_t sx = keep(base + OFF_KV + w4 * 512 + ((g & 1) * 4 + ((g >> 1) ^ (g & 1))) * 64 + t * 16);
      if (w4 == 3) {
        const uint32_t tag = get_tag();
#pragma unroll 1
        for (int i = 0; i < 2; i++) {
          const uint32_t tp = keep(tag_at(i) + 8 * 1792);
          named_sync(i ? 0 : 11, 64);
          if (mt < 31) {
            const uint32_t own = lds32(tp);
            sts32(tp, tag);
            smem_fence();
            __syncwarp();
            if (elect()) { bulk_s2g(p.scr + ((G_HALO + b) * GRP + i * 3584), base + OFF_KV + i * KV + 8 * 1792, 3584); bump(cnt(C_HALO + b)); bulk_wait(); }
            __syncwarp();
            OBS(lane == 0, i ? 15 : 23);
            sts32(tp, own);
            smem_fence();
            __syncwarp();
          }
          if (lane == 0) mbar_arrive(bars + B_HALO + i * 8);
        }
      } else if (w4 < NP_U) { wait_until(clock() + PU0 + w4 * PH_U); watch_flag(F_U, cnt(C_U), 128); OBS(tid == 0, 121); }
      named_sync(5, 256);
      OBS0(21, 10);
#pragma unroll 1
      for (int r = 0; ; r++) {
#pragma unroll
        for (int j = 0; j < 8; j++) {
          const bool site = j == SA % 8 || j == SB % 8, yield = (j == SA % 8 && r == SA / 8) || (j == SB % 8 && r == SB / 8);
          stage<1>(acc, p.dw, p.db, (j + 5) & 7, (r + (j > 2)) & 1, ok, trc, false, rel && (j || r), [&](int k) {
            if (k == 3 - HK) { if (site) arrive_if(N_GO, yield); if (j == 3) arrive_if(8, r == 3); } });
          if (site && yield) named_sync(N_DONE, 256);
          if (j == 3 && r == 3) goto gemm2_done;
        }
      }
      gemm2_done:
      wg_wait<0>();
      OBS(rel, 24);
      uint32_t G[28], dep = 0;
#pragma unroll
      for (int j = 0; j < 28; j++) {
        const uint32_t hh = hfma2(pack2(acc[2 * j], acc[2 * j + 1]), 0x3e803e80u, hb[2 + (j & 1)]);
        const float a = bf_lo(hh), c = bf_hi(hh);
        G[j] = pack2(fmaf(a, tanh_fast(a), a), fmaf(c, tanh_fast(c), c));
        dep |= G[j];
      }
      OBS(rel, 26);
      named_sync(12 + w4 + dep * threadIdx.y, 64);
      uint4 S4[8];
#pragma unroll
      for (int i = 0; i < 8; i++) S4[i] = lds128(sx + i * 2048);
#pragma unroll
      for (int i = 0; i < 8; i++) {
        const uint32_t Sv[4] = {S4[i].x, S4[i].y, S4[i].z, S4[i].w};
        const int h = i & 1, n = i >> 1;
        uint32_t Y[4];
#pragma unroll
        for (int j = 0; j < (n < 3 ? 4 : 2); j++) Y[j] = hadd2(R[h * 14 + 4 * n + j], hmul2(Sv[j], G[8 * n + 2 * j + h]));
        if (n < 3) stg128(p.out + oo + (h * 8 * D_ * 2 + n * 64), Y); else stg64(p.out + oq + h * 8 * D_ * 2, Y);
      }
      OBS(rel, 28);
    } else {
      asm volatile("setmaxnreg.inc.sync.aligned.u32 256;");
      float ka[56];
      {
        uint32_t X[28][4];
#pragma unroll
        for (int k = 0; k < 28; k++)
          ldsm4(X[k], base + OFF_X + (w4 * 16 + (mi & 1) * 8 + r8) * 896 + (k >> 2) * 128 + ((((2 * (k & 3) + (mi >> 1)) ^ ((k >> 2) - r8)) & 7) << 4));
        uint32_t all = 0;
#pragma unroll
        for (int k = 0; k < 28; k++) all |= X[k][0];
        if (lane == 0) mbar_arrive(bars + B_XF + all * threadIdx.y);
        mbar_wait(bars + B_F0, 0);
        LnC l[2];
        asm volatile("{\n.reg .pred p;\n.reg .u32 n, a, b;\nmov.u32 n, 0;\nLAB_LN:\n"
                     "ld.relaxed.gpu.global.v4.u32 {%0,%1,%2,a}, [%6];\nld.relaxed.gpu.global.v4.u32 {%3,%4,%5,b}, [%6+16];\n"
                     "setp.eq.u32 p, a, %7;\nsetp.eq.and.u32 p, b, %7, p;\nvote.sync.all.pred p, p, 0xffffffff;\n@p bra DONE;\n"
                     "add.u32 n, n, 1;\nsetp.lt.u32 p, n, 1000000;\n@p bra LAB_LN;\ntrap;\nDONE:\n}"
                     : "=&r"(l[0].m), "=&r"(l[0].rh), "=&r"(l[0].rl), "=&r"(l[1].m), "=&r"(l[1].rh), "=&r"(l[1].rl)
                     : "l"(p.scr + (SCR_LN + (mt * 64 + w4 * 16 + 2 * g) * 16)), "r"(get_tag()) : "memory");
        const int kc = mi & 1 ? 7 - r8 : r8;
        const uint32_t kst = keep(base + OFF_KV + (2 + 2 * w4 + (mi & 1)) * 1792 + (mi >> 1) * 128 + kc * 16);
        const uint32_t vst = keep(base + OFF_KV + KV + (2 + 2 * w4 + (kc >> 2)) * 1792 + (mi >> 1) * 128 + (((2 * kc) & 7) + ((mi & 1) ^ (kc >> 2))) * 16);
        int once = threadIdx.y;
#pragma unroll 1
        do {
#pragma unroll
          for (int k = 0; k < 112; k++) X[k >> 2][k & 3] = ln_apply(X[k >> 2][k & 3], l[k & 1]);
        } while (once--);
        float va[56];
        auto put = [&](const float (&a)[56], uint32_t dst, int i, int id) {
#pragma unroll
          for (int n = 2 * KP * i; n < 2 * KP * (i + 1) && n < 14; n += 2)
            if (i >= 0) stsm4(dst + n * 128, pack2(a[4 * n], a[4 * n + 1]), pack2(a[4 * n + 2], a[4 * n + 3]), pack2(a[4 * n + 4], a[4 * n + 5]), pack2(a[4 * n + 6], a[4 * n + 7]));
          if (i == (6 / KP | 3) && w4 == 3) named_arrive(id, 64);
        };
        named_sync(3, 256);
        fresh(ka);
        OBS0(0, 8);
#pragma unroll
        for (int c = 0; c < 7; c++) stage<2>(ka, 0, p.db, c, 0, ok, trc, c == 0, rel && c, nohook, &X[c * 4]);
        if (rel) mbar_arrive(bars + B_WO);
        fresh(va);
#pragma unroll
        for (int c = 7; c < 14; c++)
          stage<2>(va, 0, p.db, c & 7, c >> 3, ok, trc, c == 7, rel, [&](int k) { put(ka, kst, (c - 8) * 4 + k, 11); }, &X[(c - 7) * 4]);
        fresh(ka);
        OBS(rel, 9);
#pragma unroll
        for (int c = 14; c < 21; c++)
          stage<2>(ka, 0, p.db, c & 7, (c >> 3) & 1, ok, trc, c == 14, rel, [&](int k) {
            put(va, vst, (c - 15) * 4 + k, 0);
            if (c == 20 && k == 3 - HK) named_arrive(5, 256); }, &X[(c - 14) * 4]);
        smem_fence();
        wg_wait<0>();
        if (rel) mbar_arrive(bars + B_EMPTY + 4 * 8);
      }
      {
        uint32_t Q[8][4];
#pragma unroll
        for (int i = 0; i < 16; i++) {
          const int n = i - (i + 4) / 8;
#pragma unroll
          for (int h = 0; h < 2; h++) {
            const uint32_t v = pack2(ka[4 * n + 2 * h], ka[4 * n + 2 * h + 1]);
            Q[i >> 1][(i & 1) * 2 + h] = (i & 7) == 3 ? (t < 2 ? v : 0u) : ((i & 7) == 4 ? (t < 2 ? 0u : v) : v);
          }
        }
#pragma unroll
        for (int i = 0; i < 8; i++) pin(Q[i]);
        const bool in[2][2] = {{2 * t > g, 2 * t + 1 > g}, {7 - 2 * t > g, 6 - 2 * t > g}};
        const uint32_t zero = threadIdx.y, meta = 0x88dddd88u + zero;
        uint32_t M[2][5];
#pragma unroll
        for (int i = 0; i < 10; i++) {
          const uint32_t em = (in[i / 5][0] ? 0xffffu : 0u) | (in[i / 5][1] ? 0xffff0000u : 0u);
          M[i / 5][i % 5] = keep(i % 5 == w4 ? em : (i % 5 == w4 + 1 ? ~em : 0u));
        }
        float Sc[4][40], O[4][16];
        mbar_wait(bars + B_HALO, 0);
        OBS(rel, 11);
#pragma unroll
        for (int hh = 0; hh < 4; hh++) fresh(Sc[hh]);
        wg_fence();
        named_sync(N_GO, 256);
#pragma unroll
        for (int k = 0; k < 2; k++)
#pragma unroll
          for (int hh = 0; hh < 4; hh++) {
            if (k == 1 && hh == 3) named_arrive(N_DONE, 256);
            wgmma_rs_n80<0>(Sc[hh], Q[hh * 2 + k], dlo(OFF_KV + (hh * 7 / 2 + 2 * k) * 128, 128), p.dk, k);
          }
        wg_commit();
        uint32_t L[4][2];
        wg_wait<0>();
        OBS(rel, 12);
        auto pick = [&](int w) {
#pragma unroll
          for (int hh = 0; hh < 4; hh++)
#pragma unroll
            for (int h = 0; h < 2; h++) {
              const int i = (2 * w + h) * 4 + 2 * h;
              L[hh][h] = pack2(in[h][0] ? Sc[hh][i] : Sc[hh][i + 8], in[h][1] ? Sc[hh][i + 1] : Sc[hh][i + 9]);
              asm volatile("" : "+r"(L[hh][h]));
            }
        };
        if (w4 == 0) pick(0); else if (w4 == 1) pick(1); else if (w4 == 2) pick(2); else pick(3);
#pragma unroll
        for (int i = 0; i < 8; i++) L[i >> 1][i & 1] = hfma2(L[i >> 1][i & 1], 0x3e423e42u, hmul2(L[i >> 1][i & 1], 0xb9f7b9f7u));
        if (mt == 0) {
#pragma unroll
          for (int i = 0; i < 8; i++) { L[i >> 1][i & 1] = (L[i >> 1][i & 1] & ~M[i & 1][0]) | (0xce6ece6eu & M[i & 1][0]); asm volatile("" : "+r"(L[i >> 1][i & 1])); }
        }
        uint32_t A[4][3][4], mx[4];
        float P[8][2], sm[8];
#pragma unroll
        for (int hh = 0; hh < 4; hh++) mx[hh] = hmax2(__byte_perm(L[hh][0], L[hh][1], 0x5410), __byte_perm(L[hh][0], L[hh][1], 0x7632));
        const uint32_t x1 = 1 + ((mx[0] | mx[1] | mx[2] | mx[3]) & zero);
#pragma unroll
        for (int hh = 0; hh < 4; hh++) mx[hh] = hmax2(mx[hh], __shfl_xor_sync(0xffffffffu, mx[hh], x1));
#pragma unroll
        for (int hh = 0; hh < 4; hh++) mx[hh] = hmax2(mx[hh], __shfl_xor_sync(0xffffffffu, mx[hh], 2));
        uint32_t x2 = 0;
#pragma unroll
        for (int i = 0; i < 8; i++) {
          const float m = (i & 1 ? bf_hi(mx[i >> 1]) : bf_lo(mx[i >> 1])) * -LOG2E;
          P[i][0] = ex2_fast(fmaf(bf_lo(L[i >> 1][i & 1]), LOG2E, m)); P[i][1] = ex2_fast(fmaf(bf_hi(L[i >> 1][i & 1]), LOG2E, m));
          sm[i] = P[i][0] + P[i][1];
          x2 |= __float_as_uint(sm[i]);
        }
        x2 = 1 + (x2 & zero);
#pragma unroll
        for (int i = 0; i < 8; i++) sm[i] += __shfl_xor_sync(0xffffffffu, sm[i], x2);
#pragma unroll
        for (int i = 0; i < 8; i++) sm[i] += __shfl_xor_sync(0xffffffffu, sm[i], 2);
#pragma unroll
        for (int i = 0; i < 8; i++) {
          const float inv = rcp_fast(sm[i]);
          const uint32_t pp = pack2(P[i][0] * inv, P[i][1] * inv);
#pragma unroll
          for (int j = 0; j < 6; j++) A[i >> 1][j >> 1][(j & 1) * 2 + (i & 1)] = pp & (j == 4 ? zero : M[i & 1][j - (j > 4)]);
        }
#pragma unroll
        for (int hh = 0; hh < 4; hh++) fresh(O[hh]);
#pragma unroll
        for (int i = 0; i < 12; i++) pin(A[i / 3][i % 3]);
        OBS(rel, 13);
        mbar_wait(bars + B_HALO + 8, 0);
        OBS(rel, 31);
        named_sync(N_GO, 256);
        wg_fence();
        auto opair = [&](int m, int h2) {
          const int hb2 = m / 7 * 2, r = m % 7;
          if (r < 3) return pack2(O[hb2][4 * r + h2], O[hb2][4 * r + h2 + 1]);
          if (r == 3) return pack2(t < 2 ? O[hb2][12 + h2] : O[hb2 + 1][h2], t < 2 ? O[hb2][13 + h2] : O[hb2 + 1][h2 + 1]);
          return pack2(O[hb2 + 1][4 * (r - 3) + h2], O[hb2 + 1][4 * (r - 3) + h2 + 1]);
        };
        auto pv = [&](int hh, int j) { wgmma_sp_n32(O[hh], A[hh][j], dlo(OFF_KV + KV + hh * 7 / 2 * 128 + (j ? j + 1 : 0) * 3584, 1792), p.db, meta, j); };
#pragma unroll
        for (int i = 0; i < 12; i++) {
          if (i == 10) named_arrive(N_DONE, 256);
          pv(i & 3, i >> 2);
        }
        wg_commit();
        OBS(rel, 19);
        wg_wait<0>();
        OBS(rel, 21);
#pragma unroll
        for (int h = 0; h < 2; h++) {
          uint32_t U[14];
#pragma unroll
          for (int j = 0; j < 14; j++) U[j] = opair(h * 7 + (j >> 1), (j & 1) * 2);
          put_half(h, U);
          smem_fence();
          __syncwarp();
          if (lane == 0) mbar_arrive(bars + B_OS + h * 8);
        }
        if (w4 < NP_O) { wait_until(clock() + PH_O + w4 * 300); watch_flag(F_O, cnt(C_O + mt), 4); }
      }
      const uint32_t sx = keep(base + OFF_KV + w4 * 512 + (g >> 2) * 2048 + (g & 3) * 64 + t * 16);
      named_sync(8, 256);
      OBS0(49, 25);
      fresh(ka);
#pragma unroll
      for (int c = 49; c < 56; c++) stage<0>(ka, p.dx, p.db, c & 7, 0, ok, trc, c == 49, false, nohook);
      wg_wait<0>();
      OBS(rel, 27);
#pragma unroll
      for (int i = 0; i < 8; i++) {
        const float* a = ka + (i >> 1) * 16 + (i & 1) * 2;
        const uint32_t dst = (sx ^ ((i & 1) * 320)) + (i >> 1) * 4096, v0 = pack2(a[0], a[1]), v1 = pack2(a[4], a[5]);
        if (i < 6) sts128(dst, v0, v1, pack2(a[8], a[9]), pack2(a[12], a[13])); else sts64(dst, __uint_as_float(v0), __uint_as_float(v1));
      }
      named_arrive(12 + w4, 64);
    }
  }
}

typedef CUresult (*EncFn)(CUtensorMap*, CUtensorMapDataType, cuuint32_t, void*, const cuuint64_t*, const cuuint64_t*, const cuuint32_t*,
                          const cuuint32_t*, CUtensorMapInterleave, CUtensorMapSwizzle, CUtensorMapL2promotion, CUtensorMapFloatOOBfill);
void enc(EncFn f, CUtensorMap* m, const void* ptr, const cuuint64_t (&gd)[4], const cuuint64_t (&gs)[3], const cuuint32_t (&bx)[4], CUtensorMapSwizzle sw) {
  cuuint32_t es[4] = {1, 1, 1, 1};
  f(m, CU_TENSOR_MAP_DATA_TYPE_BFLOAT16, 4, (void*)ptr, gd, gs, bx, es, CU_TENSOR_MAP_INTERLEAVE_NONE, sw,
    CU_TENSOR_MAP_L2_PROMOTION_L2_128B, CU_TENSOR_MAP_FLOAT_OOB_FILL_NONE);
}
}

extern "C" void kernel_launch(void* const* d_in, const int* in_sizes, int n_in, void* d_out, int out_size) {
  (void)in_sizes; (void)n_in; (void)out_size;
  void* fp = nullptr;
  cudaDriverEntryPointQueryResult qr;
  cudaGetDriverEntryPoint("cuTensorMapEncodeTiled", &fp, cudaEnableDefault, &qr);
  EncFn f = (EncFn)fp;
  CUtensorMap m_w1, m_w2, m_b14, m_a8, m_b7, m_xt, m_wi;
  void* scr = nullptr;
  cudaGetSymbolAddress(&scr, g_scr);
  scr = (void*)((((uintptr_t)scr + PAGE - 1) & ~(uintptr_t)(PAGE - 1)) + -SCR_CNT);
  enc(f, &m_w1, d_in[4], {F_, 16, 1, S_ / 16}, {F_ * 2, F_ * 2, F_ * 32}, {64, 8, 1, 8}, CU_TENSOR_MAP_SWIZZLE_128B);
  {
    cuuint64_t gd[5] = {64, 7, 8, 2, S_ / 16}, gs[4] = {128, D_ * 4, D_ * 2, D_ * 32};
    cuuint32_t bx[5] = {64, 7, 8, 2, 4}, es[5] = {1, 1, 1, 1, 1};
    f(&m_xt, CU_TENSOR_MAP_DATA_TYPE_BFLOAT16, 5, d_in[0], gd, gs, bx, es, CU_TENSOR_MAP_INTERLEAVE_NONE, CU_TENSOR_MAP_SWIZZLE_128B,
      CU_TENSOR_MAP_L2_PROMOTION_L2_128B, CU_TENSOR_MAP_FLOAT_OOB_FILL_NONE);
  }
  enc(f, &m_w2, d_in[6], {S_, 1, 1, F_}, {S_ * 2, S_ * 2, S_ * 2}, {64, 1, 1, 64}, CU_TENSOR_MAP_SWIZZLE_128B);
  enc(f, &m_b14, scr, {64, 56, 1, G_END}, {128, GRP, GRP}, {64, 14, 1, 8}, CU_TENSOR_MAP_SWIZZLE_NONE);
  enc(f, &m_wi, d_in[1], {64, 21, 1, D_}, {128, D_ * 6, D_ * 6}, {64, 7, 1, 8}, CU_TENSOR_MAP_SWIZZLE_NONE);
  enc(f, &m_b7, scr, {64, 56, 1, G_END}, {128, GRP, GRP}, {64, 7, 1, 8}, CU_TENSOR_MAP_SWIZZLE_NONE);
  enc(f, &m_a8, scr, {64, 56, 1, G_END}, {128, GRP, GRP}, {64, 8, 1, 8}, CU_TENSOR_MAP_SWIZZLE_NONE);
  Params p;
  p.x = (const unsigned char*)d_in[0]; p.wo = (const unsigned char*)d_in[2];
  p.w1 = (const unsigned char*)d_in[4]; p.b1 = (const unsigned short*)d_in[5];
  p.w2 = (const unsigned char*)d_in[6]; p.b2 = (const unsigned short*)d_in[7];
  p.out = (unsigned char*)d_out; p.scr = (unsigned char*)scr;
  p.dw = 0x40000040u; p.dx = 64; p.db = 8; p.dk = 112;
  cudaFuncSetAttribute(fused_kernel, cudaFuncAttributeMaxDynamicSharedMemorySize, SMEM_BYTES);
  fused_kernel<<<128, NTHREADS, SMEM_BYTES, cudaStreamPerThread>>>(p, m_w1, m_w2, m_b14, m_a8, m_b7, m_xt, m_wi);
}
```

```cpp
#include <cuda_runtime.h>
#include <cuda.h>
#include <cuda_bf16.h>
#include <stdint.h>

template<int TA, int TB> __device__ __forceinline__ void wgmma_n112(float (&d)[56], uint32_t al, uint32_t ah, uint32_t bl, uint32_t bh, int sc) {
  asm volatile("{\n.reg .pred p;\n.reg .b64 a, b;\nsetp.ne.b32 p, %60, 0;\nmov.b64 a, {%56, %57};\nmov.b64 b, {%58, %59};\n"
    "wgmma.mma_async.sync.aligned.m64n112k16.f32.bf16.bf16 {%0, %1, %2, %3, %4, %5, %6, %7, %8, %9, %10, %11, %12, %13, %14, %15, %16, %17, %18, %19, %20, %21, %22, %23, %24, %25, %26, %27, %28, %29, %30, %31, %32, %33, %34, %35, %36, %37, %38, %39, %40, %41, %42, %43, %44, %45, %46, %47, %48, %49, %50, %51, %52, %53, %54, %55}, a, b, p, 1, 1, %61, %62;\n}\n"
    : "+f"(d[0]), "+f"(d[1]), "+f"(d[2]), "+f"(d[3]), "+f"(d[4]), "+f"(d[5]), "+f"(d[6]), "+f"(d[7]), "+f"(d[8]), "+f"(d[9]), "+f"(d[10]), "+f"(d[11]), "+f"(d[12]), "+f"(d[13]), "+f"(d[14]), "+f"(d[15]), "+f"(d[16]), "+f"(d[17]), "+f"(d[18]), "+f"(d[19]), "+f"(d[20]), "+f"(d[21]), "+f"(d[22]), "+f"(d[23]), "+f"(d[24]), "+f"(d[25]), "+f"(d[26]), "+f"(d[27]), "+f"(d[28]), "+f"(d[29]), "+f"(d[30]), "+f"(d[31]), "+f"(d[32]), "+f"(d[33]), "+f"(d[34]), "+f"(d[35]), "+f"(d[36]), "+f"(d[37]), "+f"(d[38]), "+f"(d[39]), "+f"(d[40]), "+f"(d[41]), "+f"(d[42]), "+f"(d[43]), "+f"(d[44]), "+f"(d[45]), "+f"(d[46]), "+f"(d[47]), "+f"(d[48]), "+f"(d[49]), "+f"(d[50]), "+f"(d[51]), "+f"(d[52]), "+f"(d[53]), "+f"(d[54]), "+f"(d[55])
    : "r"(al), "r"(ah), "r"(bl), "r"(bh), "r"(sc), "n"(TA), "n"(TB));
}

template<int TB> __device__ __forceinline__ void wgmma_rs_n80(float (&d)[40], const uint32_t (&a)[4], uint32_t bl, uint32_t bh, int sc) {
  asm volatile("{\n.reg .pred p;\n.reg .b64 b;\nsetp.ne.b32 p, %46, 0;\nmov.b64 b, {%44, %45};\n"
    "wgmma.mma_async.sync.aligned.m64n80k16.f32.bf16.bf16 {%0, %1, %2, %3, %4, %5, %6, %7, %8, %9, %10, %11, %12, %13, %14, %15, %16, %17, %18, %19, %20, %21, %22, %23, %24, %25, %26, %27, %28, %29, %30, %31, %32, %33, %34, %35, %36, %37, %38, %39}, {%40, %41, %42, %43}, b, p, 1, 1, %47;\n}\n"
    : "+f"(d[0]), "+f"(d[1]), "+f"(d[2]), "+f"(d[3]), "+f"(d[4]), "+f"(d[5]), "+f"(d[6]), "+f"(d[7]), "+f"(d[8]), "+f"(d[9]), "+f"(d[10]), "+f"(d[11]), "+f"(d[12]), "+f"(d[13]), "+f"(d[14]), "+f"(d[15]), "+f"(d[16]), "+f"(d[17]), "+f"(d[18]), "+f"(d[19]), "+f"(d[20]), "+f"(d[21]), "+f"(d[22]), "+f"(d[23]), "+f"(d[24]), "+f"(d[25]), "+f"(d[26]), "+f"(d[27]), "+f"(d[28]), "+f"(d[29]), "+f"(d[30]), "+f"(d[31]), "+f"(d[32]), "+f"(d[33]), "+f"(d[34]), "+f"(d[35]), "+f"(d[36]), "+f"(d[37]), "+f"(d[38]), "+f"(d[39])
    : "r"(a[0]), "r"(a[1]), "r"(a[2]), "r"(a[3]), "r"(bl), "r"(bh), "r"(sc), "n"(TB));
}

__device__ __forceinline__ void wgmma_sp_n32(float (&d)[16], const uint32_t (&a)[4], uint32_t bl, uint32_t bh, uint32_t meta, int sc) {
  asm volatile("{\n.reg .pred p;\n.reg .b64 b;\nsetp.ne.b32 p, %23, 0;\nmov.b64 b, {%20, %21};\n"
    "wgmma.mma_async.sp.sync.aligned.m64n32k32.f32.bf16.bf16 {%0, %1, %2, %3, %4, %5, %6, %7, %8, %9, %10, %11, %12, %13, %14, %15}, {%16, %17, %18, %19}, b, %22, 0, p, 1, 1, 1;\n}\n"
    : "+f"(d[0]), "+f"(d[1]), "+f"(d[2]), "+f"(d[3]), "+f"(d[4]), "+f"(d[5]), "+f"(d[6]), "+f"(d[7]), "+f"(d[8]), "+f"(d[9]), "+f"(d[10]), "+f"(d[11]), "+f"(d[12]), "+f"(d[13]), "+f"(d[14]), "+f"(d[15])
    : "r"(a[0]), "r"(a[1]), "r"(a[2]), "r"(a[3]), "r"(bl), "r"(bh), "r"(meta), "r"(sc));
}

template<int TB> __device__ __forceinline__ void wgmma_rs_n112(float (&d)[56], const uint32_t (&a)[4], uint32_t bl, uint32_t bh, int sc) {
  asm volatile("{\n.reg .pred p;\n.reg .b64 b;\nsetp.ne.b32 p, %62, 0;\nmov.b64 b, {%60, %61};\n"
    "wgmma.mma_async.sync.aligned.m64n112k16.f32.bf16.bf16 {%0, %1, %2, %3, %4, %5, %6, %7, %8, %9, %10, %11, %12, %13, %14, %15, %16, %17, %18, %19, %20, %21, %22, %23, %24, %25, %26, %27, %28, %29, %30, %31, %32, %33, %34, %35, %36, %37, %38, %39, %40, %41, %42, %43, %44, %45, %46, %47, %48, %49, %50, %51, %52, %53, %54, %55}, {%56, %57, %58, %59}, b, p, 1, 1, %63;\n}\n"
    : "+f"(d[0]), "+f"(d[1]), "+f"(d[2]), "+f"(d[3]), "+f"(d[4]), "+f"(d[5]), "+f"(d[6]), "+f"(d[7]), "+f"(d[8]), "+f"(d[9]), "+f"(d[10]), "+f"(d[11]), "+f"(d[12]), "+f"(d[13]), "+f"(d[14]), "+f"(d[15]), "+f"(d[16]), "+f"(d[17]), "+f"(d[18]), "+f"(d[19]), "+f"(d[20]), "+f"(d[21]), "+f"(d[22]), "+f"(d[23]), "+f"(d[24]), "+f"(d[25]), "+f"(d[26]), "+f"(d[27]), "+f"(d[28]), "+f"(d[29]), "+f"(d[30]), "+f"(d[31]), "+f"(d[32]), "+f"(d[33]), "+f"(d[34]), "+f"(d[35]), "+f"(d[36]), "+f"(d[37]), "+f"(d[38]), "+f"(d[39]), "+f"(d[40]), "+f"(d[41]), "+f"(d[42]), "+f"(d[43]), "+f"(d[44]), "+f"(d[45]), "+f"(d[46]), "+f"(d[47]), "+f"(d[48]), "+f"(d[49]), "+f"(d[50]), "+f"(d[51]), "+f"(d[52]), "+f"(d[53]), "+f"(d[54]), "+f"(d[55])
    : "r"(a[0]), "r"(a[1]), "r"(a[2]), "r"(a[3]), "r"(bl), "r"(bh), "r"(sc), "n"(TB));
}

namespace {
constexpr int S_ = 2048, D_ = 448, F_ = 1792;
constexpr int SLOT = 22528, BT = 14336;
constexpr int KV = 10 * 1792;
constexpr int OFF_KV = 8 * SLOT;
constexpr int OFF_X = OFF_KV - 64 * 896;
constexpr int OFF_U = OFF_KV + 2 * KV;
constexpr int OFF_PART = OFF_U + BT;
constexpr int OFF_BAR = OFF_PART + 768;
constexpr int OFF_OBS = OFF_BAR + 320;
constexpr int SMEM_BYTES = OFF_OBS + 512;
constexpr uint32_t base = 1024, bars = base + OFF_BAR;
#define DLY_X 1200
#define DLY_W 3100
#define TPW 170
#define PF0 2800
#define PACE1 450
#define PACE2 330
#define SY_H 750
#define SY_U 1470
#define SY_B 1000
#define PS_H 150
#define PH_U 300
#define DLY_Q 2000
#define DLY_D 2600
#define DLY_E 2500
#define PQ 240
#define PS_O 500
#define PU0 1300
#define DLY_P 3200
#define PH_O 800
#define SY_O 1150
#define SY_C 1000
#define NP_O 3
#define PK0 200
#define PB0 550
#define PFN 23
#define PF1 600
#define PACE3 350
#define NP_U 2
#define TUG 480
#define TUH 200
#define SA 0
#define SB 7
#define HK 1
#define NAP 30
#define NPB 2
#define KP 2
#define OBS(c, i) do {} while (0)
constexpr int NTHREADS = 384;
constexpr float LOG2E = 1.4426950408889634f;

constexpr int GRP = 7168;
constexpr int G_H = 0, G_W = 256, G_U = G_W + 168, G_WO = G_U + 224, G_O = G_WO + 56, G_HALO = G_O + 256, G_END = G_HALO + 128;
constexpr int SCR_LN = -S_ * 16, SCR_CNT = -65536;
constexpr int C_H = 0, C_U = 2, C_W = 3, C_TICKET = 4, C_O = 5, C_HALO = 37, C_END = 165;
#define PAGE_LOG 21
constexpr int PAGE = 1 << PAGE_LOG;
__device__ unsigned char g_scr[PAGE - SCR_CNT + G_END * GRP];

__device__ __forceinline__ uint32_t smem_u32(const void* p) { return (uint32_t)__cvta_generic_to_shared(p); }
__device__ __forceinline__ void mbar_init(uint32_t bar, uint32_t cnt) { asm volatile("mbarrier.init.shared::cta.b64 [%0], %1;" :: "r"(bar), "r"(cnt)); }
__device__ __forceinline__ void mbar_expect_tx(uint32_t bar, uint32_t bytes) { asm volatile("mbarrier.arrive.expect_tx.shared::cta.b64 _, [%0], %1;" :: "r"(bar), "r"(bytes) : "memory"); }
__device__ __forceinline__ void mbar_arrive(uint32_t bar) { asm volatile("mbarrier.arrive.shared::cta.b64 _, [%0];" :: "r"(bar) : "memory"); }
__device__ __forceinline__ void mbar_wait(uint32_t bar, uint32_t parity) {
  asm volatile("{\n.reg .pred p;\n.reg .u32 n;\nmov.u32 n, 0;\nLAB_WAIT:\n"
               "mbarrier.try_wait.parity.shared::cta.b64 p, [%0], %1;\n@p bra DONE;\n"
               "add.u32 n, n, 1;\nsetp.lt.u32 p, n, 4000000;\n@p bra LAB_WAIT;\ntrap;\nDONE:\n}" :: "r"(bar), "r"(parity) : "memory");
}
__device__ __forceinline__ void mbar_wait_u(uint32_t bar, uint32_t parity) {
  asm volatile("{\n.reg .pred p;\nLAB_WAIT:\nmbarrier.try_wait.parity.shared::cta.b64 p, [%0], %1;\n@!p bra LAB_WAIT;\n}" :: "r"(bar), "r"(parity) : "memory");
}
__device__ __forceinline__ uint32_t mbar_try(uint32_t bar, uint32_t parity) {
  uint32_t ok;
  asm volatile("{\n.reg .pred p;\nmbarrier.test_wait.parity.shared::cta.b64 p, [%1], %2;\nselp.u32 %0, 1, 0, p;\n}" : "=r"(ok) : "r"(bar), "r"(parity) : "memory");
  return ok;
}
__device__ __forceinline__ void tma4d(uint32_t dst, const CUtensorMap* m, int c0, int c1, int c3, uint32_t bar) {
  asm volatile("cp.async.bulk.tensor.4d.shared::cluster.global.mbarrier::complete_tx::bytes [%0], [%1, {%3, %4, %6, %5}], [%2];"
               :: "r"(dst), "l"(m), "r"(bar), "r"(c0), "r"(c1), "r"(c3), "r"(0) : "memory");
}
__device__ __forceinline__ void tma_store(const CUtensorMap* m, int c1, int c3, uint32_t src) {
  asm volatile("cp.async.bulk.tensor.4d.global.shared::cta.bulk_group [%0, {%4, %2, %4, %3}], [%1];" :: "l"(m), "r"(src), "r"(c1), "r"(c3), "r"(0) : "memory");
}
__device__ __forceinline__ void bulk_g2s(uint32_t dst, const void* src, uint32_t bytes, uint32_t bar) {
  asm volatile("cp.async.bulk.shared::cluster.global.mbarrier::complete_tx::bytes [%0], [%1], %2, [%3];" :: "r"(dst), "l"(src), "r"(bytes), "r"(bar) : "memory");
}
__device__ __forceinline__ void bulk_s2g(void* dst, uint32_t src, uint32_t bytes) {
  asm volatile("cp.async.bulk.global.shared::cta.bulk_group [%0], [%1], %2;" :: "l"(dst), "r"(src), "r"(bytes) : "memory");
}
__device__ __forceinline__ void wg_fence() { asm volatile("wgmma.fence.sync.aligned;" ::: "memory"); }
__device__ __forceinline__ void wg_commit() { asm volatile("wgmma.commit_group.sync.aligned;" ::: "memory"); }
template <int N> __device__ __forceinline__ void wg_wait() { asm volatile("wgmma.wait_group.sync.aligned %0;" :: "n"(N) : "memory"); }
__device__ __forceinline__ void smem_fence() { asm volatile("mbarrier.init.shared::cta.b64 [%0], 1;" :: "r"(bars + 280) : "memory"); }
__device__ __forceinline__ bool elect() {
  uint32_t r; asm volatile("{\n.reg .pred p;\nelect.sync _|p, 0xffffffff;\nselp.u32 %0, 1, 0, p;\n}" : "=r"(r)); return r != 0;
}
__device__ __forceinline__ void trap_if(bool c) { asm volatile("{\n.reg .pred p;\nsetp.ne.u32 p, %0, 0;\n@p trap;\n}" :: "r"((uint32_t)c)); }
__device__ __forceinline__ uint32_t gtime() { uint32_t v; asm volatile("mov.u32 %0, %%globaltimer_lo;" : "=r"(v)); return v; }
__device__ __forceinline__ void wait_until(uint32_t tn) {
  asm volatile("{\n.reg .pred p;\n.reg .u32 c;\nLAB_T:\nmov.u32 c, %%clock;\nsub.u32 c, c, %0;\nsetp.lt.s32 p, c, 0;\n@p nanosleep.u32 20;\n@p bra LAB_T;\n}" :: "r"(tn) : "memory");
}
__device__ __forceinline__ void spin_until(uint32_t tn) {
  asm volatile("{\n.reg .pred p;\n.reg .u32 c;\nLAB_T:\nmov.u32 c, %%clock;\nsub.u32 c, c, %0;\nsetp.lt.s32 p, c, 0;\n@p bra LAB_T;\n}" :: "r"(tn) : "memory");
}
__device__ __forceinline__ uint32_t keep(uint32_t v) { return __shfl_sync(0xffffffffu, v, threadIdx.x & 31); }
__device__ __forceinline__ uint32_t ld_l2(const void* p) { uint32_t v; asm volatile("ld.relaxed.gpu.global.u32 %0, [%1];" : "=r"(v) : "l"(p) : "memory"); return v; }
__device__ __forceinline__ void bump(unsigned char* cnt) { asm volatile("red.relaxed.gpu.global.inc.u32 [%0], 0xffffffff;" :: "l"(cnt) : "memory"); }
__device__ __forceinline__ void mark(unsigned char* cnt) {
  asm volatile("red.relaxed.gpu.global.max.u32 [%0+4], %1;" :: "l"(cnt), "r"(gtime()) : "memory");
}
__device__ __forceinline__ void bulk_wait() {
  asm volatile("cp.async.bulk.commit_group;" ::: "memory");
  asm volatile("cp.async.bulk.wait_group 0;" ::: "memory");
}
__device__ __forceinline__ void publish(unsigned char* cnt) {
  asm volatile("cp.async.bulk.commit_group;" ::: "memory");
  mark(cnt);
  asm volatile("cp.async.bulk.wait_group 0;" ::: "memory");
  bump(cnt);
}
__device__ __forceinline__ void landed() { asm volatile("fence.proxy.async;" ::: "memory"); }
__device__ __forceinline__ void spin_ge(const unsigned char* cnt, unsigned target) {
  asm volatile("{\n.reg .pred p;\n.reg .u32 n, v;\nmov.u32 n, 0;\nLAB_SPIN:\n"
               "ld.relaxed.gpu.global.u32 v, [%0];\nsetp.ge.u32 p, v, %1;\n@p bra DONE;\n"
               "add.u32 n, n, 1;\nsetp.lt.u32 p, n, 4000000;\n@p bra LAB_SPIN;\ntrap;\nDONE:\n}" :: "l"(cnt), "r"(target) : "memory");
}
__device__ __forceinline__ uint4 lds128(uint32_t a) { uint4 v; asm volatile("ld.shared.v4.u32 {%0,%1,%2,%3}, [%4];" : "=r"(v.x), "=r"(v.y), "=r"(v.z), "=r"(v.w) : "r"(a) : "memory"); return v; }
__device__ __forceinline__ uint32_t lds32(uint32_t a) { uint32_t v; asm volatile("ld.volatile.shared.u32 %0, [%1];" : "=r"(v) : "r"(a) : "memory"); return v; }
__device__ __forceinline__ void sts32(uint32_t a, uint32_t v) { asm volatile("st.shared.u32 [%0], %1;" :: "r"(a), "r"(v) : "memory"); }
__device__ __forceinline__ void sts128(uint32_t p, uint32_t a, uint32_t b, uint32_t c, uint32_t d) { asm volatile("st.shared.v4.u32 [%0], {%1,%2,%3,%4};" :: "r"(p), "r"(a), "r"(b), "r"(c), "r"(d) : "memory"); }
__device__ __forceinline__ void sts64(uint32_t p, float a, float b) { asm volatile("st.shared.v2.f32 [%0], {%1,%2};" :: "r"(p), "f"(a), "f"(b) : "memory"); }
__device__ __forceinline__ void named_sync(int id, int n) { asm volatile("bar.sync %0, %1;" :: "r"(id), "r"(n) : "memory"); }
__device__ __forceinline__ void named_arrive(int id, int n) { asm volatile("bar.arrive %0, %1;" :: "r"(id), "r"(n) : "memory"); }
__device__ __forceinline__ constexpr uint32_t dlo(uint32_t off, uint32_t lbo) { return ((base + off) >> 4) | (lbo >> 4 << 16); }
__device__ __forceinline__ uint32_t pack2(float lo, float hi) { uint32_t r; asm("cvt.rn.bf16x2.f32 %0, %1, %2;" : "=r"(r) : "f"(hi), "f"(lo)); return r; }
__device__ __forceinline__ float bf_lo(uint32_t v) { return __uint_as_float(v << 16); }
__device__ __forceinline__ float bf_hi(uint32_t v) { return __uint_as_float(v & 0xffff0000u); }
__device__ __forceinline__ float rbf(float x) { return bf_lo(pack2(x, 0.f)); }
__device__ __forceinline__ uint32_t hsub2(uint32_t a, uint32_t b) { uint32_t r; asm("sub.rn.bf16x2 %0, %1, %2;" : "=r"(r) : "r"(a), "r"(b)); return r; }
__device__ __forceinline__ uint32_t hadd2(uint32_t a, uint32_t b) { uint32_t r; asm("add.rn.bf16x2 %0, %1, %2;" : "=r"(r) : "r"(a), "r"(b)); return r; }
__device__ __forceinline__ uint32_t hmax2(uint32_t a, uint32_t b) { uint32_t r; asm("max.bf16x2 %0, %1, %2;" : "=r"(r) : "r"(a), "r"(b)); return r; }
__device__ __forceinline__ uint32_t hmul2(uint32_t a, uint32_t b) { uint32_t r; asm("mul.rn.bf16x2 %0, %1, %2;" : "=r"(r) : "r"(a), "r"(b)); return r; }
__device__ __forceinline__ uint32_t hfma2(uint32_t a, uint32_t b, uint32_t c) { uint32_t r; asm("fma.rn.bf16x2 %0, %1, %2, %3;" : "=r"(r) : "r"(a), "r"(b), "r"(c)); return r; }
__device__ __forceinline__ float tanh_fast(float x) { float r; asm("tanh.approx.f32 %0, %1;" : "=f"(r) : "f"(x)); return r; }
__device__ __forceinline__ float rcp_fast(float x) { float r; asm("rcp.approx.ftz.f32 %0, %1;" : "=f"(r) : "f"(x)); return r; }
__device__ __forceinline__ float ex2_fast(float x) { float r; asm("ex2.approx.ftz.f32 %0, %1;" : "=f"(r) : "f"(x)); return r; }
__device__ __forceinline__ void ldsm4(uint32_t (&r)[4], uint32_t addr) {
  asm volatile("ldmatrix.sync.aligned.m8n8.x4.shared.b16 {%0,%1,%2,%3}, [%4];" : "=r"(r[0]), "=r"(r[1]), "=r"(r[2]), "=r"(r[3]) : "r"(addr) : "memory");
}
__device__ __forceinline__ void stsm4(uint32_t addr, uint32_t a, uint32_t b, uint32_t c, uint32_t d) {
  asm volatile("stmatrix.sync.aligned.m8n8.x4.shared.b16 [%0], {%1,%2,%3,%4};" :: "r"(addr), "r"(a), "r"(b), "r"(c), "r"(d) : "memory");
}
__device__ __forceinline__ void stsm2(uint32_t addr, uint32_t a, uint32_t b) {
  asm volatile("stmatrix.sync.aligned.m8n8.x2.shared.b16 [%0], {%1,%2};" :: "r"(addr), "r"(a), "r"(b) : "memory");
}
__device__ __forceinline__ void stg128(void* p, const uint32_t* r) { asm volatile("st.global.v4.u32 [%0], {%1,%2,%3,%4};" :: "l"(p), "r"(r[0]), "r"(r[1]), "r"(r[2]), "r"(r[3]) : "memory"); }
__device__ __forceinline__ void stg64(void* p, const uint32_t* r) { asm volatile("st.global.v2.u32 [%0], {%1,%2};" :: "l"(p), "r"(r[0]), "r"(r[1]) : "memory"); }
__device__ __forceinline__ void load_row(uint32_t (&r)[14], const unsigned char* p, int t) {
#pragma unroll
  for (int i = 0; i < 3; i++)
    asm volatile("ld.global.nc.L1::no_allocate.v4.u32 {%0,%1,%2,%3}, [%4];" : "=r"(r[4 * i]), "=r"(r[4 * i + 1]), "=r"(r[4 * i + 2]), "=r"(r[4 * i + 3]) : "l"(p + i * 64 + t * 16));
  asm volatile("ld.global.nc.L1::no_allocate.v2.u32 {%0,%1}, [%2];" : "=r"(r[12]), "=r"(r[13]) : "l"(p + 192 + (t & 1) * 16 + (t >> 1) * 8));
}
__device__ __forceinline__ void lds_row(uint32_t* r, uint32_t a, int t) {
#pragma unroll
  for (int i = 0; i < 3; i++) { const uint4 v = lds128(a + i * 64 + t * 16); r[4 * i] = v.x; r[4 * i + 1] = v.y; r[4 * i + 2] = v.z; r[4 * i + 3] = v.w; }
  asm volatile("ld.shared.v2.u32 {%0,%1}, [%2];" : "=r"(r[12]), "=r"(r[13]) : "r"(a + 192 + (t & 1) * 16 + (t >> 1) * 8) : "memory");
}
__device__ __forceinline__ void tile_row(uint32_t* r, int tok, int d, int t) {
  const int xi = (tok >> 1) & 7;
#pragma unroll
  for (int j = 0; j < 4; j++) {
    const int c = d * 14 + (j < 3 ? 4 * j + t : 12 + (t & 1));
    const uint4 v = lds128(base + OFF_X + ((tok & 48) + (tok & 1) * 8 + xi) * 896 + (c >> 3) * 128 + (((c ^ ((c >> 3) - xi)) & 7) << 4));
    if (j < 3) { r[4 * j] = v.x; r[4 * j + 1] = v.y; r[4 * j + 2] = v.z; r[4 * j + 3] = v.w; }
    else { r[12] = t >> 1 ? v.z : v.x; r[13] = t >> 1 ? v.w : v.y; }
  }
}

struct LnC { uint32_t m, rh, rl; float r; };
__device__ __forceinline__ LnC ln_consts(float mean, float var) {
  float sd;
  asm("sqrt.approx.ftz.f32 %0, %1;" : "=f"(sd) : "f"(rbf(rbf(var) + 1e-5f)));
  const float r = rcp_fast(rbf(sd)), rh = rbf(r);
  return {pack2(mean, mean), pack2(rh, rh), pack2(r - rh, r - rh), r};
}
__device__ __forceinline__ float variance(float mean, float sq) { return fmaxf(fmaf(-mean, mean, sq * (1.0f / D_)), 0.f); }
__device__ __forceinline__ uint32_t ln_apply(uint32_t x, const LnC& c) { const uint32_t d = hsub2(x, c.m); return hfma2(d, c.rh, hmul2(d, c.rl)); }

template <int N> __device__ __forceinline__ void fresh(float (&a)[N]) {
#pragma unroll
  for (int i = 0; i < N; i++) asm volatile("" : "=f"(a[i]));
}
__device__ __forceinline__ void pin(uint32_t (&a)[4]) { asm volatile("" : "+r"(a[0]), "+r"(a[1]), "+r"(a[2]), "+r"(a[3])); }
constexpr int B_EMPTY = 64, B_F0 = 128, B_F1 = 136, B_HALO = 144, B_WO = 160, B_XF = 168, B_X = 176, B_HL = 184, B_OS = 200, B_RL = 216, B_RS = 248, S_FLAG = 288;
constexpr int N_GO = 6, N_DONE = 7;
constexpr int F_H = 0, F_U = 2, F_O = 3;
__device__ __forceinline__ void watch_flag(int slot, const unsigned char* cnt, unsigned target) {
  asm volatile("{\n.reg .pred p;\n.reg .u32 n, v, t;\nmov.u32 n, 0;\nLAB_SPIN:\n"
               "ld.relaxed.gpu.global.v2.u32 {v, t}, [%1];\nsetp.ge.u32 p, v, %2;\n@p st.volatile.shared.v2.u32 [%0], {v, t};\n"
               "ld.volatile.shared.u32 v, [%0];\nsetp.ne.u32 p, v, 0;\n@p bra DONE;\n"
               "add.u32 n, n, 1;\nsetp.lt.u32 p, n, 4000000;\n@p bra LAB_SPIN;\ntrap;\nDONE:\n}" :: "r"(bars + S_FLAG + slot * 8), "l"(cnt), "r"(target) : "memory");
}
__device__ __forceinline__ uint32_t wait_flag(int slot, int delay = 0) {
  uint32_t v, last;
  while (true) {
    asm volatile("ld.volatile.shared.v2.u32 {%0, %1}, [%2];" : "=r"(v), "=r"(last) : "r"(bars + S_FLAG + slot * 8) : "memory");
    if (v) break;
    __nanosleep(NAP);
  }
  while (gtime() - last < (uint32_t)delay);
  return last;
}
__device__ __forceinline__ void arrive_if(int id, bool on) {
  asm volatile("{\n.reg .pred p;\nsetp.ne.u32 p, %1, 0;\n@p bar.arrive %0, 256;\n}" :: "r"(id), "r"((uint32_t)on) : "memory");
}
template <int TA, class Hook>
__device__ __forceinline__ void stage(float (&acc)[56], uint32_t ah, uint32_t bh, int sb, uint32_t par, uint32_t& ok, int& g_tr, bool first, bool rel, Hook hook, const uint32_t (*X)[4] = nullptr) {
  if (!ok) mbar_wait(bars + sb * 8, par);
  wg_fence();
#pragma unroll
  for (int k = 0; k < 4; k++) {
    if constexpr (TA == 2) wgmma_rs_n112<1>(acc, X[k], dlo(sb * SLOT + 8192 + k * 3584, 1792), bh, k || !first);
    else wgmma_n112<TA, 1>(acc, dlo(sb * SLOT + k * (TA ? 2048 : 256), TA ? 8192 : 128), ah, dlo(sb * SLOT + 8192 + k * 3584, 1792), bh, k || !first);
    if (k == 1) ok = mbar_try(bars + ((sb + 1) & 7) * 8, sb == 7 ? par ^ 1 : par);
    hook(k);
  }
  wg_commit();
  wg_wait<1>();
  if (rel) mbar_arrive(bars + B_EMPTY + ((sb + 7) & 7) * 8);
}

struct Params {
  const unsigned char* x;
  unsigned char *scr, *out;
  uint32_t dw, dx, db, dk;
  const unsigned char *wo, *w1, *w2;
  const unsigned short *b1, *b2;
};

__global__ void __launch_bounds__(NTHREADS, 1)
fused_kernel(const Params p, const __grid_constant__ CUtensorMap m_w1, const __grid_constant__ CUtensorMap m_w2, const __grid_constant__ CUtensorMap m_b14,
             const __grid_constant__ CUtensorMap m_a8, const __grid_constant__ CUtensorMap m_b7, const __grid_constant__ CUtensorMap m_xt, const __grid_constant__ CUtensorMap m_wi) {
  extern __shared__ __align__(1024) unsigned char smem_raw[];
  const uint32_t t0 = clock();
  const int tid = threadIdx.x, lane = tid & 31, b = blockIdx.x;
  const int g = lane >> 2, t = lane & 3, r8 = lane & 7, mi = lane >> 3;
  uint32_t H[14];
  if (tid < 128) load_row(H, p.x + (b * 16 + g) * (D_ * 2) + (tid >> 5) * 224, t);
  const int warp = __shfl_sync(0xffffffffu, tid >> 5, 0);
  const int dt = b & 3, mt = b >> 2;
  const bool g1 = b < 112;
  const int kg0 = (mt & 3) * 14 + dt * 4, nk = dt < 3 ? 4 : 2;
  auto cnt = [&](int i) { return p.scr + (SCR_CNT + i * 128); };
  auto get_tag = [&]() { return (wait_flag(F_H) >> 5) & 0x3fffbfffu; };
  auto tag_at = [&](int i) { return base + OFF_KV + i * KV + min(lane, 27) * 128 + (lane < 14 ? 0 : 112 - i * 16); };
  auto fetch_halo = [&](int i, uint32_t tag) {
    if (mt > 0) {
      const uint32_t tp = keep(tag_at(i));
      uint32_t ph = 0;
      spin_ge(cnt(C_HALO + b - 4), i + 1);
      do {
        trap_if(ph > 1000000);
        if (elect()) { mbar_expect_tx(bars + B_HL + i * 8, 3584); bulk_g2s(base + OFF_KV + i * KV, p.scr + ((G_HALO + b - 4) * GRP + i * 3584), 3584, bars + B_HL + i * 8); }
        mbar_wait(bars + B_HL + i * 8, ph++ & 1);
      } while (__any_sync(0xffffffffu, lds32(tp) != tag));
    }
    if (lane == 0) mbar_arrive(bars + B_HALO + i * 8);
    OBS(lane == 0, i ? 122 : 29);
  };
  if (warp >= 8) {
    if (warp == 8) {
      if (elect()) {
        asm volatile("prefetch.tensormap [%0];" :: "l"(&m_xt) : "memory");
        trap_if(smem_u32(smem_raw) != base);
#pragma unroll
        for (int i = 0; i < B_RL; i += 8) mbar_init(bars + i, i == B_XF ? 8 : i >= B_OS ? 4 : (i == B_HALO || i == B_HALO + 8 || ((i == B_F1 || i == B_WO) && !g1) ? 2 : 1));
        if (!g1) {
#pragma unroll
          for (int i = 0; i < 64; i += 8) mbar_init(bars + B_RL + i, i < 32 ? 1 : 4);
        }

#pragma unroll
        for (int i = 0; i < 32; i += 16) sts128(bars + S_FLAG + i, 0, 0, 0, 0);
        asm volatile("fence.mbarrier_init.release.cluster;" ::: "memory");
      }
      __syncwarp();
      named_arrive(12, 160); named_arrive(13, 160);
    }
    named_sync(15, 128);
    asm volatile("setmaxnreg.dec.sync.aligned.u32 80;");
    if (warp == 8) {
      if (elect()) {
        wait_until(t0 + DLY_X);
        mbar_expect_tx(bars + B_X, 64 * 896);
        asm volatile("cp.async.bulk.tensor.5d.shared::cluster.global.mbarrier::complete_tx::bytes [%0], [%1, {%4, %4, %4, %4, %3}], [%2];"
                     :: "r"(base + OFF_X), "l"(&m_xt), "r"(bars + B_X), "r"(mt * 4), "r"(0) : "memory");
        if (g1) {
          wait_until(t0 + DLY_D);
          asm volatile("prefetch.tensormap [%0];" :: "l"(&m_w1) : "memory");
          asm volatile("prefetch.tensormap [%0];" :: "l"(&m_b14) : "memory");
#pragma unroll 1
          for (int c = 0; c < 8; c++) {
            wait_until(t0 + DLY_W + c * TPW);
            if (c == 6) mbar_wait(bars + B_XF, 0);
            tma4d(base + c * SLOT, &m_w1, mt * 64, 0, c * 8, bars + c * 8);
          }
        } else {
          asm volatile("prefetch.tensormap [%0];" :: "l"(&m_wi) : "memory");
#pragma unroll 1
          for (int i = 0; i < 16; i++) {
            const int m = i >> 2, j = i & 3;
            if (j == 0) mbar_expect_tx(bars + B_RL + m * 8, nk * GRP);
            wait_until(t0 + DLY_Q + i * PQ);
            if (j >= nk) continue;
            if (m < 3) tma4d(base + i * GRP, &m_wi, 0, (m + 1) % 3 * 7, (kg0 + j) * 8, bars + B_RL + m * 8);
            else bulk_g2s(base + OFF_KV + j * GRP, p.wo + (kg0 + j) * GRP, GRP, bars + B_RL + 24);
          }
        }
#pragma unroll 1
        for (int r = g1 ? 1 : 4; r < 4; r++) {
#pragma unroll
          for (int s = 0; s < 8; s++) {
            mbar_wait_u(bars + B_EMPTY + s * 8, (r & 1) ^ 1);
            tma4d(base + s * SLOT, &m_w1, mt * 64, (r & 2) * 4, (r & 1) * 64 + s * 8, bars + s * 8);
          }
        }
        mbar_wait(bars + B_WO, 0);
#pragma unroll 1
        for (int r = 0; ; r++) {
#pragma unroll
          for (int j = 0; j < 8; j++) {
            const int s = (j + 5) & 7;
            mbar_wait_u(bars + B_EMPTY + s * 8, (r + (j < 3)) & 1);
            tma4d(base + s * SLOT, &m_w2, mt * 64, 0, r * 512 + j * 64, bars + s * 8);
            if (j == 3 && r == 3) goto w2_done;
          }
        }
        w2_done:
        wait_flag(F_O, SY_O);
        OBS(1, 22);
#pragma unroll
        for (int s = 1; s < 8; s++) {
          mbar_wait_u(bars + B_EMPTY + s * 8, 1);
          tma4d(base + s * SLOT, &m_a8, 0, s * 8 - 8, G_O + mt * 8, bars + s * 8);
        }
      }
    } else if (warp == 9) {
      if (elect()) {
        const uint32_t early = ld_l2(cnt(C_H));
        wait_until(t0 + DLY_E);
        asm volatile("prefetch.tensormap [%0];" :: "l"(&m_b7) : "memory");
        asm volatile("prefetch.tensormap [%0];" :: "l"(&m_w2) : "memory");
        asm volatile("prefetch.tensormap [%0];" :: "l"(&m_a8) : "memory");
        uint32_t bytes = SLOT, tn;
        if (g1) {
#pragma unroll
          for (int s = 0; s < 8; s++) mbar_expect_tx(bars + s * 8, SLOT);
          if (early < 128) wait_until(t0 + DLY_P);
          watch_flag(F_H, cnt(C_H), 128);
          wait_flag(F_H, SY_H);
#pragma unroll
          for (int s = 0; s < 8; s++) {
            if (s == 5) mbar_wait(bars + B_XF, 0);
            tma4d(base + s * SLOT + 8192, &m_b14, 0, dt * 14, s * 8, bars + s * 8);
            if (s == 0) OBS(1, 16);
          }
        }
#pragma unroll 1
        for (int r = g1 ? 1 : 4; r < 11; r++) {
          if (r == 2) { mbar_wait(bars + B_F0, 0); OBS(1, 17); }
          if (r == 4) { mbar_wait(bars + B_F1, 0); OBS(1, 18); bytes = BT; }
#pragma unroll
          for (int s = 0; s < 8; s++) {
            if (s) mbar_wait_u(bars + B_EMPTY + s * 8, (r & 1) ^ 1); else mbar_wait(bars + B_EMPTY, (r & 1) ^ 1);
            if (s == 5 && r == 6) { bytes = SLOT; wait_flag(F_U, SY_U); tn = clock() + TUG; OBS(1, 20); }
            if (s > 5 && r == 6) spin_until(tn + (s - 6) * TUH);
            mbar_expect_tx(bars + s * 8, bytes);
            tma4d(base + s * SLOT + 8192, &m_b14, 0, dt * 14, r * 64 + s * 8, bars + s * 8);
          }
        }
      }
    } else if (warp == 10) {
      uint32_t tn = t0 + PF0;
      const unsigned char* src = p.w1 + (b + b / 7 * 7) * 4096 + lane * 128;
#pragma unroll 1
      for (int i = g1 ? 0 : 32; i < 32; i++) {
        if (i == PFN) { wait_flag(F_U, PF1); tn = clock(); }
        wait_until(tn);
        if (i == 8) src -= 16 * 458752 - 8 * 3584;
        if (i == 16) src = p.w2 + b * 4096 + lane * 128;
        asm volatile("prefetch.global.L2 [%0];" :: "l"(src) : "memory");
        src += i < 16 ? 2 * 458752 : 458752;
        tn += i < 16 ? PACE1 : (i < PFN ? PACE2 : PACE3);
      }
      if (!g1 && elect()) {
#pragma unroll 1
        for (int m = 0; m < 3; m++) {
          mbar_wait(bars + B_RS + m * 8, 0);
          bulk_s2g(p.scr + (G_W + m * 56 + kg0) * GRP, base + (12 + m * 4) * GRP, nk * GRP);
        }
        bulk_wait();
        mbar_arrive(bars + B_F1);
        landed();
        bump(cnt(C_W));
        OBS(1, 6);
        mbar_wait(bars + B_RS + 24, 0);
#pragma unroll 1
        for (int i = 0; i < nk; i++) bulk_s2g(p.scr + (G_WO + kg0 + i) * GRP, base + i * SLOT, GRP);
        bulk_wait();
        mbar_arrive(bars + B_WO);
        landed();
        bump(cnt(C_U));
        OBS(1, 16);
      }
      __syncwarp();
      wait_flag(F_U);
      watch_flag(F_O, cnt(C_O + mt), 4);
      unsigned tk = 0;
      if (lane == 0) tk = atomicAdd((unsigned*)cnt(C_TICKET), 1);
      if (__any_sync(0xffffffffu, tk == 127)) {
#pragma unroll 1
        for (int i = lane; i < C_END; i += 32) *(uint2*)cnt(i) = make_uint2(0, 0);
      }
    } else {
      unsigned char* hg = p.scr + (G_H + b) * GRP;
      const uint32_t early = ld_l2(cnt(C_H + 1));
      if (mt == 0) {
#pragma unroll
        for (int i = 0; i < 14; i++) sts128(base + OFF_KV + (i / 7) * KV + (i % 7) * 512 + lane * 16, 0, 0, 0, 0);
      }
      named_sync(10, 160);
      smem_fence();
      if (elect()) { bulk_s2g(hg, base + OFF_U, GRP); publish(cnt(C_H)); OBS(1, 3); }
      __syncwarp();
      named_sync(9, 160);
      if (!g1) {
        smem_fence();
        if (elect()) { bulk_s2g(hg + 128 * GRP, base + OFF_U + GRP, GRP); publish(cnt(C_H + 1)); }
        __syncwarp();
        watch_flag(F_H, cnt(C_H), 128);
      }
      const uint32_t tag = get_tag();
      if (lane < 16) sts32(base + OFF_PART + 512 + lane * 16 + 12, tag);
      smem_fence();
      __syncwarp();
      if (elect()) {
        bulk_s2g(p.scr + (SCR_LN + b * 256), base + OFF_PART + 512, 256);
        if (g1) {
          wait_flag(F_H, SY_B);
          const uint32_t tn = clock();
#pragma unroll
          for (int i = 0; i < NPB; i++) { if (i) wait_until(tn + i * PS_H); bulk_s2g(hg + (128 * GRP + i * (GRP / NPB)), base + OFF_U + GRP + i * (GRP / NPB), GRP / NPB); }
          publish(cnt(C_H + 1));
        }
        OBS(1, 4);
      }
      __syncwarp();
      if (early < 128) wait_until(clock() + PB0);
      watch_flag(F_H + 1, cnt(C_H + 1), 128);
      wait_flag(F_H + 1, SY_C);
      if (lane == 0) mbar_arrive(bars + B_F0);
      spin_ge(cnt(C_W), 16);
      if (lane == 0) mbar_arrive(bars + B_F1);
      const uint32_t have = ld_l2(cnt(C_HALO + max(b - 4, 0)));
      if (g1) {
        named_sync(14, 160);
        smem_fence();
        if (elect()) tma_store(&m_b7, dt * 14, G_U + mt * 8, base + OFF_U);
        named_sync(10, 160);
        smem_fence();
        if (elect()) { tma_store(&m_b7, dt * 14 + 7, G_U + mt * 8, base + OFF_U + GRP); publish(cnt(C_U)); OBS(1, 7); }
        __syncwarp();
      }
      if (!have) wait_until(clock() + PK0);
#pragma unroll 1
      for (int i = 0; i < 2; i++) fetch_halo(i, tag);
      if (elect()) {
        mbar_wait(bars + B_OS, 0);
        const uint32_t tn = clock() + PS_O;
        tma_store(&m_b7, dt * 14, G_O + mt * 8, base + OFF_U);
        mbar_wait(bars + B_OS + 8, 0);
        wait_until(tn);
        tma_store(&m_b7, dt * 14 + 7, G_O + mt * 8, base + OFF_U + GRP);
        OBS(1, 14);
        publish(cnt(C_O + mt));
        OBS(1, 120);
      }
    }
  } else {
    const int wg = warp >> 2, w4 = warp & 3;
    const bool rel = (tid & 127) == 0;
    auto put_row = [&](uint32_t st, const uint32_t* r) {
#pragma unroll
      for (int i = 0; i < 3; i++) stsm4(st + i * 512, r[4 * i], r[4 * i + 1], r[4 * i + 2], r[4 * i + 3]);
      stsm2(st + 1536, r[12], r[13]);
    };
    auto put_half = [&](int hf, const uint32_t* r) {
      const uint32_t st = base + OFF_U + hf * GRP + (w4 * 2 + (mi & 1)) * 896 + (mi >> 1) * 128 + r8 * 16;
#pragma unroll
      for (int j = 0; j < 3; j++) stsm4(st + j * 256, r[4 * j], r[4 * j + 1], r[4 * j + 2], r[4 * j + 3]);
      stsm2(st + 768, r[12], r[13]);
    };
    {
      if (wg) { named_sync(13, 160); mbar_wait(bars + B_X, 0); tile_row(H, dt * 16 + 8 + g, w4, t); }
      const uint32_t part = base + OFF_PART + wg * 256 + g * 32;
      float s0 = 0.f, s1 = 0.f, q0 = 0.f, q1 = 0.f;
#pragma unroll
      for (int j = 0; j < 14; j++) { const float a = bf_lo(H[j]), c = bf_hi(H[j]); s0 += a; s1 += c; q0 = fmaf(a, a, q0); q1 = fmaf(c, c, q1); }
      s0 += s1; q0 += q1;
#pragma unroll
      for (int o = 1; o < 4; o <<= 1) { s0 += __shfl_xor_sync(0xffffffffu, s0, o); q0 += __shfl_xor_sync(0xffffffffu, q0, o); }
      if (t == 0) sts64(part + w4 * 8, s0, q0);
      OBS(tid == 0, 0);
      named_sync(1 + wg, 128);
      const uint4 u = lds128(part), v = lds128(part + 16);
      const float mean = ((__uint_as_float(u.x) + __uint_as_float(u.z)) + (__uint_as_float(v.x) + __uint_as_float(v.z))) * (1.0f / D_);
      const float var = variance(mean, (__uint_as_float(u.y) + __uint_as_float(u.w)) + (__uint_as_float(v.y) + __uint_as_float(v.w)));
      const LnC l = ln_consts(mean, var), l2 = ln_consts((mean - bf_lo(l.m)) * l.r, var * l.r * l.r);
#pragma unroll
      for (int j = 0; j < 14; j++) H[j] = ln_apply(ln_apply(H[j], l), l2);
      put_row(base + OFF_U + warp * 1792 + lane * 16, H);
      if (w4 == 0 && t == 0) sts128(base + OFF_PART + 512 + wg * 128 + g * 16, l.m, l.rh, l.rl, 0);
      named_arrive(10 - wg, 160);
      OBS(rel, 1 + wg);
    }
    uint32_t ok = 0;
    int trc = 0;
    auto nohook = [](int) {};
#define OBS0(c, i) ok = 0
    if (wg == 0) {
      uint32_t hb[4], R[28];
      named_sync(12, 160);
#pragma unroll
      for (int i = 0; i < 4; i++)
        asm volatile("ld.relaxed.cta.global.u16 %0, [%1];" : "=r"(hb[i]) : "l"((i < 2 ? p.b1 + (g1 ? mt * 64 : 0) : p.b2 + mt * 64) + w4 * 16 + g + (i & 1) * 8) : "memory");
      mbar_wait(bars + B_X, 0);
#pragma unroll
      for (int h = 0; h < 2; h++) tile_row(R + h * 14, w4 * 16 + h * 8 + g, dt, t);
      if (lane == 0) mbar_arrive(bars + B_XF + (R[0] | R[4] | R[8] | R[12] | R[14] | R[18] | R[22] | R[26]) * threadIdx.y);
      float acc[56];
      if (g1) {
#pragma unroll
        for (int i = 0; i < 56; i++) { acc[i] = bf_lo(hb[(i >> 1) & 1]); asm volatile("" : "+f"(acc[i])); }
        OBS0(0, 5);
#pragma unroll 1
        for (int r = 0; r < 4; r++)
#pragma unroll
          for (int c = 0; c < 8; c++) stage<1>(acc, p.dw, p.db, c, r & 1, ok, trc, false, rel && (c || r), [&](int k) { if (c == 7 && k == 3 - HK) arrive_if(3, r == 3); });
        wg_wait<0>();
        if (rel) mbar_arrive(bars + B_EMPTY + 7 * 8);
        OBS(rel, 6);
#pragma unroll
        for (int hf = 0; hf < 2; hf++) {
          uint32_t U[14];
#pragma unroll
          for (int j = 0; j < 14; j++) {
            const float a = acc[hf * 28 + 2 * j], c = acc[hf * 28 + 2 * j + 1];
            U[j] = pack2(fmaf(a, tanh_fast(a * fmaf(a * a, 0.0356774081f, 0.7978845608f)), a), fmaf(c, tanh_fast(c * fmaf(c * c, 0.0356774081f, 0.7978845608f)), c));
          }
          put_half(hf, U);
          named_arrive(hf ? 10 : 14, 160);
          if (!hf) mbar_wait(bars + B_X, 0);
        }
        OBS(rel, 30);
      } else {
#pragma unroll 1
        for (int m = 0; m < 3; m++) {
          mbar_wait(bars + B_RL + m * 8, 0);
          OBS(tid == 0 && m == 0, 7);
          if (w4 < nk) {
            uint4 v[14];
#pragma unroll
            for (int l = 0; l < 14; l++) v[l] = lds128(base + (m * 4 + w4) * GRP + r8 * 896 + (l >> 1) * 128 + ((r8 + mi + (l & 1) * 4) & 7) * 16);
#pragma unroll
            for (int l = 0; l < 14; l++) sts128(base + (12 + m * 4 + w4) * GRP + (l >> 1) * 1024 + ((r8 + mi + (l & 1) * 4) & 7) * 128 + r8 * 16, v[l].x, v[l].y, v[l].z, v[l].w);
          }
          smem_fence();
          __syncwarp();
          if (lane == 0) mbar_arrive(bars + B_RS + m * 8);
          if (m == 0) mbar_wait(bars + B_XF, 0);
        }
        named_sync(1, 128);
        mbar_wait(bars + B_RL + 24, 0);
#pragma unroll 1
        for (int i = 0; i < nk; i++) {
          uint32_t W[14];
          lds_row(W, base + OFF_KV + i * GRP + g * 896 + w4 * 224, t);
          put_row(base + i * SLOT + w4 * 1792 + lane * 16, W);
        }
        smem_fence();
        __syncwarp();
        if (lane == 0) mbar_arrive(bars + B_RS + 24);
        named_sync(1, 128);
        named_arrive(3, 256);
      }
#pragma unroll
      for (int i = 0; i < 56; i++) { acc[i] = 0.f; asm volatile("" : "+f"(acc[i])); }
#pragma unroll
      for (int i = 2; i < 4; i++) hb[i] = keep(hmul2(hb[i] * 0x10001u, 0x3f003f00u));
      const uint32_t oo = keep((mt * 64 + w4 * 16 + g) * (D_ * 2) + dt * 224 + t * 16), oq = keep(oo + 192 - (t >> 1) * 24);
      const uint32_t sx = keep(base + OFF_KV + w4 * 512 + ((g & 1) * 4 + ((g >> 1) ^ (g & 1))) * 64 + t * 16);
      if (w4 == 3) {
        const uint32_t tag = get_tag();
#pragma unroll 1
        for (int i = 0; i < 2; i++) {
          const uint32_t tp = keep(tag_at(i) + 8 * 1792);
          named_sync(i ? 0 : 11, 64);
          if (mt < 31) {
            const uint32_t own = lds32(tp);
            sts32(tp, tag);
            smem_fence();
            __syncwarp();
            if (elect()) { bulk_s2g(p.scr + ((G_HALO + b) * GRP + i * 3584), base + OFF_KV + i * KV + 8 * 1792, 3584); bump(cnt(C_HALO + b)); bulk_wait(); }
            __syncwarp();
            OBS(lane == 0, i ? 15 : 23);
            sts32(tp, own);
            smem_fence();
            __syncwarp();
          }
          if (lane == 0) mbar_arrive(bars + B_HALO + i * 8);
        }
      } else if (w4 < NP_U) { wait_until(clock() + PU0 + w4 * PH_U); watch_flag(F_U, cnt(C_U), 128); OBS(tid == 0, 121); }
      named_sync(5, 256);
      OBS0(21, 10);
#pragma unroll 1
      for (int r = 0; ; r++) {
#pragma unroll
        for (int j = 0; j < 8; j++) {
          const bool site = j == SA % 8 || j == SB % 8, yield = (j == SA % 8 && r == SA / 8) || (j == SB % 8 && r == SB / 8);
          stage<1>(acc, p.dw, p.db, (j + 5) & 7, (r + (j > 2)) & 1, ok, trc, false, rel && (j || r), [&](int k) {
            if (k == 3 - HK) { if (site) arrive_if(N_GO, yield); if (j == 3) arrive_if(8, r == 3); } });
          if (site && yield) named_sync(N_DONE, 256);
          if (j == 3 && r == 3) goto gemm2_done;
        }
      }
      gemm2_done:
      wg_wait<0>();
      OBS(rel, 24);
      uint32_t G[28], dep = 0;
#pragma unroll
      for (int j = 0; j < 28; j++) {
        const uint32_t hh = hfma2(pack2(acc[2 * j], acc[2 * j + 1]), 0x3e803e80u, hb[2 + (j & 1)]);
        const float a = bf_lo(hh), c = bf_hi(hh);
        G[j] = pack2(fmaf(a, tanh_fast(a), a), fmaf(c, tanh_fast(c), c));
        dep |= G[j];
      }
      OBS(rel, 26);
      named_sync(12 + w4 + dep * threadIdx.y, 64);
      uint4 S4[8];
#pragma unroll
      for (int i = 0; i < 8; i++) S4[i] = lds128(sx + i * 2048);
#pragma unroll
      for (int i = 0; i < 8; i++) {
        const uint32_t Sv[4] = {S4[i].x, S4[i].y, S4[i].z, S4[i].w};
        const int h = i & 1, n = i >> 1;
        uint32_t Y[4];
#pragma unroll
        for (int j = 0; j < (n < 3 ? 4 : 2); j++) Y[j] = hadd2(R[h * 14 + 4 * n + j], hmul2(Sv[j], G[8 * n + 2 * j + h]));
        if (n < 3) stg128(p.out + oo + (h * 8 * D_ * 2 + n * 64), Y); else stg64(p.out + oq + h * 8 * D_ * 2, Y);
      }
      OBS(rel, 28);
    } else {
      asm volatile("setmaxnreg.inc.sync.aligned.u32 256;");
      float ka[56];
      {
        uint32_t X[28][4];
#pragma unroll
        for (int k = 0; k < 28; k++)
          ldsm4(X[k], base + OFF_X + (w4 * 16 + (mi & 1) * 8 + r8) * 896 + (k >> 2) * 128 + ((((2 * (k & 3) + (mi >> 1)) ^ ((k >> 2) - r8)) & 7) << 4));
        uint32_t all = 0;
#pragma unroll
        for (int k = 0; k < 28; k++) all |= X[k][0];
        if (lane == 0) mbar_arrive(bars + B_XF + all * threadIdx.y);
        mbar_wait(bars + B_F0, 0);
        LnC l[2];
        asm volatile("{\n.reg .pred p;\n.reg .u32 n, a, b;\nmov.u32 n, 0;\nLAB_LN:\n"
                     "ld.relaxed.gpu.global.v4.u32 {%0,%1,%2,a}, [%6];\nld.relaxed.gpu.global.v4.u32 {%3,%4,%5,b}, [%6+16];\n"
                     "setp.eq.u32 p, a, %7;\nsetp.eq.and.u32 p, b, %7, p;\nvote.sync.all.pred p, p, 0xffffffff;\n@p bra DONE;\n"
                     "add.u32 n, n, 1;\nsetp.lt.u32 p, n, 1000000;\n@p bra LAB_LN;\ntrap;\nDONE:\n}"
                     : "=&r"(l[0].m), "=&r"(l[0].rh), "=&r"(l[0].rl), "=&r"(l[1].m), "=&r"(l[1].rh), "=&r"(l[1].rl)
                     : "l"(p.scr + (SCR_LN + (mt * 64 + w4 * 16 + 2 * g) * 16)), "r"(get_tag()) : "memory");
        const int kc = mi & 1 ? 7 - r8 : r8;
        const uint32_t kst = keep(base + OFF_KV + (2 + 2 * w4 + (mi & 1)) * 1792 + (mi >> 1) * 128 + kc * 16);
        const uint32_t vst = keep(base + OFF_KV + KV + (2 + 2 * w4 + (kc >> 2)) * 1792 + (mi >> 1) * 128 + (((2 * kc) & 7) + ((mi & 1) ^ (kc >> 2))) * 16);
        int once = threadIdx.y;
#pragma unroll 1
        do {
#pragma unroll
          for (int k = 0; k < 112; k++) X[k >> 2][k & 3] = ln_apply(X[k >> 2][k & 3], l[k & 1]);
        } while (once--);
        float va[56];
        auto put = [&](const float (&a)[56], uint32_t dst, int i, int id) {
#pragma unroll
          for (int n = 2 * KP * i; n < 2 * KP * (i + 1) && n < 14; n += 2)
            if (i >= 0) stsm4(dst + n * 128, pack2(a[4 * n], a[4 * n + 1]), pack2(a[4 * n + 2], a[4 * n + 3]), pack2(a[4 * n + 4], a[4 * n + 5]), pack2(a[4 * n + 6], a[4 * n + 7]));
          if (i == (6 / KP | 3) && w4 == 3) named_arrive(id, 64);
        };
        named_sync(3, 256);
        fresh(ka);
        OBS0(0, 8);
#pragma unroll
        for (int c = 0; c < 7; c++) stage<2>(ka, 0, p.db, c, 0, ok, trc, c == 0, rel && c, nohook, &X[c * 4]);
        if (rel) mbar_arrive(bars + B_WO);
        fresh(va);
#pragma unroll
        for (int c = 7; c < 14; c++)
          stage<2>(va, 0, p.db, c & 7, c >> 3, ok, trc, c == 7, rel, [&](int k) { put(ka, kst, (c - 8) * 4 + k, 11); }, &X[(c - 7) * 4]);
        fresh(ka);
        OBS(rel, 9);
#pragma unroll
        for (int c = 14; c < 21; c++)
          stage<2>(ka, 0, p.db, c & 7, (c >> 3) & 1, ok, trc, c == 14, rel, [&](int k) {
            put(va, vst, (c - 15) * 4 + k, 0);
            if (c == 20 && k == 3 - HK) named_arrive(5, 256); }, &X[(c - 14) * 4]);
        smem_fence();
        wg_wait<0>();
        if (rel) mbar_arrive(bars + B_EMPTY + 4 * 8);
      }
      {
        uint32_t Q[8][4];
#pragma unroll
        for (int i = 0; i < 16; i++) {
          const int n = i - (i + 4) / 8;
#pragma unroll
          for (int h = 0; h < 2; h++) {
            const uint32_t v = pack2(ka[4 * n + 2 * h], ka[4 * n + 2 * h + 1]);
            Q[i >> 1][(i & 1) * 2 + h] = (i & 7) == 3 ? (t < 2 ? v : 0u) : ((i & 7) == 4 ? (t < 2 ? 0u : v) : v);
          }
        }
#pragma unroll
        for (int i = 0; i < 8; i++) pin(Q[i]);
        const bool in[2][2] = {{2 * t > g, 2 * t + 1 > g}, {7 - 2 * t > g, 6 - 2 * t > g}};
        const uint32_t zero = threadIdx.y, meta = 0x88dddd88u + zero;
        uint32_t M[2][5];
#pragma unroll
        for (int i = 0; i < 10; i++) {
          const uint32_t em = (in[i / 5][0] ? 0xffffu : 0u) | (in[i / 5][1] ? 0xffff0000u : 0u);
          M[i / 5][i % 5] = keep(i % 5 == w4 ? em : (i % 5 == w4 + 1 ? ~em : 0u));
        }
        float Sc[4][40], O[4][16];
        mbar_wait(bars + B_HALO, 0);
        OBS(rel, 11);
#pragma unroll
        for (int hh = 0; hh < 4; hh++) fresh(Sc[hh]);
        wg_fence();
        named_sync(N_GO, 256);
#pragma unroll
        for (int k = 0; k < 2; k++)
#pragma unroll
          for (int hh = 0; hh < 4; hh++) {
            if (k == 1 && hh == 3) named_arrive(N_DONE, 256);
            wgmma_rs_n80<0>(Sc[hh], Q[hh * 2 + k], dlo(OFF_KV + (hh * 7 / 2 + 2 * k) * 128, 128), p.dk, k);
          }
        wg_commit();
        uint32_t L[4][2];
        wg_wait<0>();
        OBS(rel, 12);
        auto pick = [&](int w) {
#pragma unroll
          for (int hh = 0; hh < 4; hh++)
#pragma unroll
            for (int h = 0; h < 2; h++) {
              const int i = (2 * w + h) * 4 + 2 * h;
              L[hh][h] = pack2(in[h][0] ? Sc[hh][i] : Sc[hh][i + 8], in[h][1] ? Sc[hh][i + 1] : Sc[hh][i + 9]);
              asm volatile("" : "+r"(L[hh][h]));
            }
        };
        if (w4 == 0) pick(0); else if (w4 == 1) pick(1); else if (w4 == 2) pick(2); else pick(3);
#pragma unroll
        for (int i = 0; i < 8; i++) L[i >> 1][i & 1] = hfma2(L[i >> 1][i & 1], 0x3e423e42u, hmul2(L[i >> 1][i & 1], 0xb9f7b9f7u));
        if (mt == 0) {
#pragma unroll
          for (int i = 0; i < 8; i++) { L[i >> 1][i & 1] = (L[i >> 1][i & 1] & ~M[i & 1][0]) | (0xce6ece6eu & M[i & 1][0]); asm volatile("" : "+r"(L[i >> 1][i & 1])); }
        }
        uint32_t A[4][3][4], mx[4];
        float P[8][2], sm[8];
#pragma unroll
        for (int hh = 0; hh < 4; hh++) mx[hh] = hmax2(__byte_perm(L[hh][0], L[hh][1], 0x5410), __byte_perm(L[hh][0], L[hh][1], 0x7632));
        const uint32_t x1 = 1 + ((mx[0] | mx[1] | mx[2] | mx[3]) & zero);
#pragma unroll
        for (int hh = 0; hh < 4; hh++) mx[hh] = hmax2(mx[hh], __shfl_xor_sync(0xffffffffu, mx[hh], x1));
#pragma unroll
        for (int hh = 0; hh < 4; hh++) mx[hh] = hmax2(mx[hh], __shfl_xor_sync(0xffffffffu, mx[hh], 2));
        uint32_t x2 = 0;
#pragma unroll
        for (int i = 0; i < 8; i++) {
          const float m = (i & 1 ? bf_hi(mx[i >> 1]) : bf_lo(mx[i >> 1])) * -LOG2E;
          P[i][0] = ex2_fast(fmaf(bf_lo(L[i >> 1][i & 1]), LOG2E, m)); P[i][1] = ex2_fast(fmaf(bf_hi(L[i >> 1][i & 1]), LOG2E, m));
          sm[i] = P[i][0] + P[i][1];
          x2 |= __float_as_uint(sm[i]);
        }
        x2 = 1 + (x2 & zero);
#pragma unroll
        for (int i = 0; i < 8; i++) sm[i] += __shfl_xor_sync(0xffffffffu, sm[i], x2);
#pragma unroll
        for (int i = 0; i < 8; i++) sm[i] += __shfl_xor_sync(0xffffffffu, sm[i], 2);
#pragma unroll
        for (int i = 0; i < 8; i++) {
          const float inv = rcp_fast(sm[i]);
          const uint32_t pp = pack2(P[i][0] * inv, P[i][1] * inv);
#pragma unroll
          for (int j = 0; j < 6; j++) A[i >> 1][j >> 1][(j & 1) * 2 + (i & 1)] = pp & (j == 4 ? zero : M[i & 1][j - (j > 4)]);
        }
#pragma unroll
        for (int hh = 0; hh < 4; hh++) fresh(O[hh]);
#pragma unroll
        for (int i = 0; i < 12; i++) pin(A[i / 3][i % 3]);
        OBS(rel, 13);
        mbar_wait(bars + B_HALO + 8, 0);
        OBS(rel, 31);
        named_sync(N_GO, 256);
        wg_fence();
        auto opair = [&](int m, int h2) {
          const int hb2 = m / 7 * 2, r = m % 7;
          if (r < 3) return pack2(O[hb2][4 * r + h2], O[hb2][4 * r + h2 + 1]);
          if (r == 3) return pack2(t < 2 ? O[hb2][12 + h2] : O[hb2 + 1][h2], t < 2 ? O[hb2][13 + h2] : O[hb2 + 1][h2 + 1]);
          return pack2(O[hb2 + 1][4 * (r - 3) + h2], O[hb2 + 1][4 * (r - 3) + h2 + 1]);
        };
        auto pv = [&](int hh, int j) { wgmma_sp_n32(O[hh], A[hh][j], dlo(OFF_KV + KV + hh * 7 / 2 * 128 + (j ? j + 1 : 0) * 3584, 1792), p.db, meta, j); };
#pragma unroll
        for (int i = 0; i < 12; i++) {
          if (i == 10) named_arrive(N_DONE, 256);
          pv(i & 3, i >> 2);
        }
        wg_commit();
        OBS(rel, 19);
        wg_wait<0>();
        OBS(rel, 21);
#pragma unroll
        for (int h = 0; h < 2; h++) {
          uint32_t U[14];
#pragma unroll
          for (int j = 0; j < 14; j++) U[j] = opair(h * 7 + (j >> 1), (j & 1) * 2);
          put_half(h, U);
          smem_fence();
          __syncwarp();
          if (lane == 0) mbar_arrive(bars + B_OS + h * 8);
        }
        if (w4 < NP_O) { wait_until(clock() + PH_O + w4 * 300); watch_flag(F_O, cnt(C_O + mt), 4); }
      }
      const uint32_t sx = keep(base + OFF_KV + w4 * 512 + (g >> 2) * 2048 + (g & 3) * 64 + t * 16);
      named_sync(8, 256);
      OBS0(49, 25);
      fresh(ka);
#pragma unroll
      for (int c = 49; c < 56; c++) stage<0>(ka, p.dx, p.db, c & 7, 0, ok, trc, c == 49, false, nohook);
      wg_wait<0>();
      OBS(rel, 27);
#pragma unroll
      for (int i = 0; i < 8; i++) {
        const float* a = ka + (i >> 1) * 16 + (i & 1) * 2;
        const uint32_t dst = (sx ^ ((i & 1) * 320)) + (i >> 1) * 4096, v0 = pack2(a[0], a[1]), v1 = pack2(a[4], a[5]);
        if (i < 6) sts128(dst, v0, v1, pack2(a[8], a[9]), pack2(a[12], a[13])); else sts64(dst, __uint_as_float(v0), __uint_as_float(v1));
      }
      named_arrive(12 + w4, 64);
    }
  }
}

typedef CUresult (*EncFn)(CUtensorMap*, CUtensorMapDataType, cuuint32_t, void*, const cuuint64_t*, const cuuint64_t*, const cuuint32_t*,
                          const cuuint32_t*, CUtensorMapInterleave, CUtensorMapSwizzle, CUtensorMapL2promotion, CUtensorMapFloatOOBfill);
void enc(EncFn f, CUtensorMap* m, const void* ptr, const cuuint64_t (&gd)[4], const cuuint64_t (&gs)[3], const cuuint32_t (&bx)[4], CUtensorMapSwizzle sw) {
  cuuint32_t es[4] = {1, 1, 1, 1};
  f(m, CU_TENSOR_MAP_DATA_TYPE_BFLOAT16, 4, (void*)ptr, gd, gs, bx, es, CU_TENSOR_MAP_INTERLEAVE_NONE, sw,
    CU_TENSOR_MAP_L2_PROMOTION_L2_128B, CU_TENSOR_MAP_FLOAT_OOB_FILL_NONE);
}
}

extern "C" void kernel_launch(void* const* d_in, const int* in_sizes, int n_in, void* d_out, int out_size) {
  (void)in_sizes; (void)n_in; (void)out_size;
  void* fp = nullptr;
  cudaDriverEntryPointQueryResult qr;
  cudaGetDriverEntryPoint("cuTensorMapEncodeTiled", &fp, cudaEnableDefault, &qr);
  EncFn f = (EncFn)fp;
  CUtensorMap m_w1, m_w2, m_b14, m_a8, m_b7, m_xt, m_wi;
  void* scr = nullptr;
  cudaGetSymbolAddress(&scr, g_scr);
  scr = (void*)((((uintptr_t)scr + PAGE - 1) & ~(uintptr_t)(PAGE - 1)) + -SCR_CNT);
  enc(f, &m_w1, d_in[4], {F_, 16, 1, S_ / 16}, {F_ * 2, F_ * 2, F_ * 32}, {64, 8, 1, 8}, CU_TENSOR_MAP_SWIZZLE_128B);
  {
    cuuint64_t gd[5] = {64, 7, 8, 2, S_ / 16}, gs[4] = {128, D_ * 4, D_ * 2, D_ * 32};
    cuuint32_t bx[5] = {64, 7, 8, 2, 4}, es[5] = {1, 1, 1, 1, 1};
    f(&m_xt, CU_TENSOR_MAP_DATA_TYPE_BFLOAT16, 5, d_in[0], gd, gs, bx, es, CU_TENSOR_MAP_INTERLEAVE_NONE, CU_TENSOR_MAP_SWIZZLE_128B,
      CU_TENSOR_MAP_L2_PROMOTION_L2_128B, CU_TENSOR_MAP_FLOAT_OOB_FILL_NONE);
  }
  enc(f, &m_w2, d_in[6], {S_, 1, 1, F_}, {S_ * 2, S_ * 2, S_ * 2}, {64, 1, 1, 64}, CU_TENSOR_MAP_SWIZZLE_128B);
  enc(f, &m_b14, scr, {64, 56, 1, G_END}, {128, GRP, GRP}, {64, 14, 1, 8}, CU_TENSOR_MAP_SWIZZLE_NONE);
  enc(f, &m_wi, d_in[1], {64, 21, 1, D_}, {128, D_ * 6, D_ * 6}, {64, 7, 1, 8}, CU_TENSOR_MAP_SWIZZLE_NONE);
  enc(f, &m_b7, scr, {64, 56, 1, G_END}, {128, GRP, GRP}, {64, 7, 1, 8}, CU_TENSOR_MAP_SWIZZLE_NONE);
  enc(f, &m_a8, scr, {64, 56, 1, G_END}, {128, GRP, GRP}, {64, 8, 1, 8}, CU_TENSOR_MAP_SWIZZLE_NONE);
  Params p;
  p.x = (const unsigned char*)d_in[0]; p.wo = (const unsigned char*)d_in[2];
  p.w1 = (const unsigned char*)d_in[4]; p.b1 = (const unsigned short*)d_in[5];
  p.w2 = (const unsigned char*)d_in[6]; p.b2 = (const unsigned short*)d_in[7];
  p.out = (unsigned char*)d_out; p.scr = (unsigned char*)scr;
  p.dw = 0x40000040u; p.dx = 64; p.db = 8; p.dk = 112;
  cudaFuncSetAttribute(fused_kernel, cudaFuncAttributeMaxDynamicSharedMemorySize, SMEM_BYTES);
  fused_kernel<<<128, NTHREADS, SMEM_BYTES, cudaStreamPerThread>>>(p, m_w1, m_w2, m_b14, m_a8, m_b7, m_xt, m_wi);
}
```

```cpp
#include <cuda_runtime.h>
#include <cuda.h>
#include <cuda_bf16.h>
#include <stdint.h>

template<int TA, int TB> __device__ __forceinline__ void wgmma_n112(float (&d)[56], uint32_t al, uint32_t ah, uint32_t bl, uint32_t bh, int sc) {
  asm volatile("{\n.reg .pred p;\n.reg .b64 a, b;\nsetp.ne.b32 p, %60, 0;\nmov.b64 a, {%56, %57};\nmov.b64 b, {%58, %59};\n"
    "wgmma.mma_async.sync.aligned.m64n112k16.f32.bf16.bf16 {%0, %1, %2, %3, %4, %5, %6, %7, %8, %9, %10, %11, %12, %13, %14, %15, %16, %17, %18, %19, %20, %21, %22, %23, %24, %25, %26, %27, %28, %29, %30, %31, %32, %33, %34, %35, %36, %37, %38, %39, %40, %41, %42, %43, %44, %45, %46, %47, %48, %49, %50, %51, %52, %53, %54, %55}, a, b, p, 1, 1, %61, %62;\n}\n"
    : "+f"(d[0]), "+f"(d[1]), "+f"(d[2]), "+f"(d[3]), "+f"(d[4]), "+f"(d[5]), "+f"(d[6]), "+f"(d[7]), "+f"(d[8]), "+f"(d[9]), "+f"(d[10]), "+f"(d[11]), "+f"(d[12]), "+f"(d[13]), "+f"(d[14]), "+f"(d[15]), "+f"(d[16]), "+f"(d[17]), "+f"(d[18]), "+f"(d[19]), "+f"(d[20]), "+f"(d[21]), "+f"(d[22]), "+f"(d[23]), "+f"(d[24]), "+f"(d[25]), "+f"(d[26]), "+f"(d[27]), "+f"(d[28]), "+f"(d[29]), "+f"(d[30]), "+f"(d[31]), "+f"(d[32]), "+f"(d[33]), "+f"(d[34]), "+f"(d[35]), "+f"(d[36]), "+f"(d[37]), "+f"(d[38]), "+f"(d[39]), "+f"(d[40]), "+f"(d[41]), "+f"(d[42]), "+f"(d[43]), "+f"(d[44]), "+f"(d[45]), "+f"(d[46]), "+f"(d[47]), "+f"(d[48]), "+f"(d[49]), "+f"(d[50]), "+f"(d[51]), "+f"(d[52]), "+f"(d[53]), "+f"(d[54]), "+f"(d[55])
    : "r"(al), "r"(ah), "r"(bl), "r"(bh), "r"(sc), "n"(TA), "n"(TB));
}

template<int TB> __device__ __forceinline__ void wgmma_rs_n80(float (&d)[40], const uint32_t (&a)[4], uint32_t bl, uint32_t bh, int sc) {
  asm volatile("{\n.reg .pred p;\n.reg .b64 b;\nsetp.ne.b32 p, %46, 0;\nmov.b64 b, {%44, %45};\n"
    "wgmma.mma_async.sync.aligned.m64n80k16.f32.bf16.bf16 {%0, %1, %2, %3, %4, %5, %6, %7, %8, %9, %10, %11, %12, %13, %14, %15, %16, %17, %18, %19, %20, %21, %22, %23, %24, %25, %26, %27, %28, %29, %30, %31, %32, %33, %34, %35, %36, %37, %38, %39}, {%40, %41, %42, %43}, b, p, 1, 1, %47;\n}\n"
    : "+f"(d[0]), "+f"(d[1]), "+f"(d[2]), "+f"(d[3]), "+f"(d[4]), "+f"(d[5]), "+f"(d[6]), "+f"(d[7]), "+f"(d[8]), "+f"(d[9]), "+f"(d[10]), "+f"(d[11]), "+f"(d[12]), "+f"(d[13]), "+f"(d[14]), "+f"(d[15]), "+f"(d[16]), "+f"(d[17]), "+f"(d[18]), "+f"(d[19]), "+f"(d[20]), "+f"(d[21]), "+f"(d[22]), "+f"(d[23]), "+f"(d[24]), "+f"(d[25]), "+f"(d[26]), "+f"(d[27]), "+f"(d[28]), "+f"(d[29]), "+f"(d[30]), "+f"(d[31]), "+f"(d[32]), "+f"(d[33]), "+f"(d[34]), "+f"(d[35]), "+f"(d[36]), "+f"(d[37]), "+f"(d[38]), "+f"(d[39])
    : "r"(a[0]), "r"(a[1]), "r"(a[2]), "r"(a[3]), "r"(bl), "r"(bh), "r"(sc), "n"(TB));
}

__device__ __forceinline__ void wgmma_sp_n32(float (&d)[16], const uint32_t (&a)[4], uint32_t bl, uint32_t bh, uint32_t meta, int sc) {
  asm volatile("{\n.reg .pred p;\n.reg .b64 b;\nsetp.ne.b32 p, %23, 0;\nmov.b64 b, {%20, %21};\n"
    "wgmma.mma_async.sp.sync.aligned.m64n32k32.f32.bf16.bf16 {%0, %1, %2, %3, %4, %5, %6, %7, %8, %9, %10, %11, %12, %13, %14, %15}, {%16, %17, %18, %19}, b, %22, 0, p, 1, 1, 1;\n}\n"
    : "+f"(d[0]), "+f"(d[1]), "+f"(d[2]), "+f"(d[3]), "+f"(d[4]), "+f"(d[5]), "+f"(d[6]), "+f"(d[7]), "+f"(d[8]), "+f"(d[9]), "+f"(d[10]), "+f"(d[11]), "+f"(d[12]), "+f"(d[13]), "+f"(d[14]), "+f"(d[15])
    : "r"(a[0]), "r"(a[1]), "r"(a[2]), "r"(a[3]), "r"(bl), "r"(bh), "r"(meta), "r"(sc));
}

template<int TB> __device__ __forceinline__ void wgmma_rs_n112(float (&d)[56], const uint32_t (&a)[4], uint32_t bl, uint32_t bh, int sc) {
  asm volatile("{\n.reg .pred p;\n.reg .b64 b;\nsetp.ne.b32 p, %62, 0;\nmov.b64 b, {%60, %61};\n"
    "wgmma.mma_async.sync.aligned.m64n112k16.f32.bf16.bf16 {%0, %1, %2, %3, %4, %5, %6, %7, %8, %9, %10, %11, %12, %13, %14, %15, %16, %17, %18, %19, %20, %21, %22, %23, %24, %25, %26, %27, %28, %29, %30, %31, %32, %33, %34, %35, %36, %37, %38, %39, %40, %41, %42, %43, %44, %45, %46, %47, %48, %49, %50, %51, %52, %53, %54, %55}, {%56, %57, %58, %59}, b, p, 1, 1, %63;\n}\n"
    : "+f"(d[0]), "+f"(d[1]), "+f"(d[2]), "+f"(d[3]), "+f"(d[4]), "+f"(d[5]), "+f"(d[6]), "+f"(d[7]), "+f"(d[8]), "+f"(d[9]), "+f"(d[10]), "+f"(d[11]), "+f"(d[12]), "+f"(d[13]), "+f"(d[14]), "+f"(d[15]), "+f"(d[16]), "+f"(d[17]), "+f"(d[18]), "+f"(d[19]), "+f"(d[20]), "+f"(d[21]), "+f"(d[22]), "+f"(d[23]), "+f"(d[24]), "+f"(d[25]), "+f"(d[26]), "+f"(d[27]), "+f"(d[28]), "+f"(d[29]), "+f"(d[30]), "+f"(d[31]), "+f"(d[32]), "+f"(d[33]), "+f"(d[34]), "+f"(d[35]), "+f"(d[36]), "+f"(d[37]), "+f"(d[38]), "+f"(d[39]), "+f"(d[40]), "+f"(d[41]), "+f"(d[42]), "+f"(d[43]), "+f"(d[44]), "+f"(d[45]), "+f"(d[46]), "+f"(d[47]), "+f"(d[48]), "+f"(d[49]), "+f"(d[50]), "+f"(d[51]), "+f"(d[52]), "+f"(d[53]), "+f"(d[54]), "+f"(d[55])
    : "r"(a[0]), "r"(a[1]), "r"(a[2]), "r"(a[3]), "r"(bl), "r"(bh), "r"(sc), "n"(TB));
}

namespace {
constexpr int S_ = 2048, D_ = 448, F_ = 1792;
constexpr int SLOT = 22528, BT = 14336;
constexpr int KV = 10 * 1792;
constexpr int OFF_KV = 8 * SLOT;
constexpr int OFF_X = OFF_KV - 64 * 896;
constexpr int OFF_U = OFF_KV + 2 * KV;
constexpr int OFF_PART = OFF_U + BT;
constexpr int OFF_BAR = OFF_PART + 768;
constexpr int SMEM_BYTES = OFF_BAR + 320;
constexpr uint32_t base = 1024, bars = base + OFF_BAR;
constexpr int DLY_X = 1200, DLY_D = 2600, DLY_E = 2500, DLY_P = 3200, DLY_W = 3100, TPW = 170, DLY_Q = 2000, PQ = 240;
constexpr int PF0 = 2800, PACE1 = 450, PACE2 = 330, PACE3 = 350, PFN = 23, PF1 = 600;
constexpr int SY_H = 750, SY_B = 1000, SY_C = 1000, SY_U = 1470, SY_O = 1150;
constexpr int NPB = 2, PS_H = 150, PS_O = 500, TUG = 430, TUH = 200, PB0 = 550, PK0 = 200, PU0 = 1300, PH_U = 300, NP_U = 2, PH_O = 800, NP_O = 3, NAP = 30;
constexpr int SA = 0, SB = 7, HK = 1, KP = 2;
constexpr int NTHREADS = 384;
constexpr float LOG2E = 1.4426950408889634f;

constexpr int GRP = 7168;
constexpr int G_H = 0, G_W = 256, G_U = G_W + 168, G_WO = G_U + 224, G_O = G_WO + 56, G_HALO = G_O + 256, G_END = G_HALO + 128;
constexpr int SCR_LN = -S_ * 16, SCR_CNT = -65536;
constexpr int C_H = 0, C_U = 2, C_W = 3, C_TICKET = 4, C_O = 5, C_HALO = 37, C_END = 165;
constexpr int PAGE = 2 << 20;
__device__ unsigned char g_scr[PAGE - SCR_CNT + G_END * GRP];

__device__ __forceinline__ uint32_t smem_u32(const void* p) { return (uint32_t)__cvta_generic_to_shared(p); }
__device__ __forceinline__ void mbar_init(uint32_t bar, uint32_t cnt) { asm volatile("mbarrier.init.shared::cta.b64 [%0], %1;" :: "r"(bar), "r"(cnt)); }
__device__ __forceinline__ void mbar_expect_tx(uint32_t bar, uint32_t bytes) { asm volatile("mbarrier.arrive.expect_tx.shared::cta.b64 _, [%0], %1;" :: "r"(bar), "r"(bytes) : "memory"); }
__device__ __forceinline__ void mbar_arrive(uint32_t bar) { asm volatile("mbarrier.arrive.shared::cta.b64 _, [%0];" :: "r"(bar) : "memory"); }
__device__ __forceinline__ void mbar_wait(uint32_t bar, uint32_t parity) {
  asm volatile("{\n.reg .pred p;\n.reg .u32 n;\nmov.u32 n, 0;\nLAB_WAIT:\n"
               "mbarrier.try_wait.parity.shared::cta.b64 p, [%0], %1;\n@p bra DONE;\n"
               "add.u32 n, n, 1;\nsetp.lt.u32 p, n, 4000000;\n@p bra LAB_WAIT;\ntrap;\nDONE:\n}" :: "r"(bar), "r"(parity) : "memory");
}
__device__ __forceinline__ void mbar_wait_u(uint32_t bar, uint32_t parity) {
  asm volatile("{\n.reg .pred p;\nLAB_WAIT:\nmbarrier.try_wait.parity.shared::cta.b64 p, [%0], %1;\n@!p bra LAB_WAIT;\n}" :: "r"(bar), "r"(parity) : "memory");
}
__device__ __forceinline__ uint32_t mbar_try(uint32_t bar, uint32_t parity) {
  uint32_t ok;
  asm volatile("{\n.reg .pred p;\nmbarrier.test_wait.parity.shared::cta.b64 p, [%1], %2;\nselp.u32 %0, 1, 0, p;\n}" : "=r"(ok) : "r"(bar), "r"(parity) : "memory");
  return ok;
}
__device__ __forceinline__ void tma4d(uint32_t dst, const CUtensorMap* m, int c0, int c1, int c3, uint32_t bar) {
  asm volatile("cp.async.bulk.tensor.4d.shared::cluster.global.mbarrier::complete_tx::bytes [%0], [%1, {%3, %4, %6, %5}], [%2];"
               :: "r"(dst), "l"(m), "r"(bar), "r"(c0), "r"(c1), "r"(c3), "r"(0) : "memory");
}
__device__ __forceinline__ void tma_store(const CUtensorMap* m, int c1, int c3, uint32_t src) {
  asm volatile("cp.async.bulk.tensor.4d.global.shared::cta.bulk_group [%0, {%4, %2, %4, %3}], [%1];" :: "l"(m), "r"(src), "r"(c1), "r"(c3), "r"(0) : "memory");
}
__device__ __forceinline__ void bulk_g2s(uint32_t dst, const void* src, uint32_t bytes, uint32_t bar) {
  asm volatile("cp.async.bulk.shared::cluster.global.mbarrier::complete_tx::bytes [%0], [%1], %2, [%3];" :: "r"(dst), "l"(src), "r"(bytes), "r"(bar) : "memory");
}
__device__ __forceinline__ void bulk_s2g(void* dst, uint32_t src, uint32_t bytes) {
  asm volatile("cp.async.bulk.global.shared::cta.bulk_group [%0], [%1], %2;" :: "l"(dst), "r"(src), "r"(bytes) : "memory");
}
__device__ __forceinline__ void wg_fence() { asm volatile("wgmma.fence.sync.aligned;" ::: "memory"); }
__device__ __forceinline__ void wg_commit() { asm volatile("wgmma.commit_group.sync.aligned;" ::: "memory"); }
template <int N> __device__ __forceinline__ void wg_wait() { asm volatile("wgmma.wait_group.sync.aligned %0;" :: "n"(N) : "memory"); }
__device__ __forceinline__ void smem_fence() { asm volatile("fence.proxy.async.shared::cta;" ::: "memory"); }
__device__ __forceinline__ bool elect() {
  uint32_t r; asm volatile("{\n.reg .pred p;\nelect.sync _|p, 0xffffffff;\nselp.u32 %0, 1, 0, p;\n}" : "=r"(r)); return r != 0;
}
__device__ __forceinline__ void trap_if(bool c) { asm volatile("{\n.reg .pred p;\nsetp.ne.u32 p, %0, 0;\n@p trap;\n}" :: "r"((uint32_t)c)); }
__device__ __forceinline__ uint32_t gtime() { uint32_t v; asm volatile("mov.u32 %0, %%globaltimer_lo;" : "=r"(v)); return v; }
__device__ __forceinline__ void wait_until(uint32_t tn) {
  asm volatile("{\n.reg .pred p;\n.reg .u32 c;\nLAB_T:\nmov.u32 c, %%clock;\nsub.u32 c, c, %0;\nsetp.lt.s32 p, c, 0;\n@p nanosleep.u32 20;\n@p bra LAB_T;\n}" :: "r"(tn) : "memory");
}
__device__ __forceinline__ void spin_until(uint32_t tn) {
  asm volatile("{\n.reg .pred p;\n.reg .u32 c;\nLAB_T:\nmov.u32 c, %%clock;\nsub.u32 c, c, %0;\nsetp.lt.s32 p, c, 0;\n@p bra LAB_T;\n}" :: "r"(tn) : "memory");
}
__device__ __forceinline__ uint32_t keep(uint32_t v) { return __shfl_sync(0xffffffffu, v, threadIdx.x & 31); }
__device__ __forceinline__ uint32_t ld_l2(const void* p) { uint32_t v; asm volatile("ld.relaxed.gpu.global.u32 %0, [%1];" : "=r"(v) : "l"(p) : "memory"); return v; }
__device__ __forceinline__ void bump(unsigned char* cnt) { asm volatile("red.relaxed.gpu.global.inc.u32 [%0], 0xffffffff;" :: "l"(cnt) : "memory"); }
__device__ __forceinline__ void mark(unsigned char* cnt) {
  asm volatile("red.relaxed.gpu.global.max.u32 [%0+4], %1;" :: "l"(cnt), "r"(gtime()) : "memory");
}
__device__ __forceinline__ void bulk_wait() {
  asm volatile("cp.async.bulk.commit_group;" ::: "memory");
  asm volatile("cp.async.bulk.wait_group 0;" ::: "memory");
}
__device__ __forceinline__ void publish(unsigned char* cnt) {
  asm volatile("cp.async.bulk.commit_group;" ::: "memory");
  mark(cnt);
  asm volatile("cp.async.bulk.wait_group 0;" ::: "memory");
  bump(cnt);
}
__device__ __forceinline__ void landed() { asm volatile("fence.proxy.async;" ::: "memory"); }
__device__ __forceinline__ void spin_ge(const unsigned char* cnt, unsigned target) {
  asm volatile("{\n.reg .pred p;\n.reg .u32 n, v;\nmov.u32 n, 0;\nLAB_SPIN:\n"
               "ld.relaxed.gpu.global.u32 v, [%0];\nsetp.ge.u32 p, v, %1;\n@p bra DONE;\n"
               "add.u32 n, n, 1;\nsetp.lt.u32 p, n, 4000000;\n@p bra LAB_SPIN;\ntrap;\nDONE:\n}" :: "l"(cnt), "r"(target) : "memory");
}
__device__ __forceinline__ uint4 lds128(uint32_t a) { uint4 v; asm volatile("ld.shared.v4.u32 {%0,%1,%2,%3}, [%4];" : "=r"(v.x), "=r"(v.y), "=r"(v.z), "=r"(v.w) : "r"(a) : "memory"); return v; }
__device__ __forceinline__ uint32_t lds32(uint32_t a) { uint32_t v; asm volatile("ld.volatile.shared.u32 %0, [%1];" : "=r"(v) : "r"(a) : "memory"); return v; }
__device__ __forceinline__ void sts32(uint32_t a, uint32_t v) { asm volatile("st.shared.u32 [%0], %1;" :: "r"(a), "r"(v) : "memory"); }
__device__ __forceinline__ void sts128(uint32_t p, uint32_t a, uint32_t b, uint32_t c, uint32_t d) { asm volatile("st.shared.v4.u32 [%0], {%1,%2,%3,%4};" :: "r"(p), "r"(a), "r"(b), "r"(c), "r"(d) : "memory"); }
__device__ __forceinline__ void sts64(uint32_t p, float a, float b) { asm volatile("st.shared.v2.f32 [%0], {%1,%2};" :: "r"(p), "f"(a), "f"(b) : "memory"); }
__device__ __forceinline__ void named_sync(int id, int n) { asm volatile("bar.sync %0, %1;" :: "r"(id), "r"(n) : "memory"); }
__device__ __forceinline__ void named_arrive(int id, int n) { asm volatile("bar.arrive %0, %1;" :: "r"(id), "r"(n) : "memory"); }
__device__ __forceinline__ constexpr uint32_t dlo(uint32_t off, uint32_t lbo) { return ((base + off) >> 4) | (lbo >> 4 << 16); }
__device__ __forceinline__ uint32_t pack2(float lo, float hi) { uint32_t r; asm("cvt.rn.bf16x2.f32 %0, %1, %2;" : "=r"(r) : "f"(hi), "f"(lo)); return r; }
__device__ __forceinline__ float bf_lo(uint32_t v) { return __uint_as_float(v << 16); }
__device__ __forceinline__ float bf_hi(uint32_t v) { return __uint_as_float(v & 0xffff0000u); }
__device__ __forceinline__ float rbf(float x) { return bf_lo(pack2(x, 0.f)); }
__device__ __forceinline__ uint32_t hsub2(uint32_t a, uint32_t b) { uint32_t r; asm("sub.rn.bf16x2 %0, %1, %2;" : "=r"(r) : "r"(a), "r"(b)); return r; }
__device__ __forceinline__ uint32_t hadd2(uint32_t a, uint32_t b) { uint32_t r; asm("add.rn.bf16x2 %0, %1, %2;" : "=r"(r) : "r"(a), "r"(b)); return r; }
__device__ __forceinline__ uint32_t hmax2(uint32_t a, uint32_t b) { uint32_t r; asm("max.bf16x2 %0, %1, %2;" : "=r"(r) : "r"(a), "r"(b)); return r; }
__device__ __forceinline__ uint32_t hmul2(uint32_t a, uint32_t b) { uint32_t r; asm("mul.rn.bf16x2 %0, %1, %2;" : "=r"(r) : "r"(a), "r"(b)); return r; }
__device__ __forceinline__ uint32_t hfma2(uint32_t a, uint32_t b, uint32_t c) { uint32_t r; asm("fma.rn.bf16x2 %0, %1, %2, %3;" : "=r"(r) : "r"(a), "r"(b), "r"(c)); return r; }
__device__ __forceinline__ float tanh_fast(float x) { float r; asm("tanh.approx.f32 %0, %1;" : "=f"(r) : "f"(x)); return r; }
__device__ __forceinline__ float rcp_fast(float x) { float r; asm("rcp.approx.ftz.f32 %0, %1;" : "=f"(r) : "f"(x)); return r; }
__device__ __forceinline__ float ex2_fast(float x) { float r; asm("ex2.approx.ftz.f32 %0, %1;" : "=f"(r) : "f"(x)); return r; }
__device__ __forceinline__ void ldsm4(uint32_t (&r)[4], uint32_t addr) {
  asm volatile("ldmatrix.sync.aligned.m8n8.x4.shared.b16 {%0,%1,%2,%3}, [%4];" : "=r"(r[0]), "=r"(r[1]), "=r"(r[2]), "=r"(r[3]) : "r"(addr) : "memory");
}
__device__ __forceinline__ void stsm4(uint32_t addr, uint32_t a, uint32_t b, uint32_t c, uint32_t d) {
  asm volatile("stmatrix.sync.aligned.m8n8.x4.shared.b16 [%0], {%1,%2,%3,%4};" :: "r"(addr), "r"(a), "r"(b), "r"(c), "r"(d) : "memory");
}
__device__ __forceinline__ void stsm2(uint32_t addr, uint32_t a, uint32_t b) {
  asm volatile("stmatrix.sync.aligned.m8n8.x2.shared.b16 [%0], {%1,%2};" :: "r"(addr), "r"(a), "r"(b) : "memory");
}
__device__ __forceinline__ void stg128(void* p, const uint32_t* r) { asm volatile("st.global.v4.u32 [%0], {%1,%2,%3,%4};" :: "l"(p), "r"(r[0]), "r"(r[1]), "r"(r[2]), "r"(r[3]) : "memory"); }
__device__ __forceinline__ void stg64(void* p, const uint32_t* r) { asm volatile("st.global.v2.u32 [%0], {%1,%2};" :: "l"(p), "r"(r[0]), "r"(r[1]) : "memory"); }
__device__ __forceinline__ void load_row(uint32_t (&r)[14], const unsigned char* p, int t) {
#pragma unroll
  for (int i = 0; i < 3; i++)
    asm volatile("ld.global.nc.L1::no_allocate.v4.u32 {%0,%1,%2,%3}, [%4];" : "=r"(r[4 * i]), "=r"(r[4 * i + 1]), "=r"(r[4 * i + 2]), "=r"(r[4 * i + 3]) : "l"(p + i * 64 + t * 16));
  asm volatile("ld.global.nc.L1::no_allocate.v2.u32 {%0,%1}, [%2];" : "=r"(r[12]), "=r"(r[13]) : "l"(p + 192 + (t & 1) * 16 + (t >> 1) * 8));
}
__device__ __forceinline__ void lds_row(uint32_t* r, uint32_t a, int t) {
#pragma unroll
  for (int i = 0; i < 3; i++) { const uint4 v = lds128(a + i * 64 + t * 16); r[4 * i] = v.x; r[4 * i + 1] = v.y; r[4 * i + 2] = v.z; r[4 * i + 3] = v.w; }
  asm volatile("ld.shared.v2.u32 {%0,%1}, [%2];" : "=r"(r[12]), "=r"(r[13]) : "r"(a + 192 + (t & 1) * 16 + (t >> 1) * 8) : "memory");
}
__device__ __forceinline__ void tile_row(uint32_t* r, int tok, int d, int t) {
  const int xi = (tok >> 1) & 7;
#pragma unroll
  for (int j = 0; j < 4; j++) {
    const int c = d * 14 + (j < 3 ? 4 * j + t : 12 + (t & 1));
    const uint4 v = lds128(base + OFF_X + ((tok & 48) + (tok & 1) * 8 + xi) * 896 + (c >> 3) * 128 + (((c ^ ((c >> 3) - xi)) & 7) << 4));
    if (j < 3) { r[4 * j] = v.x; r[4 * j + 1] = v.y; r[4 * j + 2] = v.z; r[4 * j + 3] = v.w; }
    else { r[12] = t >> 1 ? v.z : v.x; r[13] = t >> 1 ? v.w : v.y; }
  }
}

struct LnC { uint32_t m, rh, rl; float r; };
__device__ __forceinline__ LnC ln_consts(float mean, float var) {
  float sd;
  asm("sqrt.approx.ftz.f32 %0, %1;" : "=f"(sd) : "f"(rbf(rbf(var) + 1e-5f)));
  const float r = rcp_fast(rbf(sd)), rh = rbf(r);
  return {pack2(mean, mean), pack2(rh, rh), pack2(r - rh, r - rh), r};
}
__device__ __forceinline__ float variance(float mean, float sq) { return fmaxf(fmaf(-mean, mean, sq * (1.0f / D_)), 0.f); }
__device__ __forceinline__ uint32_t ln_apply(uint32_t x, const LnC& c) { const uint32_t d = hsub2(x, c.m); return hfma2(d, c.rh, hmul2(d, c.rl)); }

template <int N> __device__ __forceinline__ void fresh(float (&a)[N]) {
#pragma unroll
  for (int i = 0; i < N; i++) asm volatile("" : "=f"(a[i]));
}
__device__ __forceinline__ void pin(uint32_t (&a)[4]) { asm volatile("" : "+r"(a[0]), "+r"(a[1]), "+r"(a[2]), "+r"(a[3])); }
constexpr int B_EMPTY = 64, B_F0 = 128, B_F1 = 136, B_HALO = 144, B_WO = 160, B_XF = 168, B_X = 176, B_HL = 184, B_OS = 200, B_RL = 216, B_RS = 248, S_FLAG = 288;
constexpr int N_GO = 6, N_DONE = 7;
constexpr int F_H = 0, F_U = 2, F_O = 3;
__device__ __forceinline__ void watch_flag(int slot, const unsigned char* cnt, unsigned target) {
  asm volatile("{\n.reg .pred p;\n.reg .u32 n, v, t;\nmov.u32 n, 0;\nLAB_SPIN:\n"
               "ld.relaxed.gpu.global.v2.u32 {v, t}, [%1];\nsetp.ge.u32 p, v, %2;\n@p st.volatile.shared.v2.u32 [%0], {v, t};\n"
               "ld.volatile.shared.u32 v, [%0];\nsetp.ne.u32 p, v, 0;\n@p bra DONE;\n"
               "add.u32 n, n, 1;\nsetp.lt.u32 p, n, 4000000;\n@p bra LAB_SPIN;\ntrap;\nDONE:\n}" :: "r"(bars + S_FLAG + slot * 8), "l"(cnt), "r"(target) : "memory");
}
__device__ __forceinline__ uint32_t wait_flag(int slot, int delay = 0) {
  uint32_t v, last;
  while (true) {
    asm volatile("ld.volatile.shared.v2.u32 {%0, %1}, [%2];" : "=r"(v), "=r"(last) : "r"(bars + S_FLAG + slot * 8) : "memory");
    if (v) break;
    __nanosleep(NAP);
  }
  while (gtime() - last < (uint32_t)delay);
  return last;
}
__device__ __forceinline__ void arrive_if(int id, bool on) {
  asm volatile("{\n.reg .pred p;\nsetp.ne.u32 p, %1, 0;\n@p bar.arrive %0, 256;\n}" :: "r"(id), "r"((uint32_t)on) : "memory");
}
template <int TA, class Hook>
__device__ __forceinline__ void stage(float (&acc)[56], uint32_t ah, uint32_t bh, int sb, uint32_t par, uint32_t& ok, bool first, bool rel, Hook hook, const uint32_t (*X)[4] = nullptr) {
  if (!ok) mbar_wait(bars + sb * 8, par);
  wg_fence();
#pragma unroll
  for (int k = 0; k < 4; k++) {
    if constexpr (TA == 2) wgmma_rs_n112<1>(acc, X[k], dlo(sb * SLOT + 8192 + k * 3584, 1792), bh, k || !first);
    else wgmma_n112<TA, 1>(acc, dlo(sb * SLOT + k * (TA ? 2048 : 256), TA ? 8192 : 128), ah, dlo(sb * SLOT + 8192 + k * 3584, 1792), bh, k || !first);
    if (k == 1) ok = mbar_try(bars + ((sb + 1) & 7) * 8, sb == 7 ? par ^ 1 : par);
    hook(k);
  }
  wg_commit();
  wg_wait<1>();
  if (rel) mbar_arrive(bars + B_EMPTY + ((sb + 7) & 7) * 8);
}

struct Params {
  const unsigned char* x;
  unsigned char *scr, *out;
  uint32_t dw, dx, db, dk;
  const unsigned char *wo, *w1, *w2;
  const unsigned short *b1, *b2;
};

__global__ void __launch_bounds__(NTHREADS, 1)
fused_kernel(const Params p, const __grid_constant__ CUtensorMap m_w1, const __grid_constant__ CUtensorMap m_w2, const __grid_constant__ CUtensorMap m_b14,
             const __grid_constant__ CUtensorMap m_a8, const __grid_constant__ CUtensorMap m_b7, const __grid_constant__ CUtensorMap m_xt, const __grid_constant__ CUtensorMap m_wi) {
  extern __shared__ __align__(1024) unsigned char smem_raw[];
  const uint32_t t0 = clock();
  const int tid = threadIdx.x, lane = tid & 31, b = blockIdx.x;
  const int g = lane >> 2, t = lane & 3, r8 = lane & 7, mi = lane >> 3;
  uint32_t H[14];
  if (tid < 128) load_row(H, p.x + (b * 16 + g) * (D_ * 2) + (tid >> 5) * 224, t);
  const int warp = __shfl_sync(0xffffffffu, tid >> 5, 0);
  const int dt = b & 3, mt = b >> 2;
  const bool g1 = b < 112;
  const int kg0 = (mt & 3) * 14 + dt * 4, nk = dt < 3 ? 4 : 2;
  auto cnt = [&](int i) { return p.scr + (SCR_CNT + i * 128); };
  auto get_tag = [&]() { const uint32_t v = wait_flag(F_H); return ((v >> 5) & 0x3fffu) | (v >> 19 << 16); };
  auto tag_at = [&](int i) { return base + OFF_KV + i * KV + min(lane, 27) * 128 + (lane < 14 ? 0 : 112 - i * 16); };
  auto fetch_halo = [&](int i, uint32_t tag) {
    if (mt > 0) {
      const uint32_t tp = keep(tag_at(i));
      uint32_t ph = 0;
      spin_ge(cnt(C_HALO + b - 4), i + 1);
      do {
        trap_if(ph > 1000000);
        if (elect()) { mbar_expect_tx(bars + B_HL + i * 8, 3584); bulk_g2s(base + OFF_KV + i * KV, p.scr + ((G_HALO + b - 4) * GRP + i * 3584), 3584, bars + B_HL + i * 8); }
        mbar_wait(bars + B_HL + i * 8, ph++ & 1);
      } while (__any_sync(0xffffffffu, lds32(tp) != tag));
    }
    if (lane == 0) mbar_arrive(bars + B_HALO + i * 8);
  };
  if (warp >= 8) {
    if (warp == 8) {
      if (elect()) {
        asm volatile("prefetch.tensormap [%0];" :: "l"(&m_xt) : "memory");
        trap_if(smem_u32(smem_raw) != base);
#pragma unroll
        for (int i = 0; i < B_RL; i += 8) mbar_init(bars + i, i == B_XF ? 8 : i >= B_OS ? 4 : (i == B_HALO || i == B_HALO + 8 || ((i == B_F1 || i == B_WO) && !g1) ? 2 : 1));
        if (!g1) {
#pragma unroll
          for (int i = 0; i < 64; i += 8) mbar_init(bars + B_RL + i, i < 32 ? 1 : 4);
        }
#pragma unroll
        for (int i = 0; i < 32; i += 16) sts128(bars + S_FLAG + i, 0, 0, 0, 0);
        asm volatile("fence.mbarrier_init.release.cluster;" ::: "memory");
      }
      __syncwarp();
      named_arrive(12, 160); named_arrive(13, 160);
    }
    named_sync(15, 128);
    asm volatile("setmaxnreg.dec.sync.aligned.u32 80;");
    if (warp == 8) {
      if (elect()) {
        wait_until(t0 + DLY_X);
        mbar_expect_tx(bars + B_X, 64 * 896);
        asm volatile("cp.async.bulk.tensor.5d.shared::cluster.global.mbarrier::complete_tx::bytes [%0], [%1, {%4, %4, %4, %4, %3}], [%2];"
                     :: "r"(base + OFF_X), "l"(&m_xt), "r"(bars + B_X), "r"(mt * 4), "r"(0) : "memory");
        if (g1) {
          wait_until(t0 + DLY_D);
          asm volatile("prefetch.tensormap [%0];" :: "l"(&m_w1) : "memory");
          asm volatile("prefetch.tensormap [%0];" :: "l"(&m_b14) : "memory");
#pragma unroll 1
          for (int c = 0; c < 8; c++) {
            wait_until(t0 + DLY_W + c * TPW);
            if (c == 6) mbar_wait(bars + B_XF, 0);
            tma4d(base + c * SLOT, &m_w1, mt * 64, 0, c * 8, bars + c * 8);
          }
        } else {
          asm volatile("prefetch.tensormap [%0];" :: "l"(&m_wi) : "memory");
#pragma unroll 1
          for (int i = 0; i < 16; i++) {
            const int m = i >> 2, j = i & 3;
            if (j == 0) mbar_expect_tx(bars + B_RL + m * 8, nk * GRP);
            wait_until(t0 + DLY_Q + i * PQ);
            if (j >= nk) continue;
            if (m < 3) tma4d(base + i * GRP, &m_wi, 0, (m + 1) % 3 * 7, (kg0 + j) * 8, bars + B_RL + m * 8);
            else bulk_g2s(base + OFF_KV + j * GRP, p.wo + (kg0 + j) * GRP, GRP, bars + B_RL + 24);
          }
        }
#pragma unroll 1
        for (int r = g1 ? 1 : 4; r < 4; r++) {
#pragma unroll
          for (int s = 0; s < 8; s++) {
            mbar_wait_u(bars + B_EMPTY + s * 8, (r & 1) ^ 1);
            tma4d(base + s * SLOT, &m_w1, mt * 64, (r & 2) * 4, (r & 1) * 64 + s * 8, bars + s * 8);
          }
        }
        mbar_wait(bars + B_WO, 0);
#pragma unroll 1
        for (int r = 0; ; r++) {
#pragma unroll
          for (int j = 0; j < 8; j++) {
            const int s = (j + 5) & 7;
            mbar_wait_u(bars + B_EMPTY + s * 8, (r + (j < 3)) & 1);
            tma4d(base + s * SLOT, &m_w2, mt * 64, 0, r * 512 + j * 64, bars + s * 8);
            if (j == 3 && r == 3) goto w2_done;
          }
        }
        w2_done:
        wait_flag(F_O, SY_O);
#pragma unroll
        for (int s = 1; s < 8; s++) {
          mbar_wait_u(bars + B_EMPTY + s * 8, 1);
          tma4d(base + s * SLOT, &m_a8, 0, s * 8 - 8, G_O + mt * 8, bars + s * 8);
        }
      }
    } else if (warp == 9) {
      if (elect()) {
        const uint32_t early = ld_l2(cnt(C_H));
        wait_until(t0 + DLY_E);
        asm volatile("prefetch.tensormap [%0];" :: "l"(&m_b7) : "memory");
        asm volatile("prefetch.tensormap [%0];" :: "l"(&m_w2) : "memory");
        asm volatile("prefetch.tensormap [%0];" :: "l"(&m_a8) : "memory");
        uint32_t bytes = SLOT, tn;
        if (g1) {
#pragma unroll
          for (int s = 0; s < 8; s++) mbar_expect_tx(bars + s * 8, SLOT);
          if (early < 128) wait_until(t0 + DLY_P);
          watch_flag(F_H, cnt(C_H), 128);
          wait_flag(F_H, SY_H);
#pragma unroll
          for (int s = 0; s < 8; s++) {
            if (s == 5) mbar_wait(bars + B_XF, 0);
            tma4d(base + s * SLOT + 8192, &m_b14, 0, dt * 14, s * 8, bars + s * 8);
          }
        }
#pragma unroll 1
        for (int r = g1 ? 1 : 4; r < 11; r++) {
          if (r == 2) { mbar_wait(bars + B_F0, 0); }
          if (r == 4) { mbar_wait(bars + B_F1, 0); bytes = BT; }
#pragma unroll
          for (int s = 0; s < 8; s++) {
            if (s) mbar_wait_u(bars + B_EMPTY + s * 8, (r & 1) ^ 1); else mbar_wait(bars + B_EMPTY, (r & 1) ^ 1);
            if (s == 5 && r == 6) { bytes = SLOT; wait_flag(F_U, SY_U); tn = clock() + TUG; }
            if (s > 5 && r == 6) spin_until(tn + (s - 6) * TUH);
            mbar_expect_tx(bars + s * 8, bytes);
            tma4d(base + s * SLOT + 8192, &m_b14, 0, dt * 14, r * 64 + s * 8, bars + s * 8);
          }
        }
      }
    } else if (warp == 10) {
      uint32_t tn = t0 + PF0;
      const unsigned char* src = p.w1 + (b + b / 7 * 7) * 4096 + lane * 128;
#pragma unroll 1
      for (int i = g1 ? 0 : 32; i < 32; i++) {
        if (i == PFN) { wait_flag(F_U, PF1); tn = clock(); }
        wait_until(tn);
        if (i == 8) src -= 16 * 458752 - 8 * 3584;
        if (i == 16) src = p.w2 + b * 4096 + lane * 128;
        asm volatile("prefetch.global.L2 [%0];" :: "l"(src) : "memory");
        src += i < 16 ? 2 * 458752 : 458752;
        tn += i < 16 ? PACE1 : (i < PFN ? PACE2 : PACE3);
      }
      if (!g1 && elect()) {
#pragma unroll 1
        for (int m = 0; m < 3; m++) {
          mbar_wait(bars + B_RS + m * 8, 0);
          bulk_s2g(p.scr + (G_W + m * 56 + kg0) * GRP, base + (12 + m * 4) * GRP, nk * GRP);
        }
        bulk_wait();
        mbar_arrive(bars + B_F1);
        landed();
        bump(cnt(C_W));
        mbar_wait(bars + B_RS + 24, 0);
#pragma unroll 1
        for (int i = 0; i < nk; i++) bulk_s2g(p.scr + (G_WO + kg0 + i) * GRP, base + i * SLOT, GRP);
        bulk_wait();
        mbar_arrive(bars + B_WO);
        landed();
        bump(cnt(C_U));
      }
      __syncwarp();
      wait_flag(F_U);
      watch_flag(F_O, cnt(C_O + mt), 4);
      unsigned tk = 0;
      if (lane == 0) tk = atomicAdd((unsigned*)cnt(C_TICKET), 1);
      if (__any_sync(0xffffffffu, tk == 127)) {
#pragma unroll 1
        for (int i = lane; i < C_END; i += 32) *(uint2*)cnt(i) = make_uint2(0, 0);
      }
    } else {
      unsigned char* hg = p.scr + (G_H + b) * GRP;
      const uint32_t early = ld_l2(cnt(C_H + 1));
      if (mt == 0) {
#pragma unroll
        for (int i = 0; i < 14; i++) sts128(base + OFF_KV + (i / 7) * KV + (i % 7) * 512 + lane * 16, 0, 0, 0, 0);
      }
      named_sync(10, 160);
      smem_fence();
      if (elect()) { bulk_s2g(hg, base + OFF_U, GRP); publish(cnt(C_H)); }
      __syncwarp();
      named_sync(9, 160);
      if (!g1) {
        smem_fence();
        if (elect()) { bulk_s2g(hg + 128 * GRP, base + OFF_U + GRP, GRP); publish(cnt(C_H + 1)); }
        __syncwarp();
        watch_flag(F_H, cnt(C_H), 128);
      }
      const uint32_t tag = get_tag();
      if (lane < 16) sts32(base + OFF_PART + 512 + lane * 16 + 12, tag);
      smem_fence();
      __syncwarp();
      if (elect()) {
        bulk_s2g(p.scr + (SCR_LN + b * 256), base + OFF_PART + 512, 256);
        if (g1) {
          wait_flag(F_H, SY_B);
          const uint32_t tn = clock();
#pragma unroll
          for (int i = 0; i < NPB; i++) { if (i) wait_until(tn + i * PS_H); bulk_s2g(hg + (128 * GRP + i * (GRP / NPB)), base + OFF_U + GRP + i * (GRP / NPB), GRP / NPB); }
          publish(cnt(C_H + 1));
        }
      }
      __syncwarp();
      if (early < 128) wait_until(clock() + PB0);
      watch_flag(F_H + 1, cnt(C_H + 1), 128);
      wait_flag(F_H + 1, SY_C);
      if (lane == 0) mbar_arrive(bars + B_F0);
      spin_ge(cnt(C_W), 16);
      if (lane == 0) mbar_arrive(bars + B_F1);
      const uint32_t have = ld_l2(cnt(C_HALO + max(b - 4, 0)));
      if (g1) {
        named_sync(14, 160);
        smem_fence();
        if (elect()) tma_store(&m_b7, dt * 14, G_U + mt * 8, base + OFF_U);
        named_sync(10, 160);
        smem_fence();
        if (elect()) { tma_store(&m_b7, dt * 14 + 7, G_U + mt * 8, base + OFF_U + GRP); publish(cnt(C_U)); }
        __syncwarp();
      } else mbar_wait(bars + B_RS + 24, 0);
      if (!have) wait_until(clock() + PK0);
#pragma unroll 1
      for (int i = 0; i < 2; i++) fetch_halo(i, tag);
      if (elect()) {
        mbar_wait(bars + B_OS, 0);
        const uint32_t tn = clock() + PS_O;
        tma_store(&m_b7, dt * 14, G_O + mt * 8, base + OFF_U);
        mbar_wait(bars + B_OS + 8, 0);
        wait_until(tn);
        tma_store(&m_b7, dt * 14 + 7, G_O + mt * 8, base + OFF_U + GRP);
        publish(cnt(C_O + mt));
      }
    }
  } else {
    const int wg = warp >> 2, w4 = warp & 3;
    const bool rel = (tid & 127) == 0;
    auto put_row = [&](uint32_t st, const uint32_t* r) {
#pragma unroll
      for (int i = 0; i < 3; i++) stsm4(st + i * 512, r[4 * i], r[4 * i + 1], r[4 * i + 2], r[4 * i + 3]);
      stsm2(st + 1536, r[12], r[13]);
    };
    auto put_half = [&](int hf, const uint32_t* r) {
      const uint32_t st = base + OFF_U + hf * GRP + (w4 * 2 + (mi & 1)) * 896 + (mi >> 1) * 128 + r8 * 16;
#pragma unroll
      for (int j = 0; j < 3; j++) stsm4(st + j * 256, r[4 * j], r[4 * j + 1], r[4 * j + 2], r[4 * j + 3]);
      stsm2(st + 768, r[12], r[13]);
    };
    {
      if (wg) { named_sync(13, 160); mbar_wait(bars + B_X, 0); tile_row(H, dt * 16 + 8 + g, w4, t); }
      float mean, var;
      auto stats = [&](uint32_t part, auto shift) {
        float s0 = 0.f, s1 = 0.f, q0 = 0.f, q1 = 0.f;
#pragma unroll
        for (int j = 0; j < 14; j++) { const float a = shift(bf_lo(H[j])), c = shift(bf_hi(H[j])); s0 += a; s1 += c; q0 = fmaf(a, a, q0); q1 = fmaf(c, c, q1); }
        s0 += s1; q0 += q1;
#pragma unroll
        for (int o = 1; o < 4; o <<= 1) { s0 += __shfl_xor_sync(0xffffffffu, s0, o); q0 += __shfl_xor_sync(0xffffffffu, q0, o); }
        if (t == 0) sts64(part + w4 * 8, s0, q0);
        named_sync(1 + wg, 128);
        const uint4 u = lds128(part), v = lds128(part + 16);
        mean = ((__uint_as_float(u.x) + __uint_as_float(u.z)) + (__uint_as_float(v.x) + __uint_as_float(v.z))) * (1.0f / D_);
        var = variance(mean, (__uint_as_float(u.y) + __uint_as_float(u.w)) + (__uint_as_float(v.y) + __uint_as_float(v.w)));
      };
      stats(base + OFF_PART + wg * 256 + g * 32, [](float a) { return a; });
      if (__any_sync(0xffffffffu, mean * mean > 4.f * var)) {
        const float m0 = mean;
        stats(base + OFF_U - 512 + wg * 256 + g * 32, [&](float a) { return a - m0; });
        mean += m0;
      }
      const LnC l = ln_consts(mean, var), l2 = ln_consts((mean - bf_lo(l.m)) * l.r, var * l.r * l.r);
#pragma unroll
      for (int j = 0; j < 14; j++) H[j] = ln_apply(ln_apply(H[j], l), l2);
      put_row(base + OFF_U + warp * 1792 + lane * 16, H);
      if (w4 == 0 && t == 0) sts128(base + OFF_PART + 512 + wg * 128 + g * 16, l.m, l.rh, l.rl, 0);
      named_arrive(10 - wg, 160);
    }
    uint32_t ok = 0;
    auto nohook = [](int) {};
    if (wg == 0) {
      uint32_t hb[4], R[28];
      named_sync(12, 160);
#pragma unroll
      for (int i = 0; i < 4; i++)
        asm volatile("ld.relaxed.cta.global.u16 %0, [%1];" : "=r"(hb[i]) : "l"((i < 2 ? p.b1 + (g1 ? mt * 64 : 0) : p.b2 + mt * 64) + w4 * 16 + g + (i & 1) * 8) : "memory");
      mbar_wait(bars + B_X, 0);
#pragma unroll
      for (int h = 0; h < 2; h++) tile_row(R + h * 14, w4 * 16 + h * 8 + g, dt, t);
      if (lane == 0) mbar_arrive(bars + B_XF + (R[0] | R[4] | R[8] | R[12] | R[14] | R[18] | R[22] | R[26]) * threadIdx.y);
      float acc[56];
      if (g1) {
#pragma unroll
        for (int i = 0; i < 56; i++) { acc[i] = bf_lo(hb[(i >> 1) & 1]); asm volatile("" : "+f"(acc[i])); }
        ok = 0;
#pragma unroll 1
        for (int r = 0; r < 4; r++)
#pragma unroll
          for (int c = 0; c < 8; c++) stage<1>(acc, p.dw, p.db, c, r & 1, ok, false, rel && (c || r), [&](int k) { if (c == 7 && k == 3 - HK) arrive_if(3, r == 3); });
        wg_wait<0>();
        if (rel) mbar_arrive(bars + B_EMPTY + 7 * 8);
#pragma unroll
        for (int hf = 0; hf < 2; hf++) {
          uint32_t U[14];
#pragma unroll
          for (int j = 0; j < 14; j++) {
            const float a = acc[hf * 28 + 2 * j], c = acc[hf * 28 + 2 * j + 1];
            U[j] = pack2(fmaf(a, tanh_fast(a * fmaf(a * a, 0.0356774081f, 0.7978845608f)), a), fmaf(c, tanh_fast(c * fmaf(c * c, 0.0356774081f, 0.7978845608f)), c));
          }
          put_half(hf, U);
          named_arrive(hf ? 10 : 14, 160);
          if (!hf) mbar_wait(bars + B_X, 0);
        }
      } else {
#pragma unroll 1
        for (int m = 0; m < 3; m++) {
          mbar_wait(bars + B_RL + m * 8, 0);
          if (w4 < nk) {
            uint4 v[14];
#pragma unroll
            for (int l = 0; l < 14; l++) v[l] = lds128(base + (m * 4 + w4) * GRP + r8 * 896 + (l >> 1) * 128 + ((r8 + mi + (l & 1) * 4) & 7) * 16);
#pragma unroll
            for (int l = 0; l < 14; l++) sts128(base + (12 + m * 4 + w4) * GRP + (l >> 1) * 1024 + ((r8 + mi + (l & 1) * 4) & 7) * 128 + r8 * 16, v[l].x, v[l].y, v[l].z, v[l].w);
          }
          smem_fence();
          __syncwarp();
          if (lane == 0) mbar_arrive(bars + B_RS + m * 8);
          if (m == 0) mbar_wait(bars + B_XF, 0);
        }
        named_sync(1, 128);
        mbar_wait(bars + B_RL + 24, 0);
#pragma unroll 1
        for (int i = 0; i < nk; i++) {
          uint32_t W[14];
          lds_row(W, base + OFF_KV + i * GRP + g * 896 + w4 * 224, t);
          put_row(base + i * SLOT + w4 * 1792 + lane * 16, W);
        }
        smem_fence();
        __syncwarp();
        if (lane == 0) mbar_arrive(bars + B_RS + 24);
        named_sync(1, 128);
        named_arrive(3, 256);
      }
#pragma unroll
      for (int i = 0; i < 56; i++) { acc[i] = 0.f; asm volatile("" : "+f"(acc[i])); }
#pragma unroll
      for (int i = 2; i < 4; i++) hb[i] = keep(hmul2(hb[i] * 0x10001u, 0x3f003f00u));
      const uint32_t oo = keep((mt * 64 + w4 * 16 + g) * (D_ * 2) + dt * 224 + t * 16), oq = keep(oo + 192 - (t >> 1) * 24);
      const uint32_t sx = keep(base + OFF_KV + w4 * 512 + ((g & 1) * 4 + ((g >> 1) ^ (g & 1))) * 64 + t * 16);
      if (w4 == 3) {
        const uint32_t tag = get_tag();
#pragma unroll 1
        for (int i = 0; i < 2; i++) {
          const uint32_t tp = keep(tag_at(i) + 8 * 1792);
          named_sync(i ? 0 : 11, 64);
          if (mt < 31) {
            const uint32_t own = lds32(tp);
            sts32(tp, tag);
            smem_fence();
            __syncwarp();
            if (elect()) { bulk_s2g(p.scr + ((G_HALO + b) * GRP + i * 3584), base + OFF_KV + i * KV + 8 * 1792, 3584); bump(cnt(C_HALO + b)); bulk_wait(); }
            __syncwarp();
            sts32(tp, own);
            smem_fence();
            __syncwarp();
          }
          if (lane == 0) mbar_arrive(bars + B_HALO + i * 8);
        }
      } else if (w4 < NP_U) { wait_until(clock() + PU0 + w4 * PH_U); watch_flag(F_U, cnt(C_U), 128); }
      named_sync(5, 256);
      ok = 0;
#pragma unroll 1
      for (int r = 0; ; r++) {
#pragma unroll
        for (int j = 0; j < 8; j++) {
          const bool site = j == SA % 8 || j == SB % 8, yield = (j == SA % 8 && r == SA / 8) || (j == SB % 8 && r == SB / 8);
          stage<1>(acc, p.dw, p.db, (j + 5) & 7, (r + (j > 2)) & 1, ok, false, rel && (j || r), [&](int k) {
            if (k == 3 - HK) { if (site) arrive_if(N_GO, yield); if (j == 3) arrive_if(8, r == 3); } });
          if (site && yield) named_sync(N_DONE, 256);
          if (j == 3 && r == 3) goto gemm2_done;
        }
      }
      gemm2_done:
      wg_wait<0>();
      uint32_t G[28], dep = 0;
#pragma unroll
      for (int j = 0; j < 28; j++) {
        const uint32_t hh = hfma2(pack2(acc[2 * j], acc[2 * j + 1]), 0x3e803e80u, hb[2 + (j & 1)]);
        const float a = bf_lo(hh), c = bf_hi(hh);
        G[j] = pack2(fmaf(a, tanh_fast(a), a), fmaf(c, tanh_fast(c), c));
        dep |= G[j];
      }
      named_sync(12 + w4 + dep * threadIdx.y, 64);
      uint4 S4[8];
#pragma unroll
      for (int i = 0; i < 8; i++) S4[i] = lds128(sx + i * 2048);
#pragma unroll
      for (int i = 0; i < 8; i++) {
        const uint32_t Sv[4] = {S4[i].x, S4[i].y, S4[i].z, S4[i].w};
        const int h = i & 1, n = i >> 1;
        uint32_t Y[4];
#pragma unroll
        for (int j = 0; j < (n < 3 ? 4 : 2); j++) Y[j] = hadd2(R[h * 14 + 4 * n + j], hmul2(Sv[j], G[8 * n + 2 * j + h]));
        if (n < 3) stg128(p.out + oo + (h * 8 * D_ * 2 + n * 64), Y); else stg64(p.out + oq + h * 8 * D_ * 2, Y);
      }
    } else {
      asm volatile("setmaxnreg.inc.sync.aligned.u32 256;");
      float ka[56];
      const bool in[2][2] = {{2 * t > g, 2 * t + 1 > g}, {7 - 2 * t > g, 6 - 2 * t > g}};
      uint32_t M[2][5];
      auto mask = [&](int i) {
        const uint32_t em = (in[i / 5][0] ? 0xffffu : 0u) | (in[i / 5][1] ? 0xffff0000u : 0u);
        M[i / 5][i % 5] = keep(i % 5 == w4 ? em : (i % 5 == w4 + 1 ? ~em : 0u));
      };
      {
        uint32_t X[28][4];
#pragma unroll
        for (int k = 0; k < 28; k++)
          ldsm4(X[k], base + OFF_X + (w4 * 16 + (mi & 1) * 8 + r8) * 896 + (k >> 2) * 128 + ((((2 * (k & 3) + (mi >> 1)) ^ ((k >> 2) - r8)) & 7) << 4));
        uint32_t all = 0;
#pragma unroll
        for (int k = 0; k < 28; k++) all |= X[k][0];
        if (lane == 0) mbar_arrive(bars + B_XF + all * threadIdx.y);
        mbar_wait(bars + B_F0, 0);
        LnC l[2];
        asm volatile("{\n.reg .pred p;\n.reg .u32 n, a, b;\nmov.u32 n, 0;\nLAB_LN:\n"
                     "ld.relaxed.gpu.global.v4.u32 {%0,%1,%2,a}, [%6];\nld.relaxed.gpu.global.v4.u32 {%3,%4,%5,b}, [%6+16];\n"
                     "setp.eq.u32 p, a, %7;\nsetp.eq.and.u32 p, b, %7, p;\nvote.sync.all.pred p, p, 0xffffffff;\n@p bra DONE;\n"
                     "add.u32 n, n, 1;\nsetp.lt.u32 p, n, 1000000;\n@p bra LAB_LN;\ntrap;\nDONE:\n}"
                     : "=&r"(l[0].m), "=&r"(l[0].rh), "=&r"(l[0].rl), "=&r"(l[1].m), "=&r"(l[1].rh), "=&r"(l[1].rl)
                     : "l"(p.scr + (SCR_LN + (mt * 64 + w4 * 16 + 2 * g) * 16)), "r"(get_tag()) : "memory");
        const int kc = mi & 1 ? 7 - r8 : r8;
        const uint32_t kst = keep(base + OFF_KV + (2 + 2 * w4 + (mi & 1)) * 1792 + (mi >> 1) * 128 + kc * 16);
        const uint32_t vst = keep(base + OFF_KV + KV + (2 + 2 * w4 + (kc >> 2)) * 1792 + (mi >> 1) * 128 + (((2 * kc) & 7) + ((mi & 1) ^ (kc >> 2))) * 16);
        int once = threadIdx.y;
#pragma unroll 1
        do {
#pragma unroll
          for (int k = 0; k < 112; k++) X[k >> 2][k & 3] = ln_apply(X[k >> 2][k & 3], l[k & 1]);
        } while (once--);
        float va[56];
        auto put = [&](const float (&a)[56], uint32_t dst, int i, int id) {
#pragma unroll
          for (int n = 2 * KP * i; n < 2 * KP * (i + 1) && n < 14; n += 2)
            if (i >= 0) stsm4(dst + n * 128, pack2(a[4 * n], a[4 * n + 1]), pack2(a[4 * n + 2], a[4 * n + 3]), pack2(a[4 * n + 4], a[4 * n + 5]), pack2(a[4 * n + 6], a[4 * n + 7]));
          if (i == (6 / KP | 3) && w4 == 3) named_arrive(id, 64);
        };
        named_sync(3, 256);
        fresh(ka);
        ok = 0;
#pragma unroll
        for (int c = 0; c < 7; c++) stage<2>(ka, 0, p.db, c, 0, ok, c == 0, rel && c, nohook, &X[c * 4]);
        if (rel) mbar_arrive(bars + B_WO);
        fresh(va);
#pragma unroll
        for (int c = 7; c < 14; c++)
          stage<2>(va, 0, p.db, c & 7, c >> 3, ok, c == 7, rel, [&](int k) { put(ka, kst, (c - 8) * 4 + k, 11); }, &X[(c - 7) * 4]);
        fresh(ka);
#pragma unroll
        for (int c = 14; c < 21; c++)
          stage<2>(ka, 0, p.db, c & 7, (c >> 3) & 1, ok, c == 14, rel, [&](int k) {
            put(va, vst, (c - 15) * 4 + k, 0);
            if (c > 16 && (c - 17) * 4 + k < 10) mask((c - 17) * 4 + k);
            if (c == 20 && k == 3 - HK) named_arrive(5, 256); }, &X[(c - 14) * 4]);
        smem_fence();
        wg_wait<0>();
        if (rel) mbar_arrive(bars + B_EMPTY + 4 * 8);
      }
      {
        uint32_t Q[8][4];
#pragma unroll
        for (int i = 0; i < 16; i++) {
          const int n = i - (i + 4) / 8;
#pragma unroll
          for (int h = 0; h < 2; h++) {
            const uint32_t v = pack2(ka[4 * n + 2 * h], ka[4 * n + 2 * h + 1]);
            Q[i >> 1][(i & 1) * 2 + h] = (i & 7) == 3 ? (t < 2 ? v : 0u) : ((i & 7) == 4 ? (t < 2 ? 0u : v) : v);
          }
        }
#pragma unroll
        for (int i = 0; i < 8; i++) pin(Q[i]);
        const uint32_t zero = threadIdx.y, meta = 0x88dddd88u + zero;
        float Sc[4][40], O[4][16];
        mbar_wait(bars + B_HALO, 0);
#pragma unroll
        for (int hh = 0; hh < 4; hh++) fresh(Sc[hh]);
        wg_fence();
        named_sync(N_GO, 256);
#pragma unroll
        for (int k = 0; k < 2; k++)
#pragma unroll
          for (int hh = 0; hh < 4; hh++) {
            if (k == 1 && hh == 3) named_arrive(N_DONE, 256);
            wgmma_rs_n80<0>(Sc[hh], Q[hh * 2 + k], dlo(OFF_KV + (hh * 7 / 2 + 2 * k) * 128, 128), p.dk, k);
          }
        wg_commit();
        uint32_t L[4][2];
        wg_wait<0>();
        auto pick = [&](int w) {
#pragma unroll
          for (int hh = 0; hh < 4; hh++)
#pragma unroll
            for (int h = 0; h < 2; h++) {
              const int i = (2 * w + h) * 4 + 2 * h;
              L[hh][h] = pack2(in[h][0] ? Sc[hh][i] : Sc[hh][i + 8], in[h][1] ? Sc[hh][i + 1] : Sc[hh][i + 9]);
              asm volatile("" : "+r"(L[hh][h]));
            }
        };
        if (w4 == 0) pick(0); else if (w4 == 1) pick(1); else if (w4 == 2) pick(2); else pick(3);
#pragma unroll
        for (int i = 0; i < 8; i++) L[i >> 1][i & 1] = hfma2(L[i >> 1][i & 1], 0x3e423e42u, hmul2(L[i >> 1][i & 1], 0xb9f7b9f7u));
        if (mt == 0) {
#pragma unroll
          for (int i = 0; i < 8; i++) { L[i >> 1][i & 1] = (L[i >> 1][i & 1] & ~M[i & 1][0]) | (0xce6ece6eu & M[i & 1][0]); asm volatile("" : "+r"(L[i >> 1][i & 1])); }
        }
        uint32_t A[4][3][4], mx[4];
        float P[8][2], sm[8];
#pragma unroll
        for (int hh = 0; hh < 4; hh++) mx[hh] = hmax2(__byte_perm(L[hh][0], L[hh][1], 0x5410), __byte_perm(L[hh][0], L[hh][1], 0x7632));
        const uint32_t x1 = 1 + ((mx[0] | mx[1] | mx[2] | mx[3]) & zero);
#pragma unroll
        for (int hh = 0; hh < 4; hh++) mx[hh] = hmax2(mx[hh], __shfl_xor_sync(0xffffffffu, mx[hh], x1));
#pragma unroll
        for (int hh = 0; hh < 4; hh++) mx[hh] = hmax2(mx[hh], __shfl_xor_sync(0xffffffffu, mx[hh], 2));
        uint32_t x2 = 0;
#pragma unroll
        for (int i = 0; i < 8; i++) {
          const float m = (i & 1 ? bf_hi(mx[i >> 1]) : bf_lo(mx[i >> 1])) * -LOG2E;
          P[i][0] = ex2_fast(fmaf(bf_lo(L[i >> 1][i & 1]), LOG2E, m)); P[i][1] = ex2_fast(fmaf(bf_hi(L[i >> 1][i & 1]), LOG2E, m));
          sm[i] = P[i][0] + P[i][1];
          x2 |= __float_as_uint(sm[i]);
        }
        x2 = 1 + (x2 & zero);
#pragma unroll
        for (int i = 0; i < 8; i++) sm[i] += __shfl_xor_sync(0xffffffffu, sm[i], x2);
#pragma unroll
        for (int i = 0; i < 8; i++) sm[i] += __shfl_xor_sync(0xffffffffu, sm[i], 2);
#pragma unroll
        for (int i = 0; i < 8; i++) {
          const float inv = rcp_fast(sm[i]);
          const uint32_t pp = pack2(P[i][0] * inv, P[i][1] * inv);
#pragma unroll
          for (int j = 0; j < 6; j++) A[i >> 1][j >> 1][(j & 1) * 2 + (i & 1)] = pp & (j == 4 ? zero : M[i & 1][j - (j > 4)]);
        }
#pragma unroll
        for (int hh = 0; hh < 4; hh++) fresh(O[hh]);
#pragma unroll
        for (int i = 0; i < 12; i++) pin(A[i / 3][i % 3]);
        mbar_wait(bars + B_HALO + 8, 0);
        named_sync(N_GO, 256);
        wg_fence();
        auto opair = [&](int m, int h2) {
          const int hb2 = m / 7 * 2, r = m % 7;
          if (r < 3) return pack2(O[hb2][4 * r + h2], O[hb2][4 * r + h2 + 1]);
          if (r == 3) return pack2(t < 2 ? O[hb2][12 + h2] : O[hb2 + 1][h2], t < 2 ? O[hb2][13 + h2] : O[hb2 + 1][h2 + 1]);
          return pack2(O[hb2 + 1][4 * (r - 3) + h2], O[hb2 + 1][4 * (r - 3) + h2 + 1]);
        };
        auto pv = [&](int hh, int j) { wgmma_sp_n32(O[hh], A[hh][j], dlo(OFF_KV + KV + hh * 7 / 2 * 128 + (j ? j + 1 : 0) * 3584, 1792), p.db, meta, j); };
#pragma unroll
        for (int i = 0; i < 12; i++) {
          if (i == 10) named_arrive(N_DONE, 256);
          pv(i & 3, i >> 2);
        }
        wg_commit();
        wg_wait<0>();
#pragma unroll
        for (int h = 0; h < 2; h++) {
          uint32_t U[14];
#pragma unroll
          for (int j = 0; j < 14; j++) U[j] = opair(h * 7 + (j >> 1), (j & 1) * 2);
          put_half(h, U);
          smem_fence();
          __syncwarp();
          if (lane == 0) mbar_arrive(bars + B_OS + h * 8);
        }
        if (w4 < NP_O) { wait_until(clock() + PH_O + w4 * 300); watch_flag(F_O, cnt(C_O + mt), 4); }
      }
      const uint32_t sx = keep(base + OFF_KV + w4 * 512 + (g >> 2) * 2048 + (g & 3) * 64 + t * 16);
      named_sync(8, 256);
      ok = 0;
      fresh(ka);
#pragma unroll
      for (int c = 49; c < 56; c++) stage<0>(ka, p.dx, p.db, c & 7, 0, ok, c == 49, false, nohook);
      wg_wait<0>();
#pragma unroll
      for (int i = 0; i < 8; i++) {
        const float* a = ka + (i >> 1) * 16 + (i & 1) * 2;
        const uint32_t dst = (sx ^ ((i & 1) * 320)) + (i >> 1) * 4096, v0 = pack2(a[0], a[1]), v1 = pack2(a[4], a[5]);
        if (i < 6) sts128(dst, v0, v1, pack2(a[8], a[9]), pack2(a[12], a[13])); else sts64(dst, __uint_as_float(v0), __uint_as_float(v1));
      }
      named_arrive(12 + w4, 64);
    }
  }
}

typedef CUresult (*EncFn)(CUtensorMap*, CUtensorMapDataType, cuuint32_t, void*, const cuuint64_t*, const cuuint64_t*, const cuuint32_t*,
                          const cuuint32_t*, CUtensorMapInterleave, CUtensorMapSwizzle, CUtensorMapL2promotion, CUtensorMapFloatOOBfill);
void enc(EncFn f, CUtensorMap* m, const void* ptr, const cuuint64_t (&gd)[4], const cuuint64_t (&gs)[3], const cuuint32_t (&bx)[4], CUtensorMapSwizzle sw) {
  cuuint32_t es[4] = {1, 1, 1, 1};
  f(m, CU_TENSOR_MAP_DATA_TYPE_BFLOAT16, 4, (void*)ptr, gd, gs, bx, es, CU_TENSOR_MAP_INTERLEAVE_NONE, sw,
    CU_TENSOR_MAP_L2_PROMOTION_L2_128B, CU_TENSOR_MAP_FLOAT_OOB_FILL_NONE);
}
}

extern "C" void kernel_launch(void* const* d_in, const int* in_sizes, int n_in, void* d_out, int out_size) {
  (void)in_sizes; (void)n_in; (void)out_size;
  void* fp = nullptr;
  cudaDriverEntryPointQueryResult qr;
  cudaGetDriverEntryPoint("cuTensorMapEncodeTiled", &fp, cudaEnableDefault, &qr);
  EncFn f = (EncFn)fp;
  CUtensorMap m_w1, m_w2, m_b14, m_a8, m_b7, m_xt, m_wi;
  void* scr = nullptr;
  cudaGetSymbolAddress(&scr, g_scr);
  scr = (void*)((((uintptr_t)scr + PAGE - 1) & ~(uintptr_t)(PAGE - 1)) + -SCR_CNT);
  enc(f, &m_w1, d_in[4], {F_, 16, 1, S_ / 16}, {F_ * 2, F_ * 2, F_ * 32}, {64, 8, 1, 8}, CU_TENSOR_MAP_SWIZZLE_128B);
  {
    cuuint64_t gd[5] = {64, 7, 8, 2, S_ / 16}, gs[4] = {128, D_ * 4, D_ * 2, D_ * 32};
    cuuint32_t bx[5] = {64, 7, 8, 2, 4}, es[5] = {1, 1, 1, 1, 1};
    f(&m_xt, CU_TENSOR_MAP_DATA_TYPE_BFLOAT16, 5, d_in[0], gd, gs, bx, es, CU_TENSOR_MAP_INTERLEAVE_NONE, CU_TENSOR_MAP_SWIZZLE_128B,
      CU_TENSOR_MAP_L2_PROMOTION_L2_128B, CU_TENSOR_MAP_FLOAT_OOB_FILL_NONE);
  }
  enc(f, &m_w2, d_in[6], {S_, 1, 1, F_}, {S_ * 2, S_ * 2, S_ * 2}, {64, 1, 1, 64}, CU_TENSOR_MAP_SWIZZLE_128B);
  enc(f, &m_b14, scr, {64, 56, 1, G_END}, {128, GRP, GRP}, {64, 14, 1, 8}, CU_TENSOR_MAP_SWIZZLE_NONE);
  enc(f, &m_wi, d_in[1], {64, 21, 1, D_}, {128, D_ * 6, D_ * 6}, {64, 7, 1, 8}, CU_TENSOR_MAP_SWIZZLE_NONE);
  enc(f, &m_b7, scr, {64, 56, 1, G_END}, {128, GRP, GRP}, {64, 7, 1, 8}, CU_TENSOR_MAP_SWIZZLE_NONE);
  enc(f, &m_a8, scr, {64, 56, 1, G_END}, {128, GRP, GRP}, {64, 8, 1, 8}, CU_TENSOR_MAP_SWIZZLE_NONE);
  Params p;
  p.x = (const unsigned char*)d_in[0]; p.wo = (const unsigned char*)d_in[2];
  p.w1 = (const unsigned char*)d_in[4]; p.b1 = (const unsigned short*)d_in[5];
  p.w2 = (const unsigned char*)d_in[6]; p.b2 = (const unsigned short*)d_in[7];
  p.out = (unsigned char*)d_out; p.scr = (unsigned char*)scr;
  p.dw = 0x40000040u; p.dx = 64; p.db = 8; p.dk = 112;
  cudaFuncSetAttribute(fused_kernel, cudaFuncAttributeMaxDynamicSharedMemorySize, SMEM_BYTES);
  fused_kernel<<<128, NTHREADS, SMEM_BYTES, cudaStreamPerThread>>>(p, m_w1, m_w2, m_b14, m_a8, m_b7, m_xt, m_wi);
}
```
